```python
import torch

def _softmax(x, axis=-1):
    return torch.softmax(x, dim=axis)

def _gelu(x):
    return torch.nn.functional.gelu(x, approximate='tanh')

def _silu(x):
    return torch.nn.functional.silu(x)

def _sigmoid(x):
    return torch.sigmoid(x)

def _layernorm(x, axis=-1, eps=1e-05):
    m = x.mean(dim=axis, keepdim=True)
    v = x.var(dim=axis, keepdim=True, unbiased=False)
    return (x - m) / torch.sqrt(v + eps)

def _scatter_add(tgt, idx, src, axis=0):
    return tgt.clone().index_add_(axis, idx, src)

def _segment_sum(src, seg, n):
    out = torch.zeros((n,) + src.shape[1:], dtype=src.dtype)
    return out.index_add_(0, seg, src)

def _pad(x, pw):
    flat = tuple((v for pair in reversed(pw) for v in pair))
    return torch.nn.functional.pad(x, flat)
kernel_name = 'concat_heads__spectral_gfnet__memory_aug_recurrent_mem_tr__prompt'

def setup_inputs():

    _w = lambda a: (lambda t: t.to(torch.bfloat16) if t.is_floating_point() else t)(torch.as_tensor(a))

    def _A_setup():
        B, S, D = (1, 2048, 1024)
        Df = D // 2 + 1
        return {'x': _w((lambda *s: torch.randn(*s, dtype=torch.bfloat16) * 0.05)(B, S, D)), 'w_r': _w((lambda *s: torch.randn(*s, dtype=torch.bfloat16) * 3.2)(S, Df) * 0.02), 'w_i': _w((lambda *s: torch.randn(*s, dtype=torch.bfloat16) * 3.2)(S, Df) * 0.02)}
    _A_in = _A_setup()

    def _B_setup():
        B, S, Dm = (1, 2048, 1024)
        H, Dh = (32, 128)
        M, seg = (8, 32)
        seg = min(seg, S)
        S = S // seg * seg
        return {'x': _w((lambda *s: torch.randn(*s, dtype=torch.bfloat16) * 0.05)(B, S, Dm)), 'mem0': _w((lambda *s: torch.randn(*s, dtype=torch.bfloat16) * 0.4)(B, M, Dm)), 'Wq': _w((lambda *s: torch.randn(*s, dtype=torch.bfloat16) * 6.4)(Dm, H, Dh) * Dm ** (-0.5)), 'Wk': _w((lambda *s: torch.randn(*s, dtype=torch.bfloat16) * 6.4)(Dm, H, Dh) * Dm ** (-0.5)), 'Wv': _w((lambda *s: torch.randn(*s, dtype=torch.bfloat16) * 0.4)(Dm, H, Dh) * Dm ** (-0.5)), 'Wo': _w((lambda *s: torch.randn(*s, dtype=torch.bfloat16) * 0.4)(H, Dh, Dm) * (H * Dh) ** (-0.5)), 'seg_len': seg}
    _B_in = _B_setup()
    return {'A_x': _A_in['x'], 'A_w_r': _A_in['w_r'], 'A_w_i': _A_in['w_i'], 'B_x': _B_in['x'], 'B_mem0': _B_in['mem0'], 'B_Wq': _B_in['Wq'], 'B_Wk': _B_in['Wk'], 'B_Wv': _B_in['Wv'], 'B_Wo': _B_in['Wo'], 'B_seg_len': _B_in['seg_len']}

def reference(A_x, A_w_r, A_w_i, B_x, B_mem0, B_Wq, B_Wk, B_Wv, B_Wo, B_seg_len):

    def _A_ref(x, w_r, w_i):
        B, S, D = x.shape
        X = (lambda x, axes=(-2, -1): torch.fft.rfft2(x.float(), dim=axes))(x, axes=(-2, -1))
        W = w_r + 1j * w_i
        X = X * W
        y = (lambda x, s, axes=(-2, -1): torch.fft.irfft2(x, s=s, dim=axes).to(torch.bfloat16))(X, (S, D), axes=(-2, -1))
        return y

    def _B_ref(x, mem0, Wq, Wk, Wv, Wo, seg_len):
        B, S, Dm = x.shape
        H, Dh = (Wq.shape[1], Wq.shape[2])
        M = mem0.shape[1]
        scale = Dh ** (-0.5)
        n_seg = S // seg_len
        L = M + seg_len
        idx = torch.arange(L)
        mask = (idx[:, None] < M) | (idx[:, None] >= idx[None, :])
        mem = mem0
        outs = []
        for s in range(n_seg):
            xs = x[:, s * seg_len:(s + 1) * seg_len, :].clone()
            h = torch.concatenate([mem, xs], axis=1)
            q = torch.einsum('btd,dhe->bhte', h, Wq)
            k = torch.einsum('btd,dhe->bhte', h, Wk)
            v = torch.einsum('btd,dhe->bhte', h, Wv)
            scores = torch.einsum('bhqe,bhke->bhqk', q, k) * scale
            scores = torch.where(mask[None, None], scores, -1000000000.0)
            p = _softmax(scores, axis=-1)
            o = torch.einsum('bhqk,bhke->bhqe', p, v)
            o = torch.einsum('bhte,hed->btd', o, Wo)
            mem = o[:, :M, :].clone()
            outs.append(o[:, M:, :])
        return torch.concatenate(outs, axis=1)
    a = _A_ref(A_x, A_w_r, A_w_i)
    b = _B_ref(B_x, B_mem0, B_Wq, B_Wk, B_Wv, B_Wo, B_seg_len)
    return torch.concatenate([a, b], axis=-1)
```

```cpp
#include <cuda_runtime.h>
#include <cuda_bf16.h>
#include <cuda.h>
#include <stdint.h>

typedef __nv_bfloat16 bf16;

#define DBG_TIMING 0

#define SPIN_LIMIT (1u << 22)

__device__ __forceinline__ uint32_t smem_u32(const void* p) { return (uint32_t)__cvta_generic_to_shared(p); }
__device__ __forceinline__ uint32_t clk() { uint32_t c; asm volatile("mov.u32 %0, %%clock;" : "=r"(c)::"memory"); return c; }
__device__ __forceinline__ void wait_clk(uint32_t t0, uint32_t d) { while (clk() - t0 < d) {} }

__device__ __forceinline__ void mbar_init(uint32_t bar, uint32_t cnt) {
    asm volatile("mbarrier.init.shared::cta.b64 [%0], %1;" ::"r"(bar), "r"(cnt) : "memory");
}
__device__ __forceinline__ void mbar_arrive(uint32_t bar) {
    asm volatile("mbarrier.arrive.shared::cta.b64 _, [%0];" ::"r"(bar) : "memory");
}
__device__ __forceinline__ void mbar_expect_tx(uint32_t bar, uint32_t bytes) {
    asm volatile("mbarrier.arrive.expect_tx.shared::cta.b64 _, [%0], %1;" ::"r"(bar), "r"(bytes) : "memory");
}
__device__ __forceinline__ void mbar_wait(uint32_t bar, uint32_t parity) {
    asm volatile(
        "{\n.reg .pred p;\n.reg .u32 n;\nmov.u32 n, 0;\n"
        "WL:\nmbarrier.try_wait.parity.shared::cta.b64 p, [%0], %1;\n@p bra WD;\n"
        "add.u32 n, n, 1;\nsetp.lt.u32 p, n, %2;\n@p bra WL;\ntrap;\nWD:\n}" ::"r"(bar), "r"(parity), "n"(SPIN_LIMIT) : "memory");
}
__device__ __forceinline__ void mbar_wait_cluster(uint32_t bar, uint32_t parity) {
    asm volatile(
        "{\n.reg .pred p;\n.reg .u32 n;\nmov.u32 n, 0;\n"
        "WL:\nmbarrier.try_wait.parity.acquire.cluster.shared::cta.b64 p, [%0], %1;\n@p bra WD;\n"
        "add.u32 n, n, 1;\nsetp.lt.u32 p, n, %2;\n@p bra WL;\ntrap;\nWD:\n}" ::"r"(bar), "r"(parity), "n"(SPIN_LIMIT) : "memory");
}
__device__ __forceinline__ void tma2d(uint32_t dst, const CUtensorMap* m, int c0, int c1, uint32_t bar) {
    asm volatile("cp.async.bulk.tensor.2d.shared::cluster.global.mbarrier::complete_tx::bytes [%0], [%1, {%3, %4}], [%2];"
                 ::"r"(dst), "l"(m), "r"(bar), "r"(c0), "r"(c1) : "memory");
}
__device__ __forceinline__ void tma2d_prefetch(const CUtensorMap* m, int c0, int c1) {
    asm volatile("cp.async.bulk.prefetch.tensor.2d.L2.global [%0, {%1, %2}];" ::"l"(m), "r"(c0), "r"(c1) : "memory");
}
__device__ __forceinline__ void fence_async_smem() { asm volatile("fence.proxy.async.shared::cta;" ::: "memory"); }
__device__ __forceinline__ void fence_gpu() { asm volatile("fence.acq_rel.gpu;" ::: "memory"); }
__device__ __forceinline__ float rcp(float x) { float r; asm("rcp.approx.ftz.f32 %0, %1;" : "=f"(r) : "f"(x)); return r; }
__device__ __forceinline__ void bar_sync(int id, int n) { asm volatile("bar.sync %0, %1;" ::"r"(id), "r"(n) : "memory"); }

__device__ __forceinline__ uint32_t pack_bf16(float lo, float hi) {
    uint32_t r; asm("cvt.rn.bf16x2.f32 %0, %1, %2;" : "=r"(r) : "f"(hi), "f"(lo)); return r;
}
__device__ __forceinline__ uint32_t add_bf16x2(uint32_t a, uint32_t b) {
    uint32_t r; asm("add.rn.bf16x2 %0, %1, %2;" : "=r"(r) : "r"(a), "r"(b)); return r;
}
__device__ __forceinline__ uint32_t movm(uint32_t a) {
    uint32_t r; asm volatile("movmatrix.sync.aligned.m8n8.trans.b16 %0, %1;" : "=r"(r) : "r"(a)); return r;
}
__device__ __forceinline__ float ex2(float x) { float r; asm("ex2.approx.ftz.f32 %0, %1;" : "=f"(r) : "f"(x)); return r; }
__device__ __forceinline__ void ldsm4t(uint32_t (&r)[4], uint32_t a) {
    asm volatile("ldmatrix.sync.aligned.m8n8.x4.trans.shared.b16 {%0,%1,%2,%3}, [%4];"
                 : "=r"(r[0]), "=r"(r[1]), "=r"(r[2]), "=r"(r[3]) : "r"(a) : "memory");
}
__device__ __forceinline__ void ldsm4(uint32_t (&r)[4], uint32_t a) {
    asm volatile("ldmatrix.sync.aligned.m8n8.x4.shared.b16 {%0,%1,%2,%3}, [%4];"
                 : "=r"(r[0]), "=r"(r[1]), "=r"(r[2]), "=r"(r[3]) : "r"(a) : "memory");
}
__device__ __forceinline__ void stsm4t(uint32_t a, uint32_t r0, uint32_t r1, uint32_t r2, uint32_t r3) {
    asm volatile("stmatrix.sync.aligned.m8n8.x4.trans.shared.b16 [%0], {%1,%2,%3,%4};"
                 ::"r"(a), "r"(r0), "r"(r1), "r"(r2), "r"(r3) : "memory");
}
__device__ __forceinline__ void stsm4(uint32_t a, uint32_t r0, uint32_t r1, uint32_t r2, uint32_t r3) {
    asm volatile("stmatrix.sync.aligned.m8n8.x4.shared.b16 [%0], {%1,%2,%3,%4};"
                 ::"r"(a), "r"(r0), "r"(r1), "r"(r2), "r"(r3) : "memory");
}
__device__ __forceinline__ void mma16816(float* c, uint32_t a0, uint32_t a1, uint32_t a2, uint32_t a3, uint32_t b0, uint32_t b1) {
    asm volatile("mma.sync.aligned.m16n8k16.row.col.f32.bf16.bf16.f32 {%0,%1,%2,%3}, {%4,%5,%6,%7}, {%8,%9}, {%0,%1,%2,%3};"
                 : "+f"(c[0]), "+f"(c[1]), "+f"(c[2]), "+f"(c[3]) : "r"(a0), "r"(a1), "r"(a2), "r"(a3), "r"(b0), "r"(b1));
}
__device__ __forceinline__ void mma1688(float* c, uint32_t a0, uint32_t a1, uint32_t b0) {
    asm volatile("mma.sync.aligned.m16n8k8.row.col.f32.bf16.bf16.f32 {%0,%1,%2,%3}, {%4,%5}, {%6}, {%0,%1,%2,%3};"
                 : "+f"(c[0]), "+f"(c[1]), "+f"(c[2]), "+f"(c[3]) : "r"(a0), "r"(a1), "r"(b0));
}
__device__ __forceinline__ void sts128(uint32_t a, float x, float y, float z, float w) {
    asm volatile("st.shared.v4.f32 [%0], {%1,%2,%3,%4};" ::"r"(a), "f"(x), "f"(y), "f"(z), "f"(w) : "memory");
}
__device__ __forceinline__ void sts64(uint32_t a, float x, float y) {
    asm volatile("st.shared.v2.f32 [%0], {%1,%2};" ::"r"(a), "f"(x), "f"(y) : "memory");
}
__device__ __forceinline__ void sts32(uint32_t a, uint32_t x) { asm volatile("st.shared.b32 [%0], %1;" ::"r"(a), "r"(x) : "memory"); }
__device__ __forceinline__ void sts128u(uint32_t a, uint4 v) {
    asm volatile("st.shared.v4.b32 [%0], {%1,%2,%3,%4};" ::"r"(a), "r"(v.x), "r"(v.y), "r"(v.z), "r"(v.w) : "memory");
}
__device__ __forceinline__ float4 lds128(uint32_t a) {
    float4 v; asm volatile("ld.shared.v4.f32 {%0,%1,%2,%3}, [%4];" : "=f"(v.x), "=f"(v.y), "=f"(v.z), "=f"(v.w) : "r"(a) : "memory"); return v;
}
__device__ __forceinline__ uint4 lds128u(uint32_t a) {
    uint4 v; asm volatile("ld.shared.v4.b32 {%0,%1,%2,%3}, [%4];" : "=r"(v.x), "=r"(v.y), "=r"(v.z), "=r"(v.w) : "r"(a) : "memory"); return v;
}
__device__ __forceinline__ float2 lds64(uint32_t a) {
    float2 v; asm volatile("ld.shared.v2.f32 {%0,%1}, [%2];" : "=f"(v.x), "=f"(v.y) : "r"(a) : "memory"); return v;
}
__device__ __forceinline__ uint2 ldg_rlx64(const void* p) {
    uint64_t v; asm volatile("ld.relaxed.gpu.global.b64 %0, [%1];" : "=l"(v) : "l"(p) : "memory");
    return make_uint2((uint32_t)v, (uint32_t)(v >> 32));
}
__device__ __forceinline__ uint4 ldg_rlx128(const void* p) {
    uint64_t a, b;
    asm volatile("{\n.reg .b128 t;\nld.relaxed.gpu.global.b128 t, [%2];\nmov.b128 {%0,%1}, t;\n}" : "=l"(a), "=l"(b) : "l"(p) : "memory");
    return make_uint4((uint32_t)a, (uint32_t)(a >> 32), (uint32_t)b, (uint32_t)(b >> 32));
}
__device__ __forceinline__ void stg_rlx64(void* p, uint32_t x, uint32_t y) {
    asm volatile("{\n.reg .b64 t;\nmov.b64 t, {%1,%2};\nst.relaxed.gpu.global.b64 [%0], t;\n}" ::"l"(p), "r"(x), "r"(y) : "memory");
}
__device__ __forceinline__ void stg128(void* p, uint32_t x, uint32_t y, uint32_t z, uint32_t w) {
    asm volatile("st.global.v4.b32 [%0], {%1,%2,%3,%4};" ::"l"(p), "r"(x), "r"(y), "r"(z), "r"(w) : "memory");
}
__device__ __forceinline__ uint32_t ld_acquire(const unsigned* p) {
    uint32_t v; asm volatile("ld.acquire.gpu.global.u32 %0, [%1];" : "=r"(v) : "l"(p) : "memory"); return v;
}
__device__ __forceinline__ void red_add_u32(unsigned* p, uint32_t v) {
    asm volatile("red.relaxed.gpu.global.add.u32 [%0], %1;" ::"l"(p), "r"(v) : "memory");
}
__device__ __forceinline__ void wait_counter(const unsigned* p, uint32_t target) {
    uint32_t n = 0;
    while (ld_acquire(p) < target) { if (++n > SPIN_LIMIT) __trap(); }
}

__device__ __forceinline__ void wg_fence() { asm volatile("wgmma.fence.sync.aligned;" ::: "memory"); }
__device__ __forceinline__ void wg_commit() { asm volatile("wgmma.commit_group.sync.aligned;" ::: "memory"); }
template <int N> __device__ __forceinline__ void wg_wait() { asm volatile("wgmma.wait_group.sync.aligned %0;" ::"n"(N) : "memory"); }
__host__ __device__ constexpr uint64_t mkdesc(uint32_t addr, uint32_t lbo, uint32_t sbo, uint32_t swz) {
    return (uint64_t)((addr & 0x3FFFF) >> 4) | ((uint64_t)(lbo >> 4) << 16) | ((uint64_t)(sbo >> 4) << 32) | ((uint64_t)swz << 62);
}
#define F4(d, o) "+f"(d[o]), "+f"(d[o + 1]), "+f"(d[o + 2]), "+f"(d[o + 3])
template <int SC> __device__ __forceinline__ void wg_rs40(float (&d)[20], const uint32_t (&a)[4], uint64_t db) {
    asm volatile("wgmma.mma_async.sync.aligned.m64n40k16.f32.bf16.bf16 "
                 "{%0,%1,%2,%3,%4,%5,%6,%7,%8,%9,%10,%11,%12,%13,%14,%15,%16,%17,%18,%19}, {%20,%21,%22,%23}, %24, %25, 1, 1, 0;"
                 : F4(d, 0), F4(d, 4), F4(d, 8), F4(d, 12), F4(d, 16)
                 : "r"(a[0]), "r"(a[1]), "r"(a[2]), "r"(a[3]), "l"(db), "n"(SC));
}
template <int SC> __device__ __forceinline__ void wg_ss40(float (&d)[20], uint64_t da, uint64_t db) {
    asm volatile("wgmma.mma_async.sync.aligned.m64n40k16.f32.bf16.bf16 "
                 "{%0,%1,%2,%3,%4,%5,%6,%7,%8,%9,%10,%11,%12,%13,%14,%15,%16,%17,%18,%19}, %20, %21, %22, 1, 1, 1, 0;"
                 : F4(d, 0), F4(d, 4), F4(d, 8), F4(d, 12), F4(d, 16)
                 : "l"(da), "l"(db), "n"(SC));
}
template <int SC> __device__ __forceinline__ void wg_ss8(float (&d)[4], uint64_t da, uint64_t db) {
    asm volatile("wgmma.mma_async.sync.aligned.m64n8k16.f32.bf16.bf16 {%0,%1,%2,%3}, %4, %5, %6, 1, 1, 1, 1;"
                 : F4(d, 0) : "l"(da), "l"(db), "n"(SC));
}

__device__ uint4 g_kvq[4 * 32 * 3 * 8 * 2 * 32];
__device__ uint2 g_alpha[2 * 32 * 3 * 8 * 2 * 32];
__device__ uint4 g_red[(4 * 65536 + 32768) / 16];
__device__ unsigned g_cnt[65 * 32];
__device__ bf16 g_ox[2048 * 4096];
#define TS(k) do {} while (0)
#define TSV(k, v) do {} while (0)
#define TSDUMP() do {} while (0)
#define GT(k) do {} while (0)

struct Tune { uint32_t d_alpha, d_alpha_v, d_r[4], v_start; };

constexpr uint32_t SM_BASE = 1024;
constexpr uint32_t O_WO = 0;
constexpr uint32_t O_WV = 65536;
constexpr uint32_t O_XB = 131072;
constexpr uint32_t O_RECV = O_XB + 40960;
constexpr uint32_t O_S = O_RECV + 24576;
constexpr uint32_t O_O = O_S + 10240;
constexpr uint32_t O_XO = O_O + 2048;
constexpr uint32_t O_BAR = O_XO + 2048;
constexpr uint32_t O_DBG = O_BAR + 256;
constexpr uint32_t MAIN_SMEM = O_DBG + (DBG_TIMING ? 4 * 32 * 24 * 4 : 0);
enum { B_WQ0 = 0, B_WQ1, B_WK0, B_WK1, B_WV, B_WO, B_QDONE, B_KDONE, B_XFULL, B_XEMPTY, B_MEM0, B_MEM1, B_MEM2, B_MEM3,
       B_RECV, B_AQK = B_RECV + 6, B_AV, B_SRDY, B_SFREE, B_COUNT };

constexpr float SM_SCALE_LOG2 = 0.08838834764831845f * 1.4426950408889634f;
constexpr float MASK_VAL = -1.0e9f / 0.08838834764831845f;

__device__ __forceinline__ uint32_t red_off_a(int c, int grp, int l) {
    return (uint32_t)((grp >> 1) * 1024 + (grp & 1) * 256 + (c & 1) * 128 + (c >> 1) * 512 + (l & 7) * 16);
}
__device__ __forceinline__ uint32_t red_off_b(int c, int grp, int l) {
    return (uint32_t)(32768 + (grp >> 1) * 1024 + (grp & 1) * 256 + (c >> 1) * 128 + (c & 1) * 64 + (l & 7) * 8);
}

template <int R>
__device__ __forceinline__ void x_epilogue(float (&d)[20], int p, int h, int nh, int kh, int w, int tid, uint32_t sb, uint32_t mate) {
    const uint32_t par = p & 1;
    const uint32_t bar = O_BAR + 8 * (B_RECV + R * 2) + 8 * par;
    const uint32_t slot = O_RECV + (par * 3 + R) * 4096 + tid * 16;
    if (tid == 0) mbar_expect_tx(sb + bar, 4096);
    float s[8], k[8];
#pragma unroll
    for (int i = 0; i < 8; i++) { s[i] = kh ? d[i] : d[8 + i]; k[i] = kh ? d[8 + i] : d[i]; }
#pragma unroll
    for (int v = 0; v < 2; v++)
        asm volatile("st.async.shared::cluster.mbarrier::complete_tx::bytes.v4.f32 [%0], {%1,%2,%3,%4}, [%5];"
                     ::"r"(mate + slot + v * 2048), "f"(s[4 * v]), "f"(s[4 * v + 1]), "f"(s[4 * v + 2]), "f"(s[4 * v + 3]), "r"(mate + bar) : "memory");
    mbar_wait_cluster(sb + bar, (p >> 1) & 1);
    float4 r0 = lds128(sb + slot), r1 = lds128(sb + slot + 2048);
    uint32_t u0 = pack_bf16(k[0] + r0.x, k[1] + r0.y), u1 = pack_bf16(k[2] + r0.z, k[3] + r0.w);
    uint32_t u2 = pack_bf16(k[4] + r1.x, k[5] + r1.y), u3 = pack_bf16(k[6] + r1.z, k[7] + r1.w);
    if (R < 2) { u0 = movm(u0); u1 = movm(u1); u2 = movm(u2); u3 = movm(u3); }
    stg128(&g_kvq[((((p & 3) * 32 + h) * 3 + R) * 16 + (nh * 4 + w) * 2 + kh) * 32 + (tid & 31)], u0, u1, u2, u3);
    fence_gpu();
    __syncwarp();
    if ((tid & 31) == 0) red_add_u32(&g_cnt[(h * 2 + par) * 32], 1);
}

template <int R>
__device__ __forceinline__ void alpha_write(float (&d)[20], int s, int h, int nh, int kh, int w, int lane) {
    uint32_t u0 = pack_bf16(d[16], d[17]), u1 = pack_bf16(d[18], d[19]);
    if (R < 2) { u0 = movm(u0); u1 = movm(u1); }
    u0 = (u0 & ~1u) | (((s >> 1) & 1) ^ 1);
    stg_rlx64(&g_alpha[((((s & 1) * 32 + h) * 3 + R) * 16 + (nh * 4 + w) * 2 + kh) * 32 + lane], u0, u1);
}

__device__ __forceinline__ void softmax10(float (&sc)[10], uint32_t (&pf)[5], float& sum) {
    float m = fmaxf(fmaxf(fmaxf(sc[0], sc[1]), fmaxf(sc[2], sc[3])), fmaxf(fmaxf(sc[4], sc[5]), fmaxf(sc[6], sc[7])));
    m = fmaxf(m, fmaxf(sc[8], sc[9]));
    m = fmaxf(m, __shfl_xor_sync(~0u, m, 1));
    m = fmaxf(m, __shfl_xor_sync(~0u, m, 2));
    const float mb = -m * SM_SCALE_LOG2;
#pragma unroll
    for (int i = 0; i < 10; i++) sc[i] = ex2(fmaf(sc[i], SM_SCALE_LOG2, mb));
#pragma unroll
    for (int n = 0; n < 5; n++) pf[n] = pack_bf16(sc[2 * n], sc[2 * n + 1]);
    sum = ((sc[0] + sc[1]) + (sc[2] + sc[3])) + ((sc[4] + sc[5]) + (sc[6] + sc[7])) + (sc[8] + sc[9]);
}

__global__ void __cluster_dims__(2, 1, 1) __launch_bounds__(512, 1)
rmt_main(const __grid_constant__ CUtensorMap tm_x, const __grid_constant__ CUtensorMap tm_wq, const __grid_constant__ CUtensorMap tm_wk,
         const __grid_constant__ CUtensorMap tm_wv, const __grid_constant__ CUtensorMap tm_wo, const bf16* __restrict__ mem0, const Tune tn) {
    extern __shared__ __align__(1024) unsigned char smem_raw[];
    const uint32_t sb = smem_u32(smem_raw);
    if ((sb & 0x3FFFF) != SM_BASE) __trap();
    const int cid = blockIdx.x >> 1, kh = blockIdx.x & 1;
    const int tpc = cid < 4 ? 62 + cid : cid - 4;
    int h, nh;
    if (tpc < 32) { h = (tpc >> 4) * 8 + (tpc & 7); nh = (tpc >> 3) & 1; }
    else if (tpc < 60) { int u = tpc - 32, r = u % 14; h = 16 + (u / 14) * 7 + r % 7; nh = r / 7; }
    else if (tpc < 62) return;
    else { h = 30 + ((tpc - 62) >> 1); nh = tpc & 1; }
    const int j = nh * 2 + kh, role = h * 4 + j;
    const int wgi = __shfl_sync(~0u, threadIdx.x >> 7, 0);
    const int tid = threadIdx.x & 127, w = tid >> 5, lane = tid & 31;
#define OPAQUE_IDS() int tid_ = tid; asm volatile("" : "+r"(tid_)); const int tid = tid_, w = tid_ >> 5, lane = tid_ & 31; (void)w; (void)lane
    unsigned char* const redp = (unsigned char*)(((uintptr_t)g_red + 32767) & ~(uintptr_t)32767);
    const uint32_t bars = sb + O_BAR;

    if (threadIdx.x == 0) {
        const uint8_t cnts[B_COUNT] = {1, 1, 1, 1, 1, 1, 4, 4, 1, 12, 2, 2, 2, 2, 1, 1, 1, 1, 1, 1, 8, 4, 4, 4};
#pragma unroll
        for (int i = 0; i < B_COUNT; i++) mbar_init(bars + 8 * i, cnts[i]);
        asm volatile("fence.mbarrier_init.release.cluster;" ::: "memory");
        fence_async_smem();
        const int c0 = h * 128 + nh * 64, r0 = kh * 512;
        for (int i = 0; i < 2; i++) {
            mbar_expect_tx(bars + 8 * (B_WK0 + i), 32768);
            tma2d(sb + O_XB + i * 32768, &tm_wk, c0, r0 + i * 256, bars + 8 * (B_WK0 + i));
            mbar_expect_tx(bars + 8 * (B_WQ0 + i), 32768);
            tma2d(sb + O_WO + i * 32768, &tm_wq, c0, r0 + i * 256, bars + 8 * (B_WQ0 + i));
        }
        mbar_expect_tx(bars + 8 * B_WV, 65536);
        for (int i = 0; i < 2; i++) tma2d(sb + O_WV + i * 32768, &tm_wv, c0, r0 + i * 256, bars + 8 * B_WV);
        for (int i = 0; i < 4; i++) tma2d_prefetch(&tm_wo, j * 256 + i * 64, h * 128);
    }
    __syncthreads();
    uint32_t mate;
    asm volatile("mapa.shared::cluster.u32 %0, %1, %2;" : "=r"(mate) : "r"(sb), "r"(kh ^ 1));

    if (wgi < 2) {
        asm volatile("setmaxnreg.inc.sync.aligned.u32 176;");
        uint32_t a[32][4];
        {
            const uint32_t stage = sb + (wgi == 0 ? O_WO : O_XB);
            const uint32_t ad = stage + (((lane >> 4) & 1) * 8 + (lane & 7)) * 128 + (((2 * w + ((lane >> 3) & 1)) ^ (lane & 7)) << 4);
#pragma unroll
            for (int i = 0; i < 2; i++) {
                mbar_wait(bars + 8 * (B_WQ0 + 2 * wgi + i), 0);
#pragma unroll
                for (int ks = 0; ks < 16; ks++) ldsm4t(a[i * 16 + ks], ad + (i * 16 + ks) * 2048);
            }
            __syncwarp();
            if (lane == 0) mbar_arrive(bars + 8 * (B_QDONE + wgi));
        }
        asm volatile("barrier.cluster.arrive.release.aligned;" ::: "memory");
        asm volatile("barrier.cluster.wait.acquire.aligned;" ::: "memory");
        float d[20];
#pragma unroll 1
        for (int p = 0; p <= 64; p++) {
            const int tsi = p; (void)tsi;
            OPAQUE_IDS();
            if (p < 64) mbar_wait(bars + 8 * B_XFULL, p & 1);
#pragma unroll
            for (int c = 0; c < 4; c++) {
                if (p > 0) mbar_wait(bars + 8 * (B_MEM0 + c), (p - 1) & 1);
                TS(c);
                wg_fence();
#pragma unroll
                for (int i = 0; i < 8; i++) {
                    const int kb = (i >> 2) * 4 + c, ks = kb * 4 + (i & 3);
                    constexpr uint64_t db0 = mkdesc(SM_BASE + O_XB, 16, 1024, 1);
                    if (c == 0 && i == 0) wg_rs40<0>(d, a[ks], db0 + ((kb * 5120 + (i & 3) * 32) >> 4));
                    else wg_rs40<1>(d, a[ks], db0 + ((kb * 5120 + (i & 3) * 32) >> 4));
                }
                wg_commit();
            }
            wg_wait<0>();
            TS(4);
            if (p > 0) {
                if (wgi == 0) alpha_write<0>(d, p - 1, h, nh, kh, w, lane); else alpha_write<1>(d, p - 1, h, nh, kh, w, lane);
                if (lane == 0) mbar_arrive(bars + 8 * B_AQK);
            }
            if (lane == 0) mbar_arrive(bars + 8 * B_XEMPTY);
            TS(5);
            if (p < 64) {
                if (wgi == 0) x_epilogue<0>(d, p, h, nh, kh, w, tid, sb, mate); else x_epilogue<1>(d, p, h, nh, kh, w, tid, sb, mate);
            }
            TS(6);
        }
        TSDUMP();
    } else if (wgi == 2) {
        asm volatile("setmaxnreg.dec.sync.aligned.u32 64;");
        asm volatile("barrier.cluster.arrive.release.aligned;" ::: "memory");
        if (tid == 0) {
            mbar_wait(bars + 8 * B_KDONE, 0);
            mbar_expect_tx(bars + 8 * B_XFULL, 32768);
            for (int kb = 0; kb < 8; kb++) tma2d(sb + O_XB + kb * 5120, &tm_x, kh * 512 + kb * 64, 0, bars + 8 * B_XFULL);
            mbar_wait(bars + 8 * B_QDONE, 0);
            mbar_expect_tx(bars + 8 * B_WO, 65536);
            for (int i = 0; i < 4; i++) tma2d(sb + O_WO + i * 16384, &tm_wo, j * 256 + i * 64, h * 128, bars + 8 * B_WO);
        }
        unsigned char* const zp = redp + (role >> 6) * 32768 + ((role & 63) >> 1) * 1024 + (role & 1) * 256 +
                                  ((lane >> 3) & 1) * 128 + (lane >> 4) * 512 + (lane & 7) * 16;
        if (w == 1) {
            for (int s = 0; s < 2; s++) {
                const uint32_t base = __float_as_uint(64.f * s);
                stg128(zp + s * 65536, 0, role >= 64 ? base : 0, 0, base);
            }
            fence_gpu();
            __syncwarp();
            if (lane == 0) red_add_u32(&g_cnt[64 * 32], 1);
        }
        __syncwarp();
        asm volatile("barrier.cluster.wait.acquire.aligned;" ::: "memory");
        mbar_wait(bars + 8 * B_WV, 0);
        float d[20];
#pragma unroll 1
        for (int p = 0; p <= 64; p++) {
            const int tsi = p; (void)tsi;
            const int s = p - 1;
            OPAQUE_IDS();
            if (p < 64) mbar_wait(bars + 8 * B_XFULL, p & 1);
            if (p > 0) mbar_wait(bars + 8 * (B_MEM0 + tn.v_start), s & 1);
#pragma unroll
            for (int c = 0; c < 4; c++) {
                if (p > 0) mbar_wait(bars + 8 * (B_MEM0 + c), s & 1);
                TS(c);
                wg_fence();
#pragma unroll
                for (int i = 0; i < 8; i++) {
                    const int kb = (i >> 2) * 4 + c, ks = kb * 4 + (i & 3);
                    constexpr uint64_t da0 = mkdesc(SM_BASE + O_WV, 16, 1024, 1), db0 = mkdesc(SM_BASE + O_XB, 16, 1024, 1);
                    if (c == 0 && i == 0) wg_ss40<0>(d, da0 + ks * 128, db0 + ((kb * 5120 + (i & 3) * 32) >> 4));
                    else wg_ss40<1>(d, da0 + ks * 128, db0 + ((kb * 5120 + (i & 3) * 32) >> 4));
                }
                wg_commit();
            }
            wg_wait<0>();
            TS(4);
            if (p > 0) {
                alpha_write<2>(d, s, h, nh, kh, w, lane);
                if (lane == 0) mbar_arrive(bars + 8 * B_AV);
            }
            if (lane == 0) mbar_arrive(bars + 8 * B_XEMPTY);
            if (tid == 0 && p < 63) {
                mbar_wait(bars + 8 * B_XEMPTY, p & 1);
                mbar_expect_tx(bars + 8 * B_XFULL, 32768);
                for (int kb = 0; kb < 8; kb++) tma2d(sb + O_XB + kb * 5120, &tm_x, kh * 512 + kb * 64, (p + 1) * 32, bars + 8 * B_XFULL);
            }
            __syncwarp();
            if (w == 1 && p >= 1 && p <= 61) {
                const uint32_t base = __float_as_uint(64.f * (p + 1));
                stg128(zp + ((p + 1) & 3) * 65536, 0, role >= 64 ? base : 0, 0, base);
            }
            TS(5);
            if (p < 64) x_epilogue<2>(d, p, h, nh, kh, w, tid, sb, mate);
            TS(6);
            if (p > 0) {
                mbar_wait(bars + 8 * B_SRDY, s & 1);
                uint4 vf[4]; uint2 vm[4];
                const uint4* vp = &g_kvq[((((s & 3) * 32 + h) * 3 + 2) * 16 + w * 4) * 32 + lane];
                const uint2* ap = &g_alpha[((((s & 1) * 32 + h) * 3 + 2) * 16 + w * 4) * 32 + lane];
#pragma unroll
                for (int i = 0; i < 4; i++) { vf[i] = ldg_rlx128(vp + i * 32); vm[i] = ldg_rlx64(ap + i * 32); }
                float sc[10];
#pragma unroll
                for (int i = 0; i < 10; i++) sc[i] = 0.f;
#pragma unroll
                for (int q = 0; q < 4; q++) {
                    const uint32_t a0 = sb + O_S + (4 + q) * 1280;
                    float4 x0 = lds128(a0 + lane * 16), x1 = lds128(a0 + 512 + lane * 16); float2 x2 = lds64(a0 + 1024 + lane * 8);
                    sc[0] += x0.x; sc[1] += x0.y; sc[2] += x0.z; sc[3] += x0.w; sc[4] += x1.x; sc[5] += x1.y; sc[6] += x1.z; sc[7] += x1.w;
                    sc[8] += x2.x; sc[9] += x2.y;
                }
                __syncwarp();
                if (lane == 0) mbar_arrive(bars + 8 * B_SFREE);
                const int lim = 8 * j + (lane >> 2) - 2 * (lane & 3);
#pragma unroll
                for (int i = 2; i < 10; i++) if (8 * ((i >> 1) - 1) + (i & 1) > lim) sc[i] = MASK_VAL;
                uint32_t pf[5]; float sum;
                softmax10(sc, pf, sum);
                sum += __shfl_xor_sync(~0u, sum, 1);
                sum += __shfl_xor_sync(~0u, sum, 2);
                const float inv = rcp(sum);
                const float i0 = __shfl_sync(~0u, inv, (lane & 3) * 8), i1 = __shfl_sync(~0u, inv, (lane & 3) * 8 + 4);
                uint32_t ow[4];
#pragma unroll
                for (int u = 0; u < 2; u++) {
                    float o[4] = {0.f, 0.f, 0.f, 0.f};
                    mma1688(o, add_bf16x2(vm[2 * u].x, vm[2 * u + 1].x), add_bf16x2(vm[2 * u].y, vm[2 * u + 1].y), pf[0]);
                    mma16816(o, vf[2 * u].x, vf[2 * u].y, vf[2 * u].z, vf[2 * u].w, pf[1], pf[2]);
                    mma16816(o, vf[2 * u + 1].x, vf[2 * u + 1].y, vf[2 * u + 1].z, vf[2 * u + 1].w, pf[3], pf[4]);
                    ow[2 * u] = pack_bf16(o[0] * i0, o[1] * i1);
                    ow[2 * u + 1] = pack_bf16(o[2] * i0, o[3] * i1);
                }
                const uint32_t xo = sb + O_XO + w * 512;
                stsm4t(xo + (lane & 7) * 64 + (((lane >> 3) ^ ((lane >> 1) & 3)) << 4), ow[0], ow[1], ow[2], ow[3]);
                __syncwarp();
                const uint4 ov = lds128u(xo + (lane >> 2) * 64 + (((lane & 3) ^ ((lane >> 3) & 3)) << 4));
                stg128(&g_ox[(size_t)(s * 32 + j * 8 + (lane >> 2)) * 4096 + h * 128 + w * 32 + (lane & 3) * 8], ov.x, ov.y, ov.z, ov.w);
                __syncwarp();
            }
            TS(7);
        }
        TSDUMP();
    } else {
        asm volatile("setmaxnreg.dec.sync.aligned.u32 96;");
        GT(0);
        asm volatile("barrier.cluster.arrive.release.aligned;" ::: "memory");
        const int jj = w & 1, c0 = w >> 1;
        mbar_wait(bars + 8 * B_KDONE, 0);
#pragma unroll
        for (int i = 0; i < 2; i++) {
            const int c = c0 + 2 * i, kb = jj * 4 + c;
#pragma unroll
            for (int q = 0; q < 2; q++) {
                const int row = (lane >> 3) + q * 4, ch = lane & 7;
                const uint4 v = *(const uint4*)(mem0 + row * 1024 + kh * 512 + kb * 64 + ch * 8);
                sts128u(sb + O_XB + kb * 5120 + 4096 + row * 128 + ((ch ^ row) << 4), v);
            }
            fence_async_smem();
            __syncwarp();
            if (lane == 0) mbar_arrive(bars + 8 * (B_MEM0 + c));
        }
        asm volatile("barrier.cluster.wait.acquire.aligned;" ::: "memory");
        if (lane == 0) wait_counter(&g_cnt[64 * 32], 128);
        __syncwarp();
        mbar_wait(bars + 8 * B_WO, 0);
        GT(1);
        const uint32_t wa_off = red_off_a(0, j * 16 + w * 4 + (lane >> 3), lane), wb_off = red_off_b(0, j * 16 + w * 4 + (lane >> 3), lane);
        const uint32_t ra_off = red_off_a(c0, (kh * 2 + jj) * 16 + (lane >> 3), lane), rb_off = red_off_b(c0, (kh * 2 + jj) * 16 + (lane >> 3), lane);
        const uint32_t dr0 = c0 ? tn.d_r[1] : tn.d_r[0], dr1 = c0 ? tn.d_r[3] : tn.d_r[2];
#pragma unroll 1
        for (int s = 0; s < 64; s++) {
            const int tsi = s; (void)tsi;
            OPAQUE_IDS();
            if (lane == 0) wait_counter(&g_cnt[(h * 2 + (s & 1)) * 32], 48 * ((s >> 1) + 1));
            __syncwarp();
            uint4 kf[4], vf[4]; uint2 qf[2];
            {
                const uint4* bp = &g_kvq[(((s & 3) * 32 + h) * 3 * 16 + w * 4) * 32 + lane];
#pragma unroll
                for (int i = 0; i < 4; i++) kf[i] = ldg_rlx128(bp + (16 + i) * 32);
#pragma unroll
                for (int u = 0; u < 2; u++) qf[u] = ldg_rlx64((const uint2*)(bp + (2 * u + nh) * 32) + kh);
#pragma unroll
                for (int i = 0; i < 4; i++) vf[i] = ldg_rlx128(bp + (32 + i) * 32);
            }
            if (s > 0) mbar_wait(bars + 8 * B_SFREE, (s - 1) & 1);
            const uint32_t tag = ((s >> 1) & 1) ^ 1;
            const uint2* ap = &g_alpha[(((s & 1) * 32 + h) * 3 * 16 + w * 4) * 32 + lane];
            TS(0);
            mbar_wait(bars + 8 * B_AQK, s & 1);
            TS(1);
            wait_clk(clk(), tn.d_alpha);
            uint2 qa[4], ka[4];
            {
                uint32_t n = 0;
                while (true) {
#pragma unroll
                    for (int i = 0; i < 4; i++) { qa[i] = ldg_rlx64(ap + i * 32); ka[i] = ldg_rlx64(ap + (16 + i) * 32); }
                    const uint32_t x = (qa[0].x ^ tag) | (qa[1].x ^ tag) | (qa[2].x ^ tag) | (qa[3].x ^ tag) |
                                       (ka[0].x ^ tag) | (ka[1].x ^ tag) | (ka[2].x ^ tag) | (ka[3].x ^ tag);
                    if (!__any_sync(~0u, x & 1)) break;
                    if (++n > SPIN_LIMIT) __trap();
                }
                if (tid == 0) TSV(20, n);
            }
            TS(2);
            float sa[5][4];
#pragma unroll
            for (int n = 0; n < 5; n++) sa[n][0] = sa[n][1] = sa[n][2] = sa[n][3] = 0.f;
#pragma unroll
            for (int u = 0; u < 2; u++) {
                const uint32_t q0 = add_bf16x2(qa[2 * u].x, qa[2 * u + 1].x), q1 = add_bf16x2(qa[2 * u].y, qa[2 * u + 1].y);
                const uint32_t k0 = add_bf16x2(ka[2 * u].x, ka[2 * u + 1].x), k1 = add_bf16x2(ka[2 * u].y, ka[2 * u + 1].y);
                mma16816(sa[1], q0, qf[u].x, q1, qf[u].y, kf[2 * u].x, kf[2 * u].y);
                mma16816(sa[2], q0, qf[u].x, q1, qf[u].y, kf[2 * u].z, kf[2 * u].w);
                mma16816(sa[3], q0, qf[u].x, q1, qf[u].y, kf[2 * u + 1].x, kf[2 * u + 1].y);
                mma16816(sa[4], q0, qf[u].x, q1, qf[u].y, kf[2 * u + 1].z, kf[2 * u + 1].w);
                mma16816(sa[0], q0, qf[u].x, q1, qf[u].y, k0, k1);
            }
            {
                const uint32_t a0 = sb + O_S + w * 1280;
                sts128(a0 + lane * 16, sa[0][0], sa[0][1], sa[1][0], sa[1][1]);
                sts128(a0 + 512 + lane * 16, sa[2][0], sa[2][1], sa[3][0], sa[3][1]);
                sts64(a0 + 1024 + lane * 8, sa[4][0], sa[4][1]);
            }
            bar_sync(1, 128);
            float sc[10];
#pragma unroll
            for (int n = 0; n < 5; n++) { sc[2 * n] = sa[n][0]; sc[2 * n + 1] = sa[n][1]; }
#pragma unroll
            for (int q = 1; q < 4; q++) {
                const uint32_t a0 = sb + O_S + ((w + q) & 3) * 1280;
                float4 x0 = lds128(a0 + lane * 16), x1 = lds128(a0 + 512 + lane * 16); float2 x2 = lds64(a0 + 1024 + lane * 8);
                sc[0] += x0.x; sc[1] += x0.y; sc[2] += x0.z; sc[3] += x0.w; sc[4] += x1.x; sc[5] += x1.y; sc[6] += x1.z; sc[7] += x1.w;
                sc[8] += x2.x; sc[9] += x2.y;
            }
            {
                const uint32_t a0 = sb + O_S + (4 + w) * 1280;
                sts128(a0 + lane * 16, sa[0][2], sa[0][3], sa[1][2], sa[1][3]);
                sts128(a0 + 512 + lane * 16, sa[2][2], sa[2][3], sa[3][2], sa[3][3]);
                sts64(a0 + 1024 + lane * 8, sa[4][2], sa[4][3]);
            }
            uint32_t pf[5]; float sum;
            softmax10(sc, pf, sum);
            TS(3);
            float o[2][4];
#pragma unroll
            for (int u = 0; u < 2; u++) {
                o[u][0] = o[u][1] = o[u][2] = o[u][3] = 0.f;
                mma16816(o[u], vf[2 * u].x, vf[2 * u].y, vf[2 * u].z, vf[2 * u].w, pf[1], pf[2]);
                mma16816(o[u], vf[2 * u + 1].x, vf[2 * u + 1].y, vf[2 * u + 1].z, vf[2 * u + 1].w, pf[3], pf[4]);
            }
            mbar_wait(bars + 8 * B_AV, s & 1);
            {
                uint2 va[4];
                uint32_t n = 0;
                while (true) {
#pragma unroll
                    for (int i = 0; i < 4; i++) va[i] = ldg_rlx64(ap + (32 + i) * 32);
                    const uint32_t x = (va[0].x ^ tag) | (va[1].x ^ tag) | (va[2].x ^ tag) | (va[3].x ^ tag);
                    if (!__any_sync(~0u, x & 1)) break;
                    if (++n > SPIN_LIMIT) __trap();
                }
                if (tid == 0) TSV(21, n);
#pragma unroll
                for (int u = 0; u < 2; u++)
                    mma1688(o[u], add_bf16x2(va[2 * u].x, va[2 * u + 1].x), add_bf16x2(va[2 * u].y, va[2 * u + 1].y), pf[0]);
            }
            TS(4);
            {
                const uint32_t oa = sb + O_O + w * 512 + lane * 4;
                sts32(oa, pack_bf16(o[0][0], o[0][1]));
                sts32(oa + 128, pack_bf16(o[0][2], o[0][3]));
                sts32(oa + 256, pack_bf16(o[1][0], o[1][1]));
                sts32(oa + 384, pack_bf16(o[1][2], o[1][3]));
            }
            fence_async_smem();
            bar_sync(1, 128);
            if (lane == 0) mbar_arrive(bars + 8 * B_SRDY);
            if (s == 0) GT(2);
            if (s == 63) { GT(3); break; }
            const uint32_t t0 = clk();
            TS(5);
            unsigned char* const rb = redp + (s & 3) * 65536;
            sum += __shfl_xor_sync(~0u, sum, 1);
            sum += __shfl_xor_sync(~0u, sum, 2);
            const float inv = rcp(sum);
            const float i0 = __shfl_sync(~0u, inv, (lane & 3) * 8), i1 = __shfl_sync(~0u, inv, (lane & 3) * 8 + 4);
#pragma unroll 1
            for (int c = 0; c < 4; c++) {
                float acc[4];
                wg_fence();
                const uint64_t da0 = mkdesc(SM_BASE + O_WO, 16, 1024, 1) + c * 1024;
#pragma unroll
                for (int ks = 0; ks < 8; ks++) {
                    constexpr uint64_t db0 = mkdesc(SM_BASE + O_O, 128, 128, 0);
                    if (ks == 0) wg_ss8<0>(acc, da0 + ks * 128, db0 + ks * 16);
                    else wg_ss8<1>(acc, da0 + ks * 128, db0 + ks * 16);
                }
                wg_commit();
                unsigned char* const pa = rb + wa_off + (c & 1) * 128 + (c >> 1) * 512;
                unsigned char* const pb = rb + wb_off + c * 64;
                wg_wait<0>();
                asm volatile("red.relaxed.gpu.global.add.v4.f32 [%0], {%1,%2,%3,%4};"
                             ::"l"(pa), "f"(acc[0] * i0), "f"(acc[1] * i1), "f"(acc[2] * i0), "f"(1.f) : "memory");
                asm volatile("red.relaxed.gpu.global.add.v2.f32 [%0], {%1,%2};"
                             ::"l"(pb), "f"(acc[3] * i1), "f"(1.f) : "memory");
                TS(6 + c);
            }
            const uint32_t target = __float_as_uint(64.f * s + 32.f);
#pragma unroll
            for (int i = 0; i < 2; i++) {
                const int c = c0 + 2 * i;
                const unsigned char* pa = rb + ra_off + i * 512;
                const unsigned char* pb = rb + rb_off + i * 128;
                wait_clk(t0, i ? dr1 : dr0);
                if (i == 0) TS(10);
                uint4 ra[4]; uint2 rbv[4];
                uint32_t n = 0;
                while (true) {
#pragma unroll
                    for (int q = 0; q < 4; q++) { ra[q] = ldg_rlx128(pa + q * 2048); rbv[q] = ldg_rlx64(pb + q * 2048); }
                    const uint32_t x = (ra[0].w ^ target) | (ra[1].w ^ target) | (ra[2].w ^ target) | (ra[3].w ^ target) |
                                       (rbv[0].y ^ target) | (rbv[1].y ^ target) | (rbv[2].y ^ target) | (rbv[3].y ^ target);
                    if (!__any_sync(~0u, x != 0)) break;
                    if (++n > SPIN_LIMIT) __trap();
                }
                if (lane == 0 && jj == 0) TSV(16 + c, n);
                TS(11 + 2 * i);
                uint32_t u[8];
#pragma unroll
                for (int q = 0; q < 4; q++) {
                    u[2 * q] = pack_bf16(__uint_as_float(ra[q].x), __uint_as_float(ra[q].y));
                    u[2 * q + 1] = pack_bf16(__uint_as_float(ra[q].z), __uint_as_float(rbv[q].x));
                }
                const uint32_t ma = sb + O_XB + (jj * 4 + c) * 5120 + 4096 + (lane & 7) * 128;
                stsm4t(ma + (((lane >> 3) ^ (lane & 7)) << 4), u[0], u[1], u[2], u[3]);
                stsm4t(ma + (((4 + (lane >> 3)) ^ (lane & 7)) << 4), u[4], u[5], u[6], u[7]);
                fence_async_smem();
                __syncwarp();
                if (lane == 0) mbar_arrive(bars + 8 * (B_MEM0 + c));
                TS(12 + 2 * i);
            }
        }
        TSDUMP();
    }
}

constexpr int G_ST = 6;
constexpr uint32_t G_SMEM = G_ST * 32768 + 256;
#define F16(d, o) F4(d, o), F4(d, o + 4), F4(d, o + 8), F4(d, o + 12)
__device__ __forceinline__ void wg_ss128(float (&d)[64], uint64_t da, uint64_t db, int sc) {
    asm volatile("{\n.reg .pred p;\nsetp.ne.b32 p, %66, 0;\nwgmma.mma_async.sync.aligned.m64n128k16.f32.bf16.bf16 "
                 "{%0,%1,%2,%3,%4,%5,%6,%7,%8,%9,%10,%11,%12,%13,%14,%15,%16,%17,%18,%19,%20,%21,%22,%23,%24,%25,%26,%27,%28,%29,%30,%31,"
                 "%32,%33,%34,%35,%36,%37,%38,%39,%40,%41,%42,%43,%44,%45,%46,%47,%48,%49,%50,%51,%52,%53,%54,%55,%56,%57,%58,%59,%60,%61,%62,%63}, "
                 "%64, %65, p, 1, 1, 0, 1;\n}"
                 : F16(d, 0), F16(d, 16), F16(d, 32), F16(d, 48) : "l"(da), "l"(db), "r"(sc));
}

__global__ void __launch_bounds__(384, 1)
out_gemm(const __grid_constant__ CUtensorMap tm_o, const __grid_constant__ CUtensorMap tm_w, bf16* __restrict__ out) {
    extern __shared__ __align__(1024) unsigned char smem_raw[];
    const uint32_t sb = smem_u32(smem_raw), bars = sb + G_ST * 32768;
    const int m0 = (blockIdx.x >> 3) * 128, n0 = (blockIdx.x & 7) * 128;
    const int wgi = __shfl_sync(~0u, threadIdx.x >> 7, 0), tid = threadIdx.x & 127;
    if (threadIdx.x == 0) {
        for (int i = 0; i < G_ST; i++) { mbar_init(bars + 8 * i, 1); mbar_init(bars + 8 * (G_ST + i), 8); }
        fence_async_smem();
    }
    if (blockIdx.x == 0 && threadIdx.x < 65) g_cnt[threadIdx.x * 32] = 0;
    __syncthreads();
    if (wgi == 0) GT(4);
    if (wgi == 2) {
        if (tid == 0) {
            for (int kt = 0; kt < 64; kt++) {
                const int st = kt % G_ST;
                if (kt >= G_ST) mbar_wait(bars + 8 * (G_ST + st), (kt / G_ST - 1) & 1);
                mbar_expect_tx(bars + 8 * st, 32768);
                tma2d(sb + st * 32768, &tm_o, kt * 64, m0, bars + 8 * st);
                tma2d(sb + st * 32768 + 16384, &tm_w, n0, kt * 64, bars + 8 * st);
                tma2d(sb + st * 32768 + 24576, &tm_w, n0 + 64, kt * 64, bars + 8 * st);
            }
        }
    } else {
        float d[64];
        int st = 0, ph = 0;
#pragma unroll 1
        for (int kt = 0; kt < 64; kt++) {
            mbar_wait(bars + 8 * st, ph);
            const uint64_t da = mkdesc(sb + st * 32768 + wgi * 8192, 16, 1024, 1), db = mkdesc(sb + st * 32768 + 16384, 8192, 1024, 1);
            wg_fence();
#pragma unroll
            for (int k = 0; k < 4; k++) wg_ss128(d, da + k * 2, db + k * 128, kt | k);
            wg_commit();
            if (kt > 0) {
                wg_wait<1>();
                if ((tid & 31) == 0) mbar_arrive(bars + 8 * (G_ST + (st == 0 ? G_ST - 1 : st - 1)));
            }
            if (++st == G_ST) { st = 0; ph ^= 1; }
        }
        wg_wait<0>();
        const int row = m0 + wgi * 64 + (tid >> 5) * 16 + ((tid & 31) >> 2);
        bf16* op = out + (size_t)row * 2048 + 1024 + n0 + (tid & 3) * 2;
#pragma unroll
        for (int i = 0; i < 16; i++) {
            *(uint32_t*)(op + i * 8) = pack_bf16(d[4 * i], d[4 * i + 1]);
            *(uint32_t*)(op + 8 * 2048 + i * 8) = pack_bf16(d[4 * i + 2], d[4 * i + 3]);
        }
        if (wgi == 0) GT(5);
    }
}

typedef CUresult (*EncodeFn)(CUtensorMap*, CUtensorMapDataType, cuuint32_t, void*, const cuuint64_t*, const cuuint64_t*,
                             const cuuint32_t*, const cuuint32_t*, CUtensorMapInterleave, CUtensorMapSwizzle,
                             CUtensorMapL2promotion, CUtensorMapFloatOOBfill);

static void make_map(EncodeFn fn, CUtensorMap* m, const void* p, uint64_t cols, uint64_t rows, uint32_t bc, uint32_t br) {
    cuuint64_t dims[2] = {cols, rows}, strides[1] = {cols * 2};
    cuuint32_t box[2] = {bc, br}, es[2] = {1, 1};
    fn(m, CU_TENSOR_MAP_DATA_TYPE_BFLOAT16, 2, (void*)p, dims, strides, box, es, CU_TENSOR_MAP_INTERLEAVE_NONE,
       CU_TENSOR_MAP_SWIZZLE_128B, CU_TENSOR_MAP_L2_PROMOTION_L2_128B, CU_TENSOR_MAP_FLOAT_OOB_FILL_NONE);
}

static Tune h_tune = {250, 0, {750, 1065, 1380, 1695}, 0};

extern "C" void kernel_launch(void* const* d_in, const int* in_sizes, int n_in, void* d_out, int out_size) {
    static bool init = false;
    static CUtensorMap tm_x, tm_wq, tm_wk, tm_wv, tm_wo, tm_o, tm_wo2;
    if (!init) {
        void* fp = nullptr; cudaDriverEntryPointQueryResult qr;
        cudaGetDriverEntryPoint("cuTensorMapEncodeTiled", &fp, cudaEnableDefault, &qr);
        EncodeFn fn = (EncodeFn)fp;
        void* ox = nullptr; cudaGetSymbolAddress(&ox, g_ox);
        make_map(fn, &tm_x, d_in[3], 1024, 2048, 64, 32);
        make_map(fn, &tm_wq, d_in[5], 4096, 1024, 64, 256);
        make_map(fn, &tm_wk, d_in[6], 4096, 1024, 64, 256);
        make_map(fn, &tm_wv, d_in[7], 4096, 1024, 64, 256);
        make_map(fn, &tm_wo, d_in[8], 1024, 4096, 64, 128);
        make_map(fn, &tm_o, ox, 4096, 2048, 64, 128);
        make_map(fn, &tm_wo2, d_in[8], 1024, 4096, 64, 64);
        cudaFuncSetAttribute(rmt_main, cudaFuncAttributeMaxDynamicSharedMemorySize, MAIN_SMEM);
        cudaFuncSetAttribute(out_gemm, cudaFuncAttributeMaxDynamicSharedMemorySize, G_SMEM);
        init = true;
    }
    rmt_main<<<132, 512, MAIN_SMEM>>>(tm_x, tm_wq, tm_wk, tm_wv, tm_wo, (const bf16*)d_in[4], h_tune);
    out_gemm<<<128, 384, G_SMEM>>>(tm_o, tm_wo2, (bf16*)d_out);
}
```

```cpp
#include <cuda_runtime.h>
#include <cuda_bf16.h>
#include <cuda.h>
#include <stdint.h>

typedef __nv_bfloat16 bf16;

#define DBG_TIMING 0

#define SPIN_LIMIT (1u << 22)

__device__ __forceinline__ uint32_t smem_u32(const void* p) { return (uint32_t)__cvta_generic_to_shared(p); }
__device__ __forceinline__ uint32_t clk() { uint32_t c; asm volatile("mov.u32 %0, %%clock;" : "=r"(c)::"memory"); return c; }
__device__ __forceinline__ void wait_clk(uint32_t t0, uint32_t d) { while (clk() - t0 < d) {} }

__device__ __forceinline__ void mbar_init(uint32_t bar, uint32_t cnt) {
    asm volatile("mbarrier.init.shared::cta.b64 [%0], %1;" ::"r"(bar), "r"(cnt) : "memory");
}
__device__ __forceinline__ void mbar_arrive(uint32_t bar) {
    asm volatile("mbarrier.arrive.shared::cta.b64 _, [%0];" ::"r"(bar) : "memory");
}
__device__ __forceinline__ void mbar_expect_tx(uint32_t bar, uint32_t bytes) {
    asm volatile("mbarrier.arrive.expect_tx.shared::cta.b64 _, [%0], %1;" ::"r"(bar), "r"(bytes) : "memory");
}
__device__ __forceinline__ void mbar_wait(uint32_t bar, uint32_t parity) {
    asm volatile(
        "{\n.reg .pred p;\n.reg .u32 n;\nmov.u32 n, 0;\n"
        "WL:\nmbarrier.try_wait.parity.shared::cta.b64 p, [%0], %1;\n@p bra WD;\n"
        "add.u32 n, n, 1;\nsetp.lt.u32 p, n, %2;\n@p bra WL;\ntrap;\nWD:\n}" ::"r"(bar), "r"(parity), "n"(SPIN_LIMIT) : "memory");
}
__device__ __forceinline__ void mbar_wait_cluster(uint32_t bar, uint32_t parity) {
    asm volatile(
        "{\n.reg .pred p;\n.reg .u32 n;\nmov.u32 n, 0;\n"
        "WL:\nmbarrier.try_wait.parity.acquire.cluster.shared::cta.b64 p, [%0], %1;\n@p bra WD;\n"
        "add.u32 n, n, 1;\nsetp.lt.u32 p, n, %2;\n@p bra WL;\ntrap;\nWD:\n}" ::"r"(bar), "r"(parity), "n"(SPIN_LIMIT) : "memory");
}
__device__ __forceinline__ void tma2d(uint32_t dst, const CUtensorMap* m, int c0, int c1, uint32_t bar) {
    asm volatile("cp.async.bulk.tensor.2d.shared::cluster.global.mbarrier::complete_tx::bytes [%0], [%1, {%3, %4}], [%2];"
                 ::"r"(dst), "l"(m), "r"(bar), "r"(c0), "r"(c1) : "memory");
}
__device__ __forceinline__ void tma4d(uint32_t dst, const CUtensorMap* m, int c2, int c3, uint32_t bar) {
    asm volatile("cp.async.bulk.tensor.4d.shared::cluster.global.mbarrier::complete_tx::bytes [%0], [%1, {%5, %5, %3, %4}], [%2];"
                 ::"r"(dst), "l"(m), "r"(bar), "r"(c2), "r"(c3), "r"(0) : "memory");
}
__device__ __forceinline__ void tma4d_prefetch(const CUtensorMap* m, int c2, int c3) {
    asm volatile("cp.async.bulk.prefetch.tensor.4d.L2.global [%0, {%3, %3, %1, %2}];" ::"l"(m), "r"(c2), "r"(c3), "r"(0) : "memory");
}
__device__ __forceinline__ void tma2d_prefetch(const CUtensorMap* m, int c0, int c1) {
    asm volatile("cp.async.bulk.prefetch.tensor.2d.L2.global [%0, {%1, %2}];" ::"l"(m), "r"(c0), "r"(c1) : "memory");
}
__device__ __forceinline__ void fence_async_smem() { asm volatile("fence.proxy.async.shared::cta;" ::: "memory"); }
__device__ __forceinline__ void fence_gpu() { asm volatile("fence.acq_rel.gpu;" ::: "memory"); }
__device__ __forceinline__ float rcp(float x) { float r; asm("rcp.approx.ftz.f32 %0, %1;" : "=f"(r) : "f"(x)); return r; }
__device__ __forceinline__ void bar_sync(int id, int n) { asm volatile("bar.sync %0, %1;" ::"r"(id), "r"(n) : "memory"); }

__device__ __forceinline__ uint32_t pack_bf16(float lo, float hi) {
    uint32_t r; asm("cvt.rn.bf16x2.f32 %0, %1, %2;" : "=r"(r) : "f"(hi), "f"(lo)); return r;
}
__device__ __forceinline__ uint32_t add_bf16x2(uint32_t a, uint32_t b) {
    uint32_t r; asm("add.rn.bf16x2 %0, %1, %2;" : "=r"(r) : "r"(a), "r"(b)); return r;
}
__device__ __forceinline__ uint32_t movm(uint32_t a) {
    uint32_t r; asm volatile("movmatrix.sync.aligned.m8n8.trans.b16 %0, %1;" : "=r"(r) : "r"(a)); return r;
}
__device__ __forceinline__ uint32_t orx(uint32_t acc, uint32_t a, uint32_t t) {
    uint32_t r; asm("lop3.b32 %0, %1, %2, %3, 0xF6;" : "=r"(r) : "r"(acc), "r"(a), "r"(t)); return r;
}
__device__ __forceinline__ uint32_t orx2(uint32_t a, uint32_t b, uint32_t t) {
    uint32_t r; asm("lop3.b32 %0, %1, %2, %3, 0x7E;" : "=r"(r) : "r"(a), "r"(b), "r"(t)); return r;
}
__device__ __forceinline__ float ex2(float x) { float r; asm("ex2.approx.ftz.f32 %0, %1;" : "=f"(r) : "f"(x)); return r; }
__device__ __forceinline__ void ldsm4t(uint32_t (&r)[4], uint32_t a) {
    asm volatile("ldmatrix.sync.aligned.m8n8.x4.trans.shared.b16 {%0,%1,%2,%3}, [%4];"
                 : "=r"(r[0]), "=r"(r[1]), "=r"(r[2]), "=r"(r[3]) : "r"(a) : "memory");
}
__device__ __forceinline__ void ldsm4(uint32_t (&r)[4], uint32_t a) {
    asm volatile("ldmatrix.sync.aligned.m8n8.x4.shared.b16 {%0,%1,%2,%3}, [%4];"
                 : "=r"(r[0]), "=r"(r[1]), "=r"(r[2]), "=r"(r[3]) : "r"(a) : "memory");
}
__device__ __forceinline__ void stsm4t(uint32_t a, uint32_t r0, uint32_t r1, uint32_t r2, uint32_t r3) {
    asm volatile("stmatrix.sync.aligned.m8n8.x4.trans.shared.b16 [%0], {%1,%2,%3,%4};"
                 ::"r"(a), "r"(r0), "r"(r1), "r"(r2), "r"(r3) : "memory");
}
__device__ __forceinline__ void stsm4(uint32_t a, uint32_t r0, uint32_t r1, uint32_t r2, uint32_t r3) {
    asm volatile("stmatrix.sync.aligned.m8n8.x4.shared.b16 [%0], {%1,%2,%3,%4};"
                 ::"r"(a), "r"(r0), "r"(r1), "r"(r2), "r"(r3) : "memory");
}
__device__ __forceinline__ void mma16816(float* c, uint32_t a0, uint32_t a1, uint32_t a2, uint32_t a3, uint32_t b0, uint32_t b1) {
    asm volatile("mma.sync.aligned.m16n8k16.row.col.f32.bf16.bf16.f32 {%0,%1,%2,%3}, {%4,%5,%6,%7}, {%8,%9}, {%0,%1,%2,%3};"
                 : "+f"(c[0]), "+f"(c[1]), "+f"(c[2]), "+f"(c[3]) : "r"(a0), "r"(a1), "r"(a2), "r"(a3), "r"(b0), "r"(b1));
}
__device__ __forceinline__ void mma1688(float* c, uint32_t a0, uint32_t a1, uint32_t b0) {
    asm volatile("mma.sync.aligned.m16n8k8.row.col.f32.bf16.bf16.f32 {%0,%1,%2,%3}, {%4,%5}, {%6}, {%0,%1,%2,%3};"
                 : "+f"(c[0]), "+f"(c[1]), "+f"(c[2]), "+f"(c[3]) : "r"(a0), "r"(a1), "r"(b0));
}
__device__ __forceinline__ void sts128(uint32_t a, float x, float y, float z, float w) {
    asm volatile("st.shared.v4.f32 [%0], {%1,%2,%3,%4};" ::"r"(a), "f"(x), "f"(y), "f"(z), "f"(w) : "memory");
}
__device__ __forceinline__ void sts64(uint32_t a, float x, float y) {
    asm volatile("st.shared.v2.f32 [%0], {%1,%2};" ::"r"(a), "f"(x), "f"(y) : "memory");
}
__device__ __forceinline__ void sts32(uint32_t a, uint32_t x) { asm volatile("st.shared.b32 [%0], %1;" ::"r"(a), "r"(x) : "memory"); }
__device__ __forceinline__ void sts128u(uint32_t a, uint4 v) {
    asm volatile("st.shared.v4.b32 [%0], {%1,%2,%3,%4};" ::"r"(a), "r"(v.x), "r"(v.y), "r"(v.z), "r"(v.w) : "memory");
}
__device__ __forceinline__ float4 lds128(uint32_t a) {
    float4 v; asm volatile("ld.shared.v4.f32 {%0,%1,%2,%3}, [%4];" : "=f"(v.x), "=f"(v.y), "=f"(v.z), "=f"(v.w) : "r"(a) : "memory"); return v;
}
__device__ __forceinline__ uint4 lds128u(uint32_t a) {
    uint4 v; asm volatile("ld.shared.v4.b32 {%0,%1,%2,%3}, [%4];" : "=r"(v.x), "=r"(v.y), "=r"(v.z), "=r"(v.w) : "r"(a) : "memory"); return v;
}
__device__ __forceinline__ float2 lds64(uint32_t a) {
    float2 v; asm volatile("ld.shared.v2.f32 {%0,%1}, [%2];" : "=f"(v.x), "=f"(v.y) : "r"(a) : "memory"); return v;
}
__device__ __forceinline__ uint2 ldg_rlx64(const void* p) {
    uint64_t v; asm volatile("ld.relaxed.gpu.global.b64 %0, [%1];" : "=l"(v) : "l"(p) : "memory");
    return make_uint2((uint32_t)v, (uint32_t)(v >> 32));
}
__device__ __forceinline__ uint4 ldg_rlx128(const void* p) {
    uint64_t a, b;
    asm volatile("{\n.reg .b128 t;\nld.relaxed.gpu.global.b128 t, [%2];\nmov.b128 {%0,%1}, t;\n}" : "=l"(a), "=l"(b) : "l"(p) : "memory");
    return make_uint4((uint32_t)a, (uint32_t)(a >> 32), (uint32_t)b, (uint32_t)(b >> 32));
}
__device__ __forceinline__ void stg_rlx64(void* p, uint32_t x, uint32_t y) {
    asm volatile("{\n.reg .b64 t;\nmov.b64 t, {%1,%2};\nst.relaxed.gpu.global.b64 [%0], t;\n}" ::"l"(p), "r"(x), "r"(y) : "memory");
}
__device__ __forceinline__ void stg_rlx128(void* p, uint32_t x, uint32_t y, uint32_t z, uint32_t w) {
    asm volatile("{\n.reg .b64 a, b;\n.reg .b128 t;\nmov.b64 a, {%1,%2};\nmov.b64 b, {%3,%4};\nmov.b128 t, {a,b};\nst.relaxed.gpu.global.b128 [%0], t;\n}"
                 ::"l"(p), "r"(x), "r"(y), "r"(z), "r"(w) : "memory");
}
__device__ __forceinline__ uint32_t ldg_rlx32(const void* p) {
    uint32_t v; asm volatile("ld.relaxed.gpu.global.b32 %0, [%1];" : "=r"(v) : "l"(p) : "memory"); return v;
}
__device__ __forceinline__ void stg128(void* p, uint32_t x, uint32_t y, uint32_t z, uint32_t w) {
    asm volatile("st.global.v4.b32 [%0], {%1,%2,%3,%4};" ::"l"(p), "r"(x), "r"(y), "r"(z), "r"(w) : "memory");
}
__device__ __forceinline__ uint32_t ld_acquire(const unsigned* p) {
    uint32_t v; asm volatile("ld.acquire.gpu.global.u32 %0, [%1];" : "=r"(v) : "l"(p) : "memory"); return v;
}
__device__ __forceinline__ void red_add_u32(unsigned* p, uint32_t v) {
    asm volatile("red.relaxed.gpu.global.add.u32 [%0], %1;" ::"l"(p), "r"(v) : "memory");
}
__device__ __forceinline__ void wait_counter(const unsigned* p, uint32_t target) {
    uint32_t n = 0;
    while (ld_acquire(p) < target) { if (++n > SPIN_LIMIT) __trap(); }
}

__device__ __forceinline__ void wg_fence() { asm volatile("wgmma.fence.sync.aligned;" ::: "memory"); }
__device__ __forceinline__ void wg_commit() { asm volatile("wgmma.commit_group.sync.aligned;" ::: "memory"); }
template <int N> __device__ __forceinline__ void wg_wait() { asm volatile("wgmma.wait_group.sync.aligned %0;" ::"n"(N) : "memory"); }
__host__ __device__ constexpr uint64_t mkdesc(uint32_t addr, uint32_t lbo, uint32_t sbo, uint32_t swz) {
    return (uint64_t)((addr & 0x3FFFF) >> 4) | ((uint64_t)(lbo >> 4) << 16) | ((uint64_t)(sbo >> 4) << 32) | ((uint64_t)swz << 62);
}
#define F4(d, o) "+f"(d[o]), "+f"(d[o + 1]), "+f"(d[o + 2]), "+f"(d[o + 3])
template <int SC> __device__ __forceinline__ void wg_rs32(float (&d)[16], const uint32_t (&a)[4], uint64_t db) {
    asm volatile("wgmma.mma_async.sync.aligned.m64n32k16.f32.bf16.bf16 "
                 "{%0,%1,%2,%3,%4,%5,%6,%7,%8,%9,%10,%11,%12,%13,%14,%15}, {%16,%17,%18,%19}, %20, %21, 1, 1, 0;"
                 : F4(d, 0), F4(d, 4), F4(d, 8), F4(d, 12)
                 : "r"(a[0]), "r"(a[1]), "r"(a[2]), "r"(a[3]), "l"(db), "n"(SC));
}
template <int SC> __device__ __forceinline__ void wg_ss40(float (&d)[20], uint64_t da, uint64_t db) {
    asm volatile("wgmma.mma_async.sync.aligned.m64n40k16.f32.bf16.bf16 "
                 "{%0,%1,%2,%3,%4,%5,%6,%7,%8,%9,%10,%11,%12,%13,%14,%15,%16,%17,%18,%19}, %20, %21, %22, 1, 1, 1, 0;"
                 : F4(d, 0), F4(d, 4), F4(d, 8), F4(d, 12), F4(d, 16)
                 : "l"(da), "l"(db), "n"(SC));
}
template <int SC> __device__ __forceinline__ void wg_ss8(float (&d)[4], uint64_t da, uint64_t db) {
    asm volatile("wgmma.mma_async.sync.aligned.m64n8k16.f32.bf16.bf16 {%0,%1,%2,%3}, %4, %5, %6, 1, 1, 1, 1;"
                 : F4(d, 0) : "l"(da), "l"(db), "n"(SC));
}

__device__ uint4 g_kvq[4 * 32 * 3 * 8 * 2 * 32];
__device__ uint2 g_alpha[2 * 32 * 3 * 8 * 2 * 32];
__device__ uint4 g_red[(4 * 65536 + 32768) / 16];
__device__ unsigned g_start;
__device__ bf16 g_ox[2048 * 4096];
#define TSI(st) do {} while (0)
#define TS(k) do {} while (0)
#define TSV(k, v) do {} while (0)
#define TSDUMP() do {} while (0)
#define GT(k) do {} while (0)
#define FLAG(b) false

struct Tune { uint32_t d_alpha, d_r0, d_r1, flags; };
#define RED_F32 0
#define V_FIRST 16

constexpr uint32_t SM_BASE = 1024;
constexpr uint32_t O_WO = 0;
constexpr uint32_t O_WV = 65536;
constexpr uint32_t O_XB = 131072;
constexpr uint32_t O_MEM = O_XB + 32768;
constexpr uint32_t O_RECV = O_MEM + 8192;
constexpr uint32_t O_S = O_RECV + 24576 + 1024;
constexpr uint32_t O_O = O_S + 10240;
constexpr uint32_t O_XO = O_O + 2048;
constexpr uint32_t O_BAR = O_XO + 2048;
constexpr uint32_t O_DBG = O_BAR + 256;
constexpr uint32_t MAIN_SMEM = O_DBG + (DBG_TIMING ? 4 * 32 * 24 * 4 : 0);
enum { B_WQ0 = 0, B_WQ1, B_WK0, B_WK1, B_WV, B_WO, B_QDONE, B_KDONE, B_XFULL, B_XEMPTY, B_MEM0, B_MEM1, B_MEM2, B_MEM3,
       B_RECV, B_QKA = B_RECV + 6, B_QKB, B_AV, B_SDONE, B_SRDY, B_SFREE, B_OPDONE, B_COUNT };

constexpr float SM_SCALE_LOG2 = 0.08838834764831845f * 1.4426950408889634f;
constexpr float MASK_VAL = -1.0e9f / 0.08838834764831845f;

__host__ __device__ constexpr uint32_t red_slot(int i) { return (uint32_t)((i >> 2) * 32768 + (i & 1) * 128 + ((i >> 1) & 1) * 512); }
__device__ __forceinline__ uint32_t red_grp(int grp) { return (uint32_t)((grp >> 1) * 1024 + (grp & 1) * 256); }
__host__ __device__ constexpr int ks_order(int i) { return (((i >> 3) & 1) * 4 + (i >> 4) * 2 + ((i >> 2) & 1)) * 4 + (i & 3); }
__host__ __device__ constexpr uint64_t xdesc(int ks) { return mkdesc(SM_BASE + O_XB + (ks >> 2) * 1024 + (ks & 3) * 32, 16, 8192, 1); }

template <int R>
__device__ __forceinline__ void x_send(const float* d, float (&k)[8], int sg, int kh, int tid, uint32_t sb, uint32_t mate) {
    const uint32_t par = sg & 1;
    const uint32_t bar = O_BAR + 8 * (B_RECV + R * 2) + 8 * par;
    const uint32_t slot = O_RECV + (par * 3 + R) * 4096 + tid * 16;
    if (tid == 0) mbar_expect_tx(sb + bar, 4096);
    float s[8];
#pragma unroll
    for (int i = 0; i < 8; i++) { s[i] = kh ? d[i] : d[8 + i]; k[i] = kh ? d[8 + i] : d[i]; }
#pragma unroll
    for (int v = 0; v < 2; v++)
        asm volatile("st.async.shared::cluster.mbarrier::complete_tx::bytes.v4.f32 [%0], {%1,%2,%3,%4}, [%5];"
                     ::"r"(mate + slot + v * 2048), "f"(s[4 * v]), "f"(s[4 * v + 1]), "f"(s[4 * v + 2]), "f"(s[4 * v + 3]), "r"(mate + bar) : "memory");
}
template <int R>
__device__ __forceinline__ void x_finish(const float (&k)[8], int sg, uint32_t frag, int tid, uint32_t sb) {
    const uint32_t par = sg & 1;
    const uint32_t slot = O_RECV + (par * 3 + R) * 4096 + tid * 16;
    mbar_wait_cluster(sb + O_BAR + 8 * (B_RECV + R * 2) + 8 * par, (sg >> 1) & 1);
    float4 r0 = lds128(sb + slot), r1 = lds128(sb + slot + 2048);
    uint32_t u0 = pack_bf16(k[0] + r0.x, k[1] + r0.y), u1 = pack_bf16(k[2] + r0.z, k[3] + r0.w);
    uint32_t u2 = pack_bf16(k[4] + r1.x, k[5] + r1.y), u3 = pack_bf16(k[6] + r1.z, k[7] + r1.w);
    if (R < 2) { u0 = movm(u0); u1 = movm(u1); u2 = movm(u2); u3 = movm(u3); }
    const uint32_t tag = ((sg >> 2) & 1) ^ 1;
    u0 = (u0 & ~1u) | tag;
    if (R == 0) u2 = (u2 & ~1u) | tag;
    stg_rlx128(&g_kvq[(sg & 3) * (32 * 3 * 512) + R * 512 + frag], u0, u1, u2, u3);
}
template <int R>
__device__ __forceinline__ void alpha_write(float d0, float d1, float d2, float d3, int s, uint32_t frag) {
    uint32_t u0 = pack_bf16(d0, d1), u1 = pack_bf16(d2, d3);
    if (R < 2) { u0 = movm(u0); u1 = movm(u1); }
    u0 = (u0 & ~1u) | (((s >> 1) & 1) ^ 1);
    stg_rlx64(&g_alpha[(s & 1) * (32 * 3 * 512) + R * 512 + frag], u0, u1);
}

__device__ __forceinline__ void softmax10(float (&sc)[10], uint32_t (&pf)[5], float& sum) {
    float m = fmaxf(fmaxf(fmaxf(sc[0], sc[1]), fmaxf(sc[2], sc[3])), fmaxf(fmaxf(sc[4], sc[5]), fmaxf(sc[6], sc[7])));
    m = fmaxf(m, fmaxf(sc[8], sc[9]));
    m = fmaxf(m, __shfl_xor_sync(~0u, m, 1));
    m = fmaxf(m, __shfl_xor_sync(~0u, m, 2));
    const float mb = -m * SM_SCALE_LOG2;
#pragma unroll
    for (int i = 0; i < 10; i++) sc[i] = ex2(fmaf(sc[i], SM_SCALE_LOG2, mb));
#pragma unroll
    for (int n = 0; n < 5; n++) pf[n] = pack_bf16(sc[2 * n], sc[2 * n + 1]);
    sum = ((sc[0] + sc[1]) + (sc[2] + sc[3])) + ((sc[4] + sc[5]) + (sc[6] + sc[7])) + (sc[8] + sc[9]);
}

__global__ void __cluster_dims__(2, 1, 1) __launch_bounds__(512, 1)
rmt_main(const __grid_constant__ CUtensorMap tm_x, const __grid_constant__ CUtensorMap tm_wq, const __grid_constant__ CUtensorMap tm_wk,
         const __grid_constant__ CUtensorMap tm_wv, const __grid_constant__ CUtensorMap tm_wo, const bf16* __restrict__ mem0, const Tune tn) {
    extern __shared__ __align__(1024) unsigned char smem_raw[];
    const uint32_t sb = smem_u32(smem_raw);
    if ((sb & 0x3FFFF) != SM_BASE) __trap();
    const int cid = blockIdx.x >> 1, kh = blockIdx.x & 1;
    const int tpc = cid < 4 ? 62 + cid : cid - 4;
    int h, nh;
    if (tpc < 32) { h = (tpc >> 4) * 8 + (tpc & 7); nh = (tpc >> 3) & 1; }
    else if (tpc < 60) { int u = tpc - 32, r = u % 14; h = 16 + (u / 14) * 7 + r % 7; nh = r / 7; }
    else if (tpc < 62) return;
    else { h = 30 + ((tpc - 62) >> 1); nh = tpc & 1; }
    const int j = nh * 2 + kh, role = h * 4 + j;
    const int wgi = __shfl_sync(~0u, threadIdx.x >> 7, 0);
    const int tid = threadIdx.x & 127, w = tid >> 5, lane = tid & 31;
#define OPAQUE_IDS() int tid_ = tid; asm volatile("" : "+r"(tid_)); const int tid = tid_, w = tid_ >> 5, lane = tid_ & 31; (void)w; (void)lane
    unsigned char* const redp = (unsigned char*)(((uintptr_t)g_red + 32767) & ~(uintptr_t)32767);
    const uint32_t bars = sb + O_BAR;

    if (threadIdx.x == 0) {
        const uint8_t cnts[B_COUNT] = {1, 1, 1, 1, 1, 1, 4, 4, 1, 8, 1, 1, 1, 1, 1, 1, 1, 1, 1, 1, 8, 8, 4, 4, 4, 4, 4};
#pragma unroll
        for (int i = 0; i < B_COUNT; i++) mbar_init(bars + 8 * i, cnts[i]);
        asm volatile("fence.mbarrier_init.release.cluster;" ::: "memory");
        fence_async_smem();
        const int c0 = h * 128 + nh * 64, r0 = kh * 512;
        for (int i = 0; i < 2; i++) {
            mbar_expect_tx(bars + 8 * (B_WK0 + i), 32768);
            tma2d(sb + O_XB + i * 32768, &tm_wk, c0, r0 + i * 256, bars + 8 * (B_WK0 + i));
            mbar_expect_tx(bars + 8 * (B_WQ0 + i), 32768);
            tma2d(sb + O_WO + i * 32768, &tm_wq, c0, r0 + i * 256, bars + 8 * (B_WQ0 + i));
        }
        mbar_expect_tx(bars + 8 * B_WV, 65536);
        for (int i = 0; i < 2; i++) tma2d(sb + O_WV + i * 32768, &tm_wv, c0, r0 + i * 256, bars + 8 * B_WV);
        for (int i = 0; i < 4; i++) tma2d_prefetch(&tm_wo, j * 256 + i * 64, h * 128);
        tma4d_prefetch(&tm_x, kh * 8, (role >> 1) * 4);
    }
    __syncthreads();
    uint32_t mate;
    asm volatile("mapa.shared::cluster.u32 %0, %1, %2;" : "=r"(mate) : "r"(sb), "r"(kh ^ 1));

    if (wgi < 2) {
        asm volatile("setmaxnreg.inc.sync.aligned.u32 176;");
        uint32_t a[32][4];
        {
            const uint32_t stage = sb + (wgi == 0 ? O_WO : O_XB);
            const uint32_t ad = stage + (((lane >> 4) & 1) * 8 + (lane & 7)) * 128 + (((2 * w + ((lane >> 3) & 1)) ^ (lane & 7)) << 4);
#pragma unroll
            for (int i = 0; i < 2; i++) {
                mbar_wait(bars + 8 * (B_WQ0 + 2 * wgi + i), 0);
#pragma unroll
                for (int ks = 0; ks < 16; ks++) ldsm4t(a[i * 16 + ks], ad + (i * 16 + ks) * 2048);
            }
            __syncwarp();
            if (lane == 0) mbar_arrive(bars + 8 * (B_QDONE + wgi));
        }
        asm volatile("barrier.cluster.arrive.release.aligned;" ::: "memory");
        asm volatile("barrier.cluster.wait.acquire.aligned;" ::: "memory");
        const uint32_t frag = h * (3 * 512) + ((nh * 4 + w) * 2 + kh) * 32 + lane;
        const uint32_t mb0 = sb + O_MEM + (lane & 7) * 128 + (((lane >> 3) ^ (lane & 7)) << 4);
#define PHASE_A(R)                                                                                     \
        {                                                                                              \
            float e[2][4];                                                                             \
            _Pragma("unroll") for (int i = 0; i < 4; i++) e[0][i] = e[1][i] = 0.f;                     \
            _Pragma("unroll") for (int it = 0; it < 4; it++) {                                         \
                mbar_wait(bars + 8 * (B_MEM0 + it), s & 1);                                            \
                if (it == 0) TS(0); else if (it == 1) TS(1); else if (it == 2) TS(2); else TS(3);                                                                               \
                _Pragma("unroll") for (int q = 0; q < 4; q++) {                                        \
                    const int ks = ks_order(it * 8 + q * 2);                                           \
                    uint32_t b[4];                                                                     \
                    ldsm4(b, (mb0 ^ ((ks & 2) << 5)) + (ks >> 2) * 1024);                              \
                    mma16816(e[0], a[ks][0], a[ks][1], a[ks][2], a[ks][3], b[0], b[1]);                \
                    mma16816(e[1], a[ks + 1][0], a[ks + 1][1], a[ks + 1][2], a[ks + 1][3], b[2], b[3]); \
                }                                                                                      \
                if ((it & 1) && lane == 0) mbar_arrive(bars + 8 * (B_QKA + (it >> 1)));                \
            }                                                                                          \
            TS(4);                                                                                     \
            alpha_write<R>(e[0][0] + e[1][0], e[0][1] + e[1][1], e[0][2] + e[1][2], e[0][3] + e[1][3], s, frag); \
            TS(5);                                                                                     \
        }
        if (wgi == 0) {
#pragma unroll 1
            for (int s = -1; s < 64; s++) {
                TSI(s);
                float kp[8];
                if (s < 63) {
                    float d[16];
                    mbar_wait(bars + 8 * B_XFULL, (s + 1) & 1);
                    if (s >= 1) mbar_wait(bars + 8 * B_OPDONE, (s - 1) & 1);
                    TS(6);
                    if (!FLAG(1)) {
                    wg_fence();
#pragma unroll
                    for (int ks = 0; ks < 32; ks++) { if (ks == 0) wg_rs32<0>(d, a[ks], xdesc(ks)); else wg_rs32<1>(d, a[ks], xdesc(ks)); }
                    wg_commit();
                    }
                    wg_wait<0>();
                    TS(7);
                    if (lane == 0) mbar_arrive(bars + 8 * B_XEMPTY);
                    if (!FLAG(0)) x_send<0>(d, kp, s + 1, kh, tid, sb, mate);
                    TS(8);
                }
                if (s >= 0) PHASE_A(0);
                if (s < 63 && !FLAG(0)) x_finish<0>(kp, s + 1, frag, tid, sb);
                TS(9);
            }
        } else {
#pragma unroll 1
            for (int s = -1; s < 64; s++) {
                TSI(s);
                if (s >= 0) PHASE_A(1);
                if (s < 63) {
                    float d[16], kp[8];
                    mbar_wait(bars + 8 * B_XFULL, (s + 1) & 1);
                    mbar_wait(bars + 8 * B_AV, (s + 1) & 1);
                    TS(6);
                    if (!FLAG(1)) {
                    wg_fence();
#pragma unroll
                    for (int ks = 0; ks < 16; ks++) { if (ks == 0) wg_rs32<0>(d, a[ks], xdesc(ks)); else wg_rs32<1>(d, a[ks], xdesc(ks)); }
                    wg_commit();
                    }
                    if (s >= 0) mbar_wait(bars + 8 * B_SDONE, s & 1);
                    TS(7);
                    if (!FLAG(1)) {
                    wg_fence();
#pragma unroll
                    for (int ks = 16; ks < 32; ks++) wg_rs32<1>(d, a[ks], xdesc(ks));
                    wg_commit();
                    }
                    wg_wait<0>();
                    TS(8);
                    if (lane == 0) mbar_arrive(bars + 8 * B_XEMPTY);
                    if (tid == 0 && s < 62) {
                        mbar_wait(bars + 8 * B_XEMPTY, (s + 1) & 1);
                        if (FLAG(2)) mbar_arrive(bars + 8 * B_XFULL);
                        else {
                        mbar_expect_tx(bars + 8 * B_XFULL, 32768);
                        tma4d(sb + O_XB, &tm_x, kh * 8, (s + 2) * 4, bars + 8 * B_XFULL);
                        }
                    }
                    __syncwarp();
                    if (!FLAG(0)) x_send<1>(d, kp, s + 1, kh, tid, sb, mate);
                    if (!FLAG(0)) x_finish<1>(kp, s + 1, frag, tid, sb);
                    TS(9);
                }
            }
        }
        TSDUMP();
    } else if (wgi == 2) {
        asm volatile("setmaxnreg.dec.sync.aligned.u32 64;");
        asm volatile("barrier.cluster.arrive.release.aligned;" ::: "memory");
        if (tid == 0) {
            mbar_wait(bars + 8 * B_KDONE, 0);
            mbar_expect_tx(bars + 8 * B_XFULL, 32768);
            tma4d(sb + O_XB, &tm_x, kh * 8, 0, bars + 8 * B_XFULL);
            mbar_wait(bars + 8 * B_QDONE, 0);
            mbar_expect_tx(bars + 8 * B_WO, 65536);
            for (int i = 0; i < 4; i++) tma2d(sb + O_WO + i * 16384, &tm_wo, j * 256 + i * 64, h * 128, bars + 8 * B_WO);
        }
        __syncwarp();
        asm volatile("barrier.cluster.wait.acquire.aligned;" ::: "memory");
        mbar_wait(bars + 8 * B_WV, 0);
#pragma unroll 1
        for (int s = -1; s < 64; s++) {
            TSI(s);
            OPAQUE_IDS();
            const uint32_t frag = h * (3 * 512) + ((nh * 4 + w) * 2 + kh) * 32 + lane;
            float d[20];
            if (s < 63) mbar_wait(bars + 8 * B_XFULL, (s + 1) & 1);
            if (s >= 0) mbar_wait(bars + 8 * B_QKA, s & 1);
            TS(0);
            wg_fence();
#pragma unroll
            for (int i = 0; i < 32; i++) {
                if (i == V_FIRST) {
                    wg_commit();
                    if (s >= 0) mbar_wait(bars + 8 * B_QKB, s & 1);
                    TS(1);
                    wg_fence();
                }
                const int ks = ks_order(i);
                constexpr uint64_t da0 = mkdesc(SM_BASE + O_WV, 16, 1024, 1);
                if (i == 0) wg_ss40<0>(d, da0 + ks * 128, xdesc(ks)); else wg_ss40<1>(d, da0 + ks * 128, xdesc(ks));
            }
            wg_commit();
            wg_wait<0>();
            TS(2);
            if (s >= 0) alpha_write<2>(d[16], d[17], d[18], d[19], s, frag);
            if (lane == 0) mbar_arrive(bars + 8 * B_AV);
            TS(3);
            if (s < 63) {
                float kp[8];
                if (!FLAG(0)) x_send<2>(d, kp, s + 1, kh, tid, sb, mate);
                if (!FLAG(0)) x_finish<2>(kp, s + 1, frag, tid, sb);
            }
            TS(4);
            if (s >= 0) {
                mbar_wait(bars + 8 * B_SRDY, s & 1);
                TS(5);
                if (FLAG(3)) { if (lane == 0) mbar_arrive(bars + 8 * B_SFREE); continue; }
                uint4 vf[4]; uint2 vm[4];
                const uint4* vp = &g_kvq[((s & 3) * 32 + h) * (3 * 512) + 1024 + w * 128 + lane];
                const uint2* ap = &g_alpha[((s & 1) * 32 + h) * (3 * 512) + 1024 + w * 128 + lane];
#pragma unroll
                for (int i = 0; i < 4; i++) { vf[i] = ldg_rlx128(vp + i * 32); vm[i] = ldg_rlx64(ap + i * 32); }
                float sc[10];
#pragma unroll
                for (int i = 0; i < 10; i++) sc[i] = 0.f;
#pragma unroll
                for (int q = 0; q < 4; q++) {
                    const uint32_t a0 = sb + O_S + 5120;
                    float4 x0 = lds128(a0 + q * 512 + lane * 16), x1 = lds128(a0 + 2048 + q * 512 + lane * 16);
                    float2 x2 = lds64(a0 + 4096 + q * 256 + lane * 8);
                    sc[0] += x0.x; sc[1] += x0.y; sc[2] += x0.z; sc[3] += x0.w; sc[4] += x1.x; sc[5] += x1.y; sc[6] += x1.z; sc[7] += x1.w;
                    sc[8] += x2.x; sc[9] += x2.y;
                }
                __syncwarp();
                if (lane == 0) mbar_arrive(bars + 8 * B_SFREE);
                const int lim = 8 * j + (lane >> 2) - 2 * (lane & 3);
#pragma unroll
                for (int i = 2; i < 10; i++) if (8 * ((i >> 1) - 1) + (i & 1) > lim) sc[i] = MASK_VAL;
                uint32_t pf[5]; float sum;
                softmax10(sc, pf, sum);
                sum += __shfl_xor_sync(~0u, sum, 1);
                sum += __shfl_xor_sync(~0u, sum, 2);
                const float inv = rcp(sum);
                const float i0 = __shfl_sync(~0u, inv, (lane & 3) * 8), i1 = __shfl_sync(~0u, inv, (lane & 3) * 8 + 4);
                uint32_t ow[4];
#pragma unroll
                for (int u = 0; u < 2; u++) {
                    float o[4] = {0.f, 0.f, 0.f, 0.f};
                    mma1688(o, add_bf16x2(vm[2 * u].x, vm[2 * u + 1].x), add_bf16x2(vm[2 * u].y, vm[2 * u + 1].y), pf[0]);
                    mma16816(o, vf[2 * u].x, vf[2 * u].y, vf[2 * u].z, vf[2 * u].w, pf[1], pf[2]);
                    mma16816(o, vf[2 * u + 1].x, vf[2 * u + 1].y, vf[2 * u + 1].z, vf[2 * u + 1].w, pf[3], pf[4]);
                    ow[2 * u] = pack_bf16(o[0] * i0, o[1] * i1);
                    ow[2 * u + 1] = pack_bf16(o[2] * i0, o[3] * i1);
                }
                const uint32_t xo = sb + O_XO + w * 512;
                stsm4t(xo + (lane & 7) * 64 + (((lane >> 3) ^ ((lane >> 1) & 3)) << 4), ow[0], ow[1], ow[2], ow[3]);
                __syncwarp();
                const uint4 ov = lds128u(xo + (lane >> 2) * 64 + (((lane & 3) ^ ((lane >> 3) & 3)) << 4));
                stg128(&g_ox[(size_t)(s * 32 + j * 8 + (lane >> 2)) * 4096 + h * 128 + w * 32 + (lane & 3) * 8], ov.x, ov.y, ov.z, ov.w);
                __syncwarp();
            }
            TS(6);
        }
        TSDUMP();
    } else {
        asm volatile("setmaxnreg.dec.sync.aligned.u32 96;");
        GT(0);
        asm volatile("barrier.cluster.arrive.release.aligned;" ::: "memory");
#define RED_CLEAR(st)                                                                                           \
        {                                                                                                       \
            unsigned char* zp = redp + ((st) & 3) * 65536 + (role >> 6) * 32768 + red_grp(role & 63) + red_slot(lane >> 3) + (lane & 7) * 16; \
            const uint32_t cb = RED_F32 ? __float_as_uint(64.f * (st)) : (((st) & 4) ? 0x42800000u : 0u);       \
            const uint32_t cz = (!RED_F32 && role >= 64) ? cb : 0u;                                             \
            stg128(zp, cz, cz, cz, cb);                                                                         \
        }
        uint32_t start_target = 0;
        if (w == 0) {
            RED_CLEAR(0); RED_CLEAR(1);
            fence_gpu();
            __syncwarp();
            if (lane == 0) start_target = (atomicAdd(&g_start, 1) & ~127u) + 128;
        }
        mbar_wait(bars + 8 * B_KDONE, 0);
        {
            const int kb0 = (w & 1) * 4 + (w >> 1) * 2;
#pragma unroll
            for (int q = 0; q < 4; q++) {
                const int row = (lane >> 3) + (q & 1) * 4, ch = lane & 7, kb = kb0 + (q >> 1);
                const uint4 v = *(const uint4*)(mem0 + row * 1024 + kh * 512 + kb * 64 + ch * 8);
                sts128u(sb + O_MEM + kb * 1024 + row * 128 + ((ch ^ row) << 4), v);
            }
            fence_async_smem();
            __syncwarp();
            if (lane == 0) mbar_arrive(bars + 8 * (B_MEM0 + w));
        }
        asm volatile("barrier.cluster.wait.acquire.aligned;" ::: "memory");
        if (tid == 0) { uint32_t n = 0; while ((int)(ld_acquire(&g_start) - start_target) < 0) { if (++n > SPIN_LIMIT) __trap(); } }
        mbar_wait(bars + 8 * B_WO, 0);
        GT(1);
        const uint32_t d_r = w >> 1 ? tn.d_r1 : tn.d_r0;
#pragma unroll 1
        for (int s = 0; s < 64; s++) {
            TSI(s);
            OPAQUE_IDS();
            uint4 kf[4], vf[4]; uint2 qf[2];
            {
                const uint4* bp = &g_kvq[((s & 3) * 32 + h) * (3 * 512) + w * 128 + lane];
                const uint32_t tg = ((s >> 2) & 1) ^ 1;
                uint32_t n = 0;
                while (true) {
#pragma unroll
                    for (int i = 0; i < 4; i++) kf[i] = ldg_rlx128(bp + 512 + i * 32);
#pragma unroll
                    for (int u = 0; u < 2; u++) qf[u] = ldg_rlx64((const uint2*)(bp + (2 * u + nh) * 32) + kh);
#pragma unroll
                    for (int i = 0; i < 4; i++) vf[i] = ldg_rlx128(bp + 1024 + i * 32);
                    const uint32_t x = orx2(kf[0].x, kf[1].x, tg) | orx2(kf[2].x, kf[3].x, tg) | orx2(qf[0].x, qf[1].x, tg) |
                                       orx2(vf[0].x, vf[1].x, tg) | orx2(vf[2].x, vf[3].x, tg);
                    if (!__any_sync(~0u, x & 1) || FLAG(0)) break;
                    if (++n > SPIN_LIMIT) __trap();
                }
                if (w == 0) TSV(22, n);
            }
            if (w == 0 && s < 62) RED_CLEAR(s + 2);
            if (s > 0) mbar_wait(bars + 8 * B_SFREE, (s - 1) & 1);
            const uint32_t tag = ((s >> 1) & 1) ^ 1;
            const uint2* ap = &g_alpha[((s & 1) * 32 + h) * (3 * 512) + w * 128 + lane];
            const uint32_t s16 = sb + O_S + tid * 16, s8 = sb + O_S + 4096 + tid * 8;
            TS(0);
            mbar_wait(bars + 8 * B_QKB, s & 1);
            TS(1);
            wait_clk(clk(), tn.d_alpha);
            uint2 qa[4], ka[4];
            {
                uint32_t n = 0;
                while (true) {
#pragma unroll
                    for (int i = 0; i < 4; i++) { qa[i] = ldg_rlx64(ap + i * 32); ka[i] = ldg_rlx64(ap + 512 + i * 32); }
                    const uint32_t x = orx2(qa[0].x, ka[0].x, tag) | orx2(qa[1].x, ka[1].x, tag) | orx2(qa[2].x, ka[2].x, tag) | orx2(qa[3].x, ka[3].x, tag);
                    if (!__any_sync(~0u, x & 1)) break;
                    if (++n > SPIN_LIMIT) __trap();
                }
                if (w == 0) TSV(20, n);
            }
            TS(2);
            float sa[5][4];
#pragma unroll
            for (int n = 0; n < 5; n++) sa[n][0] = sa[n][1] = sa[n][2] = sa[n][3] = 0.f;
#pragma unroll
            for (int u = 0; u < 2; u++) {
                const uint32_t q0 = add_bf16x2(qa[2 * u].x, qa[2 * u + 1].x), q1 = add_bf16x2(qa[2 * u].y, qa[2 * u + 1].y);
                const uint32_t k0 = add_bf16x2(ka[2 * u].x, ka[2 * u + 1].x), k1 = add_bf16x2(ka[2 * u].y, ka[2 * u + 1].y);
                mma16816(sa[1], q0, qf[u].x, q1, qf[u].y, kf[2 * u].x, kf[2 * u].y);
                mma16816(sa[0], q0, qf[u].x, q1, qf[u].y, k0, k1);
                mma16816(sa[2], q0, qf[u].x, q1, qf[u].y, kf[2 * u].z, kf[2 * u].w);
                mma16816(sa[3], q0, qf[u].x, q1, qf[u].y, kf[2 * u + 1].x, kf[2 * u + 1].y);
                mma16816(sa[4], q0, qf[u].x, q1, qf[u].y, kf[2 * u + 1].z, kf[2 * u + 1].w);
            }
            uint2 va[4];
#pragma unroll
            for (int i = 0; i < 4; i++) va[i] = ldg_rlx64(ap + 1024 + i * 32);
            sts128(s16, sa[0][0], sa[0][1], sa[1][0], sa[1][1]);
            sts128(s16 + 2048, sa[2][0], sa[2][1], sa[3][0], sa[3][1]);
            sts64(s8, sa[4][0], sa[4][1]);
            bar_sync(1, 128);
            if (lane == 0) mbar_arrive(bars + 8 * B_SDONE);
            TS(15);
            float sc[10];
#pragma unroll
            for (int n = 0; n < 5; n++) { sc[2 * n] = sa[n][0]; sc[2 * n + 1] = sa[n][1]; }
#pragma unroll
            for (int q = 1; q < 4; q++) {
                float4 x0 = lds128(s16 ^ (q * 512)), x1 = lds128((s16 ^ (q * 512)) + 2048); float2 x2 = lds64(s8 ^ (q * 256));
                sc[0] += x0.x; sc[1] += x0.y; sc[2] += x0.z; sc[3] += x0.w; sc[4] += x1.x; sc[5] += x1.y; sc[6] += x1.z; sc[7] += x1.w;
                sc[8] += x2.x; sc[9] += x2.y;
            }
            sts128(s16 + 5120, sa[0][2], sa[0][3], sa[1][2], sa[1][3]);
            sts128(s16 + 5120 + 2048, sa[2][2], sa[2][3], sa[3][2], sa[3][3]);
            sts64(s8 + 5120, sa[4][2], sa[4][3]);
            uint32_t pf[5]; float sum;
            softmax10(sc, pf, sum);
            TS(3);
            float o[2][4];
#pragma unroll
            for (int u = 0; u < 2; u++) {
                o[u][0] = o[u][1] = o[u][2] = o[u][3] = 0.f;
                mma16816(o[u], vf[2 * u].x, vf[2 * u].y, vf[2 * u].z, vf[2 * u].w, pf[1], pf[2]);
            }
#pragma unroll
            for (int u = 0; u < 2; u++) mma16816(o[u], vf[2 * u + 1].x, vf[2 * u + 1].y, vf[2 * u + 1].z, vf[2 * u + 1].w, pf[3], pf[4]);
            {
                uint32_t n = 0;
                while (__any_sync(~0u, (orx2(va[0].x, va[1].x, tag) | orx2(va[2].x, va[3].x, tag)) & 1)) {
#pragma unroll
                    for (int i = 0; i < 4; i++) va[i] = ldg_rlx64(ap + 1024 + i * 32);
                    if (++n > SPIN_LIMIT) __trap();
                }
                if (w == 0) TSV(21, n);
            }
#pragma unroll
            for (int u = 0; u < 2; u++)
                mma1688(o[u], add_bf16x2(va[2 * u].x, va[2 * u + 1].x), add_bf16x2(va[2 * u].y, va[2 * u + 1].y), pf[0]);
            TS(4);
            {
                const uint32_t oa = sb + O_O + w * 512 + lane * 4;
                sts32(oa, pack_bf16(o[0][0], o[0][1]));
                sts32(oa + 128, pack_bf16(o[0][2], o[0][3]));
                sts32(oa + 256, pack_bf16(o[1][0], o[1][1]));
                sts32(oa + 384, pack_bf16(o[1][2], o[1][3]));
            }
            fence_async_smem();
            bar_sync(1, 128);
            if (lane == 0) mbar_arrive(bars + 8 * B_SRDY);
            if (s == 0) GT(2);
            if (s == 63) { GT(3); break; }
            const uint32_t t0 = clk();
            TS(5);
            unsigned char* const rb = redp + (s & 3) * 65536;
            float i0, i1;
#pragma unroll 1
            for (int hf = 0; hf < 2; hf++) {
                float ca[4], cb[4];
                wg_fence();
                const uint64_t da0 = mkdesc(SM_BASE + O_WO, 16, 1024, 1) + hf * 2048;
#pragma unroll
                for (int ks = 0; ks < 8; ks++) {
                    constexpr uint64_t db0 = mkdesc(SM_BASE + O_O, 128, 128, 0);
                    if (ks == 0) { wg_ss8<0>(ca, da0, db0); wg_ss8<0>(cb, da0 + 1024, db0); }
                    else { wg_ss8<1>(ca, da0 + ks * 128, db0 + ks * 16); wg_ss8<1>(cb, da0 + 1024 + ks * 128, db0 + ks * 16); }
                }
                wg_commit();
                if (hf == 0) {
                    sum += __shfl_xor_sync(~0u, sum, 1);
                    sum += __shfl_xor_sync(~0u, sum, 2);
                    const float inv = rcp(sum);
                    i0 = __shfl_sync(~0u, inv, (lane & 3) * 8); i1 = __shfl_sync(~0u, inv, (lane & 3) * 8 + 4);
                } else if (lane == 0) mbar_arrive(bars + 8 * B_OPDONE);
                unsigned char* const pg = rb + red_grp(j * 16 + (tid >> 3));
                unsigned char* const pa = pg + (lane & 7) * 16 + hf * 512 + (h & 1) * 128;
                unsigned char* const pb = pg + (lane & 7) * 4 + 32768 + hf * 64 + (h & 1) * 32;
                wg_wait<0>();
                asm volatile("red.relaxed.gpu.global.add.noftz.v4.bf16x2 [%0], {%1,%2,%3,%4};" ::"l"(pa), "r"(pack_bf16(ca[0] * i0, ca[1] * i1)),
                             "r"(pack_bf16(ca[2] * i0, ca[3] * i1)), "r"(pack_bf16(cb[0] * i0, cb[1] * i1)), "r"(pack_bf16(cb[2] * i0, 1.f)) : "memory");
                asm volatile("red.relaxed.gpu.global.add.noftz.bf16x2 [%0], %1;" ::"l"(pb), "r"(pack_bf16(cb[3] * i1, 1.f)) : "memory");
                TSV(6 + hf, clk());
            }
            {
                const unsigned char* pg = rb + red_grp((kh * 2 + (w & 1)) * 16 + (lane >> 3));
                uint32_t u[16];
                uint32_t n = 0;
                const uint32_t target = (s & 4) ? 0x42A00000u : 0x41800000u;
                const unsigned char* pa = pg + (lane & 7) * 16 + (w >> 1) * 512;
                const unsigned char* pb = pg + (lane & 7) * 4 + 32768 + (w >> 1) * 64;
                wait_clk(t0, d_r);
                TSV(8 + (w >> 1), clk());
                uint4 ra[4], rc[4]; uint32_t re[4], rf[4];
                while (true) {
                    uint32_t x = 0;
#pragma unroll
                    for (int q = 0; q < 4; q++) {
                        ra[q] = ldg_rlx128(pa + q * 2048); rc[q] = ldg_rlx128(pa + q * 2048 + 128);
                        re[q] = ldg_rlx32(pb + q * 2048); rf[q] = ldg_rlx32(pb + q * 2048 + 32);
                    }
#pragma unroll
                    for (int q = 0; q < 4; q++) x |= (ra[q].w ^ target) | (rc[q].w ^ target) | (re[q] ^ target) | (rf[q] ^ target);
                    if (!__any_sync(~0u, x >> 16)) break;
                    if (++n > SPIN_LIMIT) __trap();
                }
#pragma unroll
                for (int q = 0; q < 4; q++) {
                    u[2 * q] = add_bf16x2(ra[q].x, rc[q].x);
                    u[2 * q + 1] = add_bf16x2(ra[q].y, rc[q].y);
                    u[8 + 2 * q] = add_bf16x2(ra[q].z, rc[q].z);
                    u[8 + 2 * q + 1] = add_bf16x2(__byte_perm(ra[q].w, re[q], 0x5410), __byte_perm(rc[q].w, rf[q], 0x5410));
                }
                TSV(10 + (w >> 1), clk());
                const uint32_t ma = sb + O_MEM + ((w & 1) * 4 + (w >> 1) * 2) * 1024 + (lane & 7) * 128 + (((lane >> 3) ^ (lane & 7)) << 4);
                stsm4t(ma, u[0], u[1], u[2], u[3]);
                stsm4t(ma ^ 64, u[4], u[5], u[6], u[7]);
                stsm4t(ma + 1024, u[8], u[9], u[10], u[11]);
                stsm4t((ma ^ 64) + 1024, u[12], u[13], u[14], u[15]);
                fence_async_smem();
                __syncwarp();
                if (lane == 0) mbar_arrive(bars + 8 * (B_MEM0 + w));
                TSV(12 + (w >> 1), clk()); TSV(16 + w, n);
            }
        }
        TSDUMP();
    }
}

constexpr int G_ST = 6;
constexpr uint32_t G_SMEM = G_ST * 32768 + 256;
#define F16(d, o) F4(d, o), F4(d, o + 4), F4(d, o + 8), F4(d, o + 12)
__device__ __forceinline__ void wg_ss128(float (&d)[64], uint64_t da, uint64_t db, int sc) {
    asm volatile("{\n.reg .pred p;\nsetp.ne.b32 p, %66, 0;\nwgmma.mma_async.sync.aligned.m64n128k16.f32.bf16.bf16 "
                 "{%0,%1,%2,%3,%4,%5,%6,%7,%8,%9,%10,%11,%12,%13,%14,%15,%16,%17,%18,%19,%20,%21,%22,%23,%24,%25,%26,%27,%28,%29,%30,%31,"
                 "%32,%33,%34,%35,%36,%37,%38,%39,%40,%41,%42,%43,%44,%45,%46,%47,%48,%49,%50,%51,%52,%53,%54,%55,%56,%57,%58,%59,%60,%61,%62,%63}, "
                 "%64, %65, p, 1, 1, 0, 1;\n}"
                 : F16(d, 0), F16(d, 16), F16(d, 32), F16(d, 48) : "l"(da), "l"(db), "r"(sc));
}

__global__ void __launch_bounds__(384, 1)
out_gemm(const __grid_constant__ CUtensorMap tm_o, const __grid_constant__ CUtensorMap tm_w, bf16* __restrict__ out) {
    extern __shared__ __align__(1024) unsigned char smem_raw[];
    const uint32_t sb = smem_u32(smem_raw), bars = sb + G_ST * 32768;
    const int m0 = (blockIdx.x >> 3) * 128, n0 = (blockIdx.x & 7) * 128;
    const int wgi = __shfl_sync(~0u, threadIdx.x >> 7, 0), tid = threadIdx.x & 127;
    if (threadIdx.x == 0) {
        for (int i = 0; i < G_ST; i++) { mbar_init(bars + 8 * i, 1); mbar_init(bars + 8 * (G_ST + i), 8); }
        fence_async_smem();
    }
    __syncthreads();
    if (wgi == 0) GT(4);
    if (wgi == 2) {
        if (tid == 0) {
            for (int kt = 0; kt < 64; kt++) {
                const int st = kt % G_ST;
                if (kt >= G_ST) mbar_wait(bars + 8 * (G_ST + st), (kt / G_ST - 1) & 1);
                mbar_expect_tx(bars + 8 * st, 32768);
                tma2d(sb + st * 32768, &tm_o, kt * 64, m0, bars + 8 * st);
                tma2d(sb + st * 32768 + 16384, &tm_w, n0, kt * 64, bars + 8 * st);
                tma2d(sb + st * 32768 + 24576, &tm_w, n0 + 64, kt * 64, bars + 8 * st);
            }
        }
    } else {
        float d[64];
        int st = 0, ph = 0;
#pragma unroll 1
        for (int kt = 0; kt < 64; kt++) {
            mbar_wait(bars + 8 * st, ph);
            const uint64_t da = mkdesc(sb + st * 32768 + wgi * 8192, 16, 1024, 1), db = mkdesc(sb + st * 32768 + 16384, 8192, 1024, 1);
            wg_fence();
#pragma unroll
            for (int k = 0; k < 4; k++) wg_ss128(d, da + k * 2, db + k * 128, kt | k);
            wg_commit();
            if (kt > 0) {
                wg_wait<1>();
                if ((tid & 31) == 0) mbar_arrive(bars + 8 * (G_ST + (st == 0 ? G_ST - 1 : st - 1)));
            }
            if (++st == G_ST) { st = 0; ph ^= 1; }
        }
        wg_wait<0>();
        const int row = m0 + wgi * 64 + (tid >> 5) * 16 + ((tid & 31) >> 2);
        bf16* op = out + (size_t)row * 2048 + 1024 + n0 + (tid & 3) * 2;
#pragma unroll
        for (int i = 0; i < 16; i++) {
            *(uint32_t*)(op + i * 8) = pack_bf16(d[4 * i], d[4 * i + 1]);
            *(uint32_t*)(op + 8 * 2048 + i * 8) = pack_bf16(d[4 * i + 2], d[4 * i + 3]);
        }
        if (wgi == 0) GT(5);
    }
}

typedef CUresult (*EncodeFn)(CUtensorMap*, CUtensorMapDataType, cuuint32_t, void*, const cuuint64_t*, const cuuint64_t*,
                             const cuuint32_t*, const cuuint32_t*, CUtensorMapInterleave, CUtensorMapSwizzle,
                             CUtensorMapL2promotion, CUtensorMapFloatOOBfill);

static void make_map(EncodeFn fn, CUtensorMap* m, const void* p, uint64_t cols, uint64_t rows, uint32_t bc, uint32_t br) {
    cuuint64_t dims[2] = {cols, rows}, strides[1] = {cols * 2};
    cuuint32_t box[2] = {bc, br}, es[2] = {1, 1};
    fn(m, CU_TENSOR_MAP_DATA_TYPE_BFLOAT16, 2, (void*)p, dims, strides, box, es, CU_TENSOR_MAP_INTERLEAVE_NONE,
       CU_TENSOR_MAP_SWIZZLE_128B, CU_TENSOR_MAP_L2_PROMOTION_L2_128B, CU_TENSOR_MAP_FLOAT_OOB_FILL_NONE);
}

static Tune h_tune = {250, 750, 1100, 0};

extern "C" void kernel_launch(void* const* d_in, const int* in_sizes, int n_in, void* d_out, int out_size) {
    static bool init = false;
    static CUtensorMap tm_x, tm_wq, tm_wk, tm_wv, tm_wo, tm_o, tm_wo2;
    if (!init) {
        void* fp = nullptr; cudaDriverEntryPointQueryResult qr;
        cudaGetDriverEntryPoint("cuTensorMapEncodeTiled", &fp, cudaEnableDefault, &qr);
        EncodeFn fn = (EncodeFn)fp;
        void* ox = nullptr; cudaGetSymbolAddress(&ox, g_ox);
        {
            cuuint64_t dims[4] = {64, 8, 16, 256}, strides[3] = {2048, 128, 16384};
            cuuint32_t box[4] = {64, 8, 8, 4}, es[4] = {1, 1, 1, 1};
            fn(&tm_x, CU_TENSOR_MAP_DATA_TYPE_BFLOAT16, 4, d_in[3], dims, strides, box, es, CU_TENSOR_MAP_INTERLEAVE_NONE,
               CU_TENSOR_MAP_SWIZZLE_128B, CU_TENSOR_MAP_L2_PROMOTION_L2_128B, CU_TENSOR_MAP_FLOAT_OOB_FILL_NONE);
        }
        make_map(fn, &tm_wq, d_in[5], 4096, 1024, 64, 256);
        make_map(fn, &tm_wk, d_in[6], 4096, 1024, 64, 256);
        make_map(fn, &tm_wv, d_in[7], 4096, 1024, 64, 256);
        make_map(fn, &tm_wo, d_in[8], 1024, 4096, 64, 128);
        make_map(fn, &tm_o, ox, 4096, 2048, 64, 128);
        make_map(fn, &tm_wo2, d_in[8], 1024, 4096, 64, 64);
        cudaFuncSetAttribute(rmt_main, cudaFuncAttributeMaxDynamicSharedMemorySize, MAIN_SMEM);
        cudaFuncSetAttribute(out_gemm, cudaFuncAttributeMaxDynamicSharedMemorySize, G_SMEM);
        init = true;
    }
    rmt_main<<<132, 512, MAIN_SMEM>>>(tm_x, tm_wq, tm_wk, tm_wv, tm_wo, (const bf16*)d_in[4], h_tune);
    out_gemm<<<128, 384, G_SMEM>>>(tm_o, tm_wo2, (bf16*)d_out);
}
```

```cpp
#include <cuda_runtime.h>
#include <cuda_bf16.h>
#include <cuda.h>
#include <stdint.h>

typedef __nv_bfloat16 bf16;

#define DBG_TIMING 0

#define SPIN_LIMIT (1u << 22)

__device__ __forceinline__ uint32_t smem_u32(const void* p) { return (uint32_t)__cvta_generic_to_shared(p); }
__device__ __forceinline__ uint32_t clk() { uint32_t c; asm volatile("mov.u32 %0, %%clock;" : "=r"(c)::"memory"); return c; }
__device__ __forceinline__ uint32_t gtime() { uint32_t c; asm volatile("mov.u32 %0, %%globaltimer_lo;" : "=r"(c)::"memory"); return c; }
__device__ __forceinline__ void wait_clk(uint32_t t0, uint32_t d) { while (clk() - t0 < d) {} }

__device__ __forceinline__ void mbar_init(uint32_t bar, uint32_t cnt) {
    asm volatile("mbarrier.init.shared::cta.b64 [%0], %1;" ::"r"(bar), "r"(cnt) : "memory");
}
__device__ __forceinline__ void mbar_arrive(uint32_t bar) {
    asm volatile("mbarrier.arrive.shared::cta.b64 _, [%0];" ::"r"(bar) : "memory");
}
__device__ __forceinline__ void mbar_expect_tx(uint32_t bar, uint32_t bytes) {
    asm volatile("mbarrier.arrive.expect_tx.shared::cta.b64 _, [%0], %1;" ::"r"(bar), "r"(bytes) : "memory");
}
__device__ __forceinline__ void mbar_wait(uint32_t bar, uint32_t parity) {
    asm volatile(
        "{\n.reg .pred p, q;\n.reg .u32 n;\nmov.u32 n, 0;\n"
        "WL:\nmbarrier.try_wait.parity.shared::cta.b64 p, [%0], %1;\n"
        "add.u32 n, n, 1;\nsetp.gt.u32 q, n, %2;\n@q trap;\n@!p bra WL;\n}" ::"r"(bar), "r"(parity), "n"(SPIN_LIMIT) : "memory");
}
__device__ __forceinline__ void mbar_wait_cluster(uint32_t bar, uint32_t parity) {
    asm volatile(
        "{\n.reg .pred p, q;\n.reg .u32 n;\nmov.u32 n, 0;\n"
        "WL:\nmbarrier.try_wait.parity.acquire.cluster.shared::cta.b64 p, [%0], %1;\n"
        "add.u32 n, n, 1;\nsetp.gt.u32 q, n, %2;\n@q trap;\n@!p bra WL;\n}" ::"r"(bar), "r"(parity), "n"(SPIN_LIMIT) : "memory");
}
__device__ __forceinline__ void tma2d(uint32_t dst, const CUtensorMap* m, int c0, int c1, uint32_t bar) {
    asm volatile("cp.async.bulk.tensor.2d.shared::cluster.global.mbarrier::complete_tx::bytes [%0], [%1, {%3, %4}], [%2];"
                 ::"r"(dst), "l"(m), "r"(bar), "r"(c0), "r"(c1) : "memory");
}
__device__ __forceinline__ void tma4d(uint32_t dst, const CUtensorMap* m, int c2, int c3, uint32_t bar) {
    asm volatile("cp.async.bulk.tensor.4d.shared::cluster.global.mbarrier::complete_tx::bytes [%0], [%1, {%5, %5, %3, %4}], [%2];"
                 ::"r"(dst), "l"(m), "r"(bar), "r"(c2), "r"(c3), "r"(0) : "memory");
}
__device__ __forceinline__ void tma4d_prefetch(const CUtensorMap* m, int c2, int c3) {
    asm volatile("cp.async.bulk.prefetch.tensor.4d.L2.global [%0, {%3, %3, %1, %2}];" ::"l"(m), "r"(c2), "r"(c3), "r"(0) : "memory");
}
__device__ __forceinline__ void tma2d_prefetch(const CUtensorMap* m, int c0, int c1) {
    asm volatile("cp.async.bulk.prefetch.tensor.2d.L2.global [%0, {%1, %2}];" ::"l"(m), "r"(c0), "r"(c1) : "memory");
}
__device__ __forceinline__ void fence_async_smem() { asm volatile("fence.proxy.async.shared::cta;" ::: "memory"); }
__device__ __forceinline__ void fence_gpu() { asm volatile("fence.acq_rel.gpu;" ::: "memory"); }
__device__ __forceinline__ float rcp(float x) { float r; asm("rcp.approx.ftz.f32 %0, %1;" : "=f"(r) : "f"(x)); return r; }
__device__ __forceinline__ void bar_sync(int id, int n) { asm volatile("bar.sync %0, %1;" ::"r"(id), "r"(n) : "memory"); }

__device__ __forceinline__ uint32_t pack_bf16(float lo, float hi) {
    uint32_t r; asm("cvt.rn.bf16x2.f32 %0, %1, %2;" : "=r"(r) : "f"(hi), "f"(lo)); return r;
}
__device__ __forceinline__ uint32_t add_bf16x2(uint32_t a, uint32_t b) {
    uint32_t r; asm("add.rn.bf16x2 %0, %1, %2;" : "=r"(r) : "r"(a), "r"(b)); return r;
}
__device__ __forceinline__ uint32_t movm(uint32_t a) {
    uint32_t r; asm volatile("movmatrix.sync.aligned.m8n8.trans.b16 %0, %1;" : "=r"(r) : "r"(a)); return r;
}
__device__ __forceinline__ uint32_t orx(uint32_t acc, uint32_t a, uint32_t t) {
    uint32_t r; asm("lop3.b32 %0, %1, %2, %3, 0xF6;" : "=r"(r) : "r"(acc), "r"(a), "r"(t)); return r;
}
__device__ __forceinline__ uint32_t orx2(uint32_t a, uint32_t b, uint32_t t) {
    uint32_t r; asm("lop3.b32 %0, %1, %2, %3, 0x7E;" : "=r"(r) : "r"(a), "r"(b), "r"(t)); return r;
}
__device__ __forceinline__ float ex2(float x) { float r; asm("ex2.approx.ftz.f32 %0, %1;" : "=f"(r) : "f"(x)); return r; }
__device__ __forceinline__ void ldsm4t(uint32_t (&r)[4], uint32_t a) {
    asm volatile("ldmatrix.sync.aligned.m8n8.x4.trans.shared.b16 {%0,%1,%2,%3}, [%4];"
                 : "=r"(r[0]), "=r"(r[1]), "=r"(r[2]), "=r"(r[3]) : "r"(a) : "memory");
}
__device__ __forceinline__ void ldsm4(uint32_t (&r)[4], uint32_t a) {
    asm volatile("ldmatrix.sync.aligned.m8n8.x4.shared.b16 {%0,%1,%2,%3}, [%4];"
                 : "=r"(r[0]), "=r"(r[1]), "=r"(r[2]), "=r"(r[3]) : "r"(a) : "memory");
}
__device__ __forceinline__ void stsm4t(uint32_t a, uint32_t r0, uint32_t r1, uint32_t r2, uint32_t r3) {
    asm volatile("stmatrix.sync.aligned.m8n8.x4.trans.shared.b16 [%0], {%1,%2,%3,%4};"
                 ::"r"(a), "r"(r0), "r"(r1), "r"(r2), "r"(r3) : "memory");
}
__device__ __forceinline__ void stsm4(uint32_t a, uint32_t r0, uint32_t r1, uint32_t r2, uint32_t r3) {
    asm volatile("stmatrix.sync.aligned.m8n8.x4.shared.b16 [%0], {%1,%2,%3,%4};"
                 ::"r"(a), "r"(r0), "r"(r1), "r"(r2), "r"(r3) : "memory");
}
__device__ __forceinline__ void mma16816(float* c, uint32_t a0, uint32_t a1, uint32_t a2, uint32_t a3, uint32_t b0, uint32_t b1) {
    asm volatile("mma.sync.aligned.m16n8k16.row.col.f32.bf16.bf16.f32 {%0,%1,%2,%3}, {%4,%5,%6,%7}, {%8,%9}, {%0,%1,%2,%3};"
                 : "+f"(c[0]), "+f"(c[1]), "+f"(c[2]), "+f"(c[3]) : "r"(a0), "r"(a1), "r"(a2), "r"(a3), "r"(b0), "r"(b1));
}
__device__ __forceinline__ void mma1688(float* c, uint32_t a0, uint32_t a1, uint32_t b0) {
    asm volatile("mma.sync.aligned.m16n8k8.row.col.f32.bf16.bf16.f32 {%0,%1,%2,%3}, {%4,%5}, {%6}, {%0,%1,%2,%3};"
                 : "+f"(c[0]), "+f"(c[1]), "+f"(c[2]), "+f"(c[3]) : "r"(a0), "r"(a1), "r"(b0));
}
__device__ __forceinline__ void sts128(uint32_t a, float x, float y, float z, float w) {
    asm volatile("st.shared.v4.f32 [%0], {%1,%2,%3,%4};" ::"r"(a), "f"(x), "f"(y), "f"(z), "f"(w) : "memory");
}
__device__ __forceinline__ void sts64(uint32_t a, float x, float y) {
    asm volatile("st.shared.v2.f32 [%0], {%1,%2};" ::"r"(a), "f"(x), "f"(y) : "memory");
}
__device__ __forceinline__ void sts32(uint32_t a, uint32_t x) { asm volatile("st.shared.b32 [%0], %1;" ::"r"(a), "r"(x) : "memory"); }
__device__ __forceinline__ void sts128u(uint32_t a, uint4 v) {
    asm volatile("st.shared.v4.b32 [%0], {%1,%2,%3,%4};" ::"r"(a), "r"(v.x), "r"(v.y), "r"(v.z), "r"(v.w) : "memory");
}
__device__ __forceinline__ float4 lds128(uint32_t a) {
    float4 v; asm volatile("ld.shared.v4.f32 {%0,%1,%2,%3}, [%4];" : "=f"(v.x), "=f"(v.y), "=f"(v.z), "=f"(v.w) : "r"(a) : "memory"); return v;
}
__device__ __forceinline__ uint4 lds128u(uint32_t a) {
    uint4 v; asm volatile("ld.shared.v4.b32 {%0,%1,%2,%3}, [%4];" : "=r"(v.x), "=r"(v.y), "=r"(v.z), "=r"(v.w) : "r"(a) : "memory"); return v;
}
__device__ __forceinline__ float2 lds64(uint32_t a) {
    float2 v; asm volatile("ld.shared.v2.f32 {%0,%1}, [%2];" : "=f"(v.x), "=f"(v.y) : "r"(a) : "memory"); return v;
}
__device__ __forceinline__ uint2 ldg_rlx64(const void* p) {
    uint64_t v; asm volatile("ld.relaxed.gpu.global.b64 %0, [%1];" : "=l"(v) : "l"(p) : "memory");
    return make_uint2((uint32_t)v, (uint32_t)(v >> 32));
}
__device__ __forceinline__ uint4 ldg_rlx128(const void* p) {
    uint64_t a, b;
    asm volatile("{\n.reg .b128 t;\nld.relaxed.gpu.global.b128 t, [%2];\nmov.b128 {%0,%1}, t;\n}" : "=l"(a), "=l"(b) : "l"(p) : "memory");
    return make_uint4((uint32_t)a, (uint32_t)(a >> 32), (uint32_t)b, (uint32_t)(b >> 32));
}
__device__ __forceinline__ void stg_rlx64(void* p, uint32_t x, uint32_t y) {
    asm volatile("{\n.reg .b64 t;\nmov.b64 t, {%1,%2};\nst.relaxed.gpu.global.b64 [%0], t;\n}" ::"l"(p), "r"(x), "r"(y) : "memory");
}
__device__ __forceinline__ void stg_rlx128(void* p, uint32_t x, uint32_t y, uint32_t z, uint32_t w) {
    asm volatile("{\n.reg .b64 a, b;\n.reg .b128 t;\nmov.b64 a, {%1,%2};\nmov.b64 b, {%3,%4};\nmov.b128 t, {a,b};\nst.relaxed.gpu.global.b128 [%0], t;\n}"
                 ::"l"(p), "r"(x), "r"(y), "r"(z), "r"(w) : "memory");
}
__device__ __forceinline__ uint32_t ldg_rlx32(const void* p) {
    uint32_t v; asm volatile("ld.relaxed.gpu.global.b32 %0, [%1];" : "=r"(v) : "l"(p) : "memory"); return v;
}
__device__ __forceinline__ void stg128(void* p, uint32_t x, uint32_t y, uint32_t z, uint32_t w) {
    asm volatile("st.global.v4.b32 [%0], {%1,%2,%3,%4};" ::"l"(p), "r"(x), "r"(y), "r"(z), "r"(w) : "memory");
}
__device__ __forceinline__ uint32_t ld_acquire(const unsigned* p) {
    uint32_t v; asm volatile("ld.acquire.gpu.global.u32 %0, [%1];" : "=r"(v) : "l"(p) : "memory"); return v;
}
__device__ __forceinline__ void red_add_u32(unsigned* p, uint32_t v) {
    asm volatile("red.relaxed.gpu.global.add.u32 [%0], %1;" ::"l"(p), "r"(v) : "memory");
}
__device__ __forceinline__ void wait_counter(const unsigned* p, uint32_t target) {
    uint32_t n = 0;
    while (ld_acquire(p) < target) { if (++n > SPIN_LIMIT) __trap(); }
}

__device__ __forceinline__ void wg_fence() { asm volatile("wgmma.fence.sync.aligned;" ::: "memory"); }
__device__ __forceinline__ void wg_commit() { asm volatile("wgmma.commit_group.sync.aligned;" ::: "memory"); }
template <int N> __device__ __forceinline__ void wg_wait() { asm volatile("wgmma.wait_group.sync.aligned %0;" ::"n"(N) : "memory"); }
__host__ __device__ constexpr uint64_t mkdesc(uint32_t addr, uint32_t lbo, uint32_t sbo, uint32_t swz) {
    return (uint64_t)((addr & 0x3FFFF) >> 4) | ((uint64_t)(lbo >> 4) << 16) | ((uint64_t)(sbo >> 4) << 32) | ((uint64_t)swz << 62);
}
#define F4(d, o) "+f"(d[o]), "+f"(d[o + 1]), "+f"(d[o + 2]), "+f"(d[o + 3])
template <int SC> __device__ __forceinline__ void wg_rs32(float (&d)[16], const uint32_t (&a)[4], uint64_t db) {
    asm volatile("wgmma.mma_async.sync.aligned.m64n32k16.f32.bf16.bf16 "
                 "{%0,%1,%2,%3,%4,%5,%6,%7,%8,%9,%10,%11,%12,%13,%14,%15}, {%16,%17,%18,%19}, %20, %21, 1, 1, 0;"
                 : F4(d, 0), F4(d, 4), F4(d, 8), F4(d, 12)
                 : "r"(a[0]), "r"(a[1]), "r"(a[2]), "r"(a[3]), "l"(db), "n"(SC));
}
template <int SC> __device__ __forceinline__ void wg_rs40(float (&d)[20], const uint32_t (&a)[4], uint64_t db) {
    asm volatile("wgmma.mma_async.sync.aligned.m64n40k16.f32.bf16.bf16 "
                 "{%0,%1,%2,%3,%4,%5,%6,%7,%8,%9,%10,%11,%12,%13,%14,%15,%16,%17,%18,%19}, {%20,%21,%22,%23}, %24, %25, 1, 1, 0;"
                 : F4(d, 0), F4(d, 4), F4(d, 8), F4(d, 12), F4(d, 16)
                 : "r"(a[0]), "r"(a[1]), "r"(a[2]), "r"(a[3]), "l"(db), "n"(SC));
}
template <int SC> __device__ __forceinline__ void wg_ss40(float (&d)[20], uint64_t da, uint64_t db) {
    asm volatile("wgmma.mma_async.sync.aligned.m64n40k16.f32.bf16.bf16 "
                 "{%0,%1,%2,%3,%4,%5,%6,%7,%8,%9,%10,%11,%12,%13,%14,%15,%16,%17,%18,%19}, %20, %21, %22, 1, 1, 1, 0;"
                 : F4(d, 0), F4(d, 4), F4(d, 8), F4(d, 12), F4(d, 16)
                 : "l"(da), "l"(db), "n"(SC));
}
template <int SC> __device__ __forceinline__ void wg_ss8(float (&d)[4], uint64_t da, uint64_t db) {
    asm volatile("wgmma.mma_async.sync.aligned.m64n8k16.f32.bf16.bf16 {%0,%1,%2,%3}, %4, %5, %6, 1, 1, 1, 1;"
                 : F4(d, 0) : "l"(da), "l"(db), "n"(SC));
}

__device__ uint4 g_kvq[4 * 32 * 3 * 8 * 2 * 32];
__device__ uint2 g_alpha[2 * 32 * 3 * 8 * 2 * 32];
__device__ uint4 g_red[(4 * 65536 + 32768) / 16];
__device__ uint4 g_stamp[32];
__device__ unsigned g_start;
__device__ bf16 g_ox[2048 * 4096];
#define TSI(st) do {} while (0)
#define TS(k) do {} while (0)
#define TSV(k, v) do {} while (0)
#define TSDUMP() do {} while (0)
#define GT(k) do {} while (0)
#define FLAG(b) false

struct Tune { uint32_t d_alpha, d_r0, d_r1, flags, d_st; };
#define RED_F32 0
#define Q_SEP 0
#define SEND_BAR B_OPDONE
#define XA_BAR B_OPDONE
#define AV_POS 1

constexpr uint32_t SM_BASE = 1024;
constexpr uint32_t O_WO = 0;
constexpr uint32_t O_WV = 65536;
constexpr uint32_t O_XB = 131072;
constexpr uint32_t O_MEM = O_XB + 32768;
constexpr uint32_t O_RECV = O_MEM + 8192;
constexpr uint32_t O_S = O_RECV + 24576 + 1024;
constexpr uint32_t O_O = O_S + 10240;
constexpr uint32_t O_XO = O_O + 2048;
constexpr uint32_t O_BAR = O_XO + 2048;
constexpr uint32_t O_DBG = O_BAR + 256;
constexpr uint32_t MAIN_SMEM = O_DBG + (DBG_TIMING ? 4 * 32 * 24 * 4 : 0);
enum { B_WQ0 = 0, B_WQ1, B_WK0, B_WK1, B_WV, B_WO, B_QDONE, B_KDONE, B_XFULL, B_XEMPTY, B_MEM0, B_MEM1, B_QH0, B_QH1,
       B_RECV, B_QKW = B_RECV + 6, B_SDONE, B_SRDY, B_SFREE, B_OPDONE, B_STAMP, B_COUNT };

constexpr float SM_SCALE_LOG2 = 0.08838834764831845f * 1.4426950408889634f;
constexpr float MASK_VAL = -1.0e9f / 0.08838834764831845f;

__host__ __device__ constexpr uint32_t red_slot(int i) { return (uint32_t)((i >> 2) * 32768 + (i & 1) * 128 + ((i >> 1) & 1) * 512); }
__device__ __forceinline__ uint32_t red_grp(int grp) { return (uint32_t)((grp >> 1) * 1024 + (grp & 1) * 256); }
__host__ __device__ constexpr int ks_order(int i) { return (((i >> 3) & 1) * 4 + (i >> 4) * 2 + ((i >> 2) & 1)) * 4 + (i & 3); }
__host__ __device__ constexpr uint64_t xdesc(int ks) { return mkdesc(SM_BASE + O_XB + (ks >> 2) * 1024 + (ks & 3) * 32, 16, 8192, 1); }

__device__ __forceinline__ void x_split(const float* d, uint32_t (&sn)[4], float (&k)[8], int kh) {
#pragma unroll
    for (int i = 0; i < 4; i++) {
        sn[i] = pack_bf16(kh ? d[2 * i] : d[8 + 2 * i], kh ? d[2 * i + 1] : d[8 + 2 * i + 1]);
        k[2 * i] = kh ? d[8 + 2 * i] : d[2 * i]; k[2 * i + 1] = kh ? d[8 + 2 * i + 1] : d[2 * i + 1];
    }
}
template <int R>
__device__ __forceinline__ void x_send(const uint32_t (&sn)[4], int sg, int tid, uint32_t sb, uint32_t mate) {
    const uint32_t par = sg & 1;
    const uint32_t bar = O_BAR + 8 * (B_RECV + R * 2) + 8 * par;
    if (tid == 0) mbar_expect_tx(sb + bar, 2048);
    asm volatile("st.async.shared::cluster.mbarrier::complete_tx::bytes.v4.b32 [%0], {%1,%2,%3,%4}, [%5];"
                 ::"r"(mate + O_RECV + (par * 3 + R) * 2048 + tid * 16), "r"(sn[0]), "r"(sn[1]), "r"(sn[2]), "r"(sn[3]), "r"(mate + bar) : "memory");
}
__device__ __forceinline__ uint32_t add_pack(float a, float b, uint32_t r) {
    return pack_bf16(a + __uint_as_float(r << 16), b + __uint_as_float(r & 0xffff0000u));
}
template <int R>
__device__ __forceinline__ void x_finish(const float (&k)[8], int sg, uint32_t frag, int tid, uint32_t sb) {
    const uint32_t par = sg & 1;
    mbar_wait_cluster(sb + O_BAR + 8 * (B_RECV + R * 2) + 8 * par, (sg >> 1) & 1);
    const uint4 r = lds128u(sb + O_RECV + (par * 3 + R) * 2048 + tid * 16);
    uint32_t u0 = add_pack(k[0], k[1], r.x), u1 = add_pack(k[2], k[3], r.y), u2 = add_pack(k[4], k[5], r.z), u3 = add_pack(k[6], k[7], r.w);
    if (R < 2) { u0 = movm(u0); u1 = movm(u1); u2 = movm(u2); u3 = movm(u3); }
    const uint32_t tag = ((sg >> 2) & 1) ^ 1;
    u0 = (u0 & ~1u) | tag;
    if (R == 0) u2 = (u2 & ~1u) | tag;
    stg_rlx128(&g_kvq[(sg & 3) * (32 * 3 * 512) + R * 512 + frag], u0, u1, u2, u3);
}
template <int R>
__device__ __forceinline__ void alpha_write(float d0, float d1, float d2, float d3, int s, uint32_t frag) {
    uint32_t u0 = pack_bf16(d0, d1), u1 = pack_bf16(d2, d3);
    if (R < 2) { u0 = movm(u0); u1 = movm(u1); }
    u0 = (u0 & ~1u) | (((s >> 1) & 1) ^ 1);
    stg_rlx64(&g_alpha[(s & 1) * (32 * 3 * 512) + R * 512 + frag], u0, u1);
}

__device__ __forceinline__ void softmax10(float (&sc)[10], uint32_t (&pf)[5], float& sum) {
    float m = fmaxf(fmaxf(fmaxf(sc[0], sc[1]), fmaxf(sc[2], sc[3])), fmaxf(fmaxf(sc[4], sc[5]), fmaxf(sc[6], sc[7])));
    m = fmaxf(m, fmaxf(sc[8], sc[9]));
    m = fmaxf(m, __shfl_xor_sync(~0u, m, 1));
    m = fmaxf(m, __shfl_xor_sync(~0u, m, 2));
    const float mb = -m * SM_SCALE_LOG2;
#pragma unroll
    for (int i = 0; i < 10; i++) sc[i] = ex2(fmaf(sc[i], SM_SCALE_LOG2, mb));
#pragma unroll
    for (int n = 0; n < 5; n++) pf[n] = pack_bf16(sc[2 * n], sc[2 * n + 1]);
    sum = ((sc[0] + sc[1]) + (sc[2] + sc[3])) + ((sc[4] + sc[5]) + (sc[6] + sc[7])) + (sc[8] + sc[9]);
}

__global__ void __cluster_dims__(2, 1, 1) __launch_bounds__(512, 1)
rmt_main(const __grid_constant__ CUtensorMap tm_x, const __grid_constant__ CUtensorMap tm_wq, const __grid_constant__ CUtensorMap tm_wk,
         const __grid_constant__ CUtensorMap tm_wv, const __grid_constant__ CUtensorMap tm_wo, const bf16* __restrict__ mem0, const Tune tn) {
    extern __shared__ __align__(1024) unsigned char smem_raw[];
    const uint32_t sb = smem_u32(smem_raw);
    if ((sb & 0x3FFFF) != SM_BASE) __trap();
    const int cid = blockIdx.x >> 1, kh = blockIdx.x & 1;
    const int tpc = cid < 4 ? 62 + cid : cid - 4;
    int h, nh;
    if (tpc < 32) { h = (tpc >> 4) * 8 + (tpc & 7); nh = (tpc >> 3) & 1; }
    else if (tpc < 60) { int u = tpc - 32, r = u % 14; h = 16 + (u / 14) * 7 + r % 7; nh = r / 7; }
    else if (tpc < 62) return;
    else { h = 30 + ((tpc - 62) >> 1); nh = tpc & 1; }
    const int j = nh * 2 + kh, role = h * 4 + j;
    const int wgi = __shfl_sync(~0u, threadIdx.x >> 7, 0);
    const int tid = threadIdx.x & 127, w = tid >> 5, lane = tid & 31;
#define OPAQUE_IDS() int tid_ = tid; asm volatile("" : "+r"(tid_)); const int tid = tid_, w = tid_ >> 5, lane = tid_ & 31; (void)w; (void)lane
    unsigned char* const redp = (unsigned char*)(((uintptr_t)g_red + 32767) & ~(uintptr_t)32767);
    const uint32_t bars = sb + O_BAR;

    if (threadIdx.x == 0) {
        const uint8_t cnts[B_COUNT] = {1, 1, 1, 1, 1, 1, 4, 4, 1, 12, 2, 2, 4, 4, 1, 1, 1, 1, 1, 1, 8, 4, 4, 4, 4, 1};
#pragma unroll
        for (int i = 0; i < B_COUNT; i++) mbar_init(bars + 8 * i, cnts[i]);
        asm volatile("fence.mbarrier_init.release.cluster;" ::: "memory");
        fence_async_smem();
        const int c0 = h * 128 + nh * 64, r0 = kh * 512;
        for (int i = 0; i < 2; i++) {
            mbar_expect_tx(bars + 8 * (B_WK0 + i), 32768);
            tma2d(sb + O_XB + i * 32768, &tm_wk, c0, r0 + i * 256, bars + 8 * (B_WK0 + i));
            mbar_expect_tx(bars + 8 * (B_WQ0 + i), 32768);
            tma2d(sb + O_WO + i * 32768, &tm_wq, c0, r0 + i * 256, bars + 8 * (B_WQ0 + i));
        }
        mbar_expect_tx(bars + 8 * B_WV, 65536);
        for (int i = 0; i < 2; i++) tma2d(sb + O_WV + i * 32768, &tm_wv, c0, r0 + i * 256, bars + 8 * B_WV);
        for (int i = 0; i < 4; i++) tma2d_prefetch(&tm_wo, j * 256 + i * 64, h * 128);
        tma4d_prefetch(&tm_x, kh * 8, (role >> 1) * 4);
    }
    __syncthreads();
    uint32_t mate;
    asm volatile("mapa.shared::cluster.u32 %0, %1, %2;" : "=r"(mate) : "r"(sb), "r"(kh ^ 1));

    if (wgi < 2) {
        asm volatile("setmaxnreg.inc.sync.aligned.u32 176;");
        uint32_t a[32][4];
        {
            const uint32_t stage = sb + (wgi == 0 ? O_WO : O_XB);
            const uint32_t ad = stage + (((lane >> 4) & 1) * 8 + (lane & 7)) * 128 + (((2 * w + ((lane >> 3) & 1)) ^ (lane & 7)) << 4);
#pragma unroll
            for (int i = 0; i < 2; i++) {
                mbar_wait(bars + 8 * (B_WQ0 + 2 * wgi + i), 0);
#pragma unroll
                for (int ks = 0; ks < 16; ks++) ldsm4t(a[i * 16 + ks], ad + (i * 16 + ks) * 2048);
            }
            __syncwarp();
            if (lane == 0) mbar_arrive(bars + 8 * (B_QDONE + wgi));
        }
        asm volatile("barrier.cluster.arrive.release.aligned;" ::: "memory");
        asm volatile("barrier.cluster.wait.acquire.aligned;" ::: "memory");
        const uint32_t frag = h * (3 * 512) + ((nh * 4 + w) * 2 + kh) * 32 + lane;
        const uint32_t mb0 = sb + O_MEM + (lane & 7) * 128 + (((lane >> 3) ^ (lane & 7)) << 4);
        uint32_t tref = gtime() - 4000;
#define MERGED_LOOP(R, HBAR)                                                                           \
        _Pragma("unroll 1") for (int s = -1; s < 64; s++) {                                            \
            TSI(s);                                                                                    \
            float d[20];                                                                               \
            if (s < 63) mbar_wait(bars + 8 * B_XFULL, (s + 1) & 1);                                    \
            _Pragma("unroll") for (int hf = 0; hf < 2; hf++) {                                         \
                if (s >= 0) mbar_wait(bars + 8 * (HBAR + hf), s & 1);                                  \
                if (hf == 0) TS(0); else TS(1);                                                        \
                wg_fence();                                                                            \
                _Pragma("unroll") for (int i = hf * 16; i < hf * 16 + 16; i++) {                       \
                    const int ks = ks_order(i);                                                        \
                    if (i == 0) wg_rs40<0>(d, a[ks], xdesc(ks)); else wg_rs40<1>(d, a[ks], xdesc(ks)); \
                }                                                                                      \
                wg_commit();                                                                           \
            }                                                                                          \
            wg_wait<0>();                                                                              \
            TS(2);                                                                                     \
            if (s >= 0) alpha_write<R>(d[16], d[17], d[18], d[19], s, frag);                           \
            if (lane == 0) { mbar_arrive(bars + 8 * B_QKW); mbar_arrive(bars + 8 * B_XEMPTY); }        \
            TS(3);                                                                                     \
            uint32_t sn[4]; float kp[8];                                                               \
            x_split(d, sn, kp, kh);                                                                    \
            if (R == 1 && w == 3 && s >= 0 && s < 63) {                                                \
                                                      \
                mbar_wait(bars + 8 * B_SDONE, s & 1);                                                  \
                wait_clk(clk(), tn.d_st);                                                              \
                uint32_t n = 0, mx;                                                                    \
                do {                                                                                   \
                    const uint4 st = ldg_rlx128(&g_stamp[lane]);                                       \
                    mx = __reduce_max_sync(~0u, max(max(st.x - tref, st.y - tref), max(st.z - tref, st.w - tref))); \
                } while (mx >= 200000u && ++n < 64);                                                   \
                tref = mx < 200000u ? tref + mx + 1 : gtime();                                         \
                if (lane == 0) { sts32(bars + 248, tref); mbar_arrive(bars + 8 * B_STAMP); }           \
                TSV(8, clk()); TSV(9, n);                                                              \
            }                                                                                          \
            if (s < 63 && !FLAG(0)) {                                                                  \
                if (s >= 0) mbar_wait(bars + 8 * SEND_BAR, s & 1);                                     \
                x_send<R>(sn, s + 1, tid, sb, mate);                                                   \
                TS(4);                                                                                 \
                if (s >= 0) mbar_wait(bars + 8 * B_OPDONE, s & 1);                                     \
                x_finish<R>(kp, s + 1, frag, tid, sb);                                                 \
                TS(5);                                                                                 \
            }                                                                                          \
        }
        if (wgi == 0) {
            MERGED_LOOP(0, B_MEM0);
        } else {
            MERGED_LOOP(1, (Q_SEP ? B_QH0 : B_MEM0));
        }
        TSDUMP();
    } else if (wgi == 2) {
        asm volatile("setmaxnreg.dec.sync.aligned.u32 64;");
        asm volatile("barrier.cluster.arrive.release.aligned;" ::: "memory");
        if (tid == 0) {
            mbar_wait(bars + 8 * B_KDONE, 0);
            mbar_expect_tx(bars + 8 * B_XFULL, 32768);
            tma4d(sb + O_XB, &tm_x, kh * 8, 0, bars + 8 * B_XFULL);
            mbar_wait(bars + 8 * B_QDONE, 0);
            mbar_expect_tx(bars + 8 * B_WO, 65536);
            for (int i = 0; i < 4; i++) tma2d(sb + O_WO + i * 16384, &tm_wo, j * 256 + i * 64, h * 128, bars + 8 * B_WO);
        }
        __syncwarp();
        asm volatile("barrier.cluster.wait.acquire.aligned;" ::: "memory");
        mbar_wait(bars + 8 * B_WV, 0);
#pragma unroll 1
        for (int s = -1; s < 64; s++) {
            TSI(s);
            OPAQUE_IDS();
            const uint32_t frag = h * (3 * 512) + ((nh * 4 + w) * 2 + kh) * 32 + lane;
            float d[20];
            mbar_wait(bars + 8 * B_QKW, (s + 1) & 1);
            TS(0);
            wg_fence();
#pragma unroll
            for (int ks = 0; ks < 32; ks++) {
                constexpr uint64_t da0 = mkdesc(SM_BASE + O_WV, 16, 1024, 1);
                if (ks == 0) wg_ss40<0>(d, da0 + ks * 128, xdesc(ks)); else wg_ss40<1>(d, da0 + ks * 128, xdesc(ks));
            }
            wg_commit();
            wg_wait<0>();
            TS(1);
            if (s >= 0) alpha_write<2>(d[16], d[17], d[18], d[19], s, frag);
            if (lane == 0) mbar_arrive(bars + 8 * B_XEMPTY);
            uint32_t sn[4]; float kp[8];
            x_split(d, sn, kp, kh);
            TS(2);
#define X_REFILL()                                                                     \
            if (s >= 0) mbar_wait(bars + 8 * B_SRDY, s & 1);                           \
            if (tid == 0 && s < 62) {                                                  \
                mbar_wait(bars + 8 * B_XEMPTY, (s + 1) & 1);                           \
                if (FLAG(2)) mbar_arrive(bars + 8 * B_XFULL);                          \
                else {                                                                 \
                    mbar_expect_tx(bars + 8 * B_XFULL, 32768);                         \
                    tma4d(sb + O_XB, &tm_x, kh * 8, (s + 2) * 4, bars + 8 * B_XFULL);  \
                }                                                                      \
            }                                                                          \
            __syncwarp();                                                              \
            if (s >= 0 && s < 63) mbar_wait(bars + 8 * B_OPDONE, s & 1);               \
            if (SEND_BAR == B_OPDONE && s < 63 && !FLAG(0)) x_send<2>(sn, s + 1, tid, sb, mate);
            if (s >= 0) mbar_wait(bars + 8 * B_SDONE, s & 1);
            if (SEND_BAR == B_SDONE && s < 63 && !FLAG(0)) x_send<2>(sn, s + 1, tid, sb, mate);
            if (XA_BAR == B_OPDONE) { X_REFILL(); }
            uint32_t pf[5]; float i0, i1;
            if (s >= 0) {
                float sc[10];
#pragma unroll
                for (int i = 0; i < 10; i++) sc[i] = 0.f;
                if (!FLAG(3)) {
#pragma unroll
                for (int q = 0; q < 4; q++) {
                    const uint32_t a0 = sb + O_S + 5120;
                    float4 x0 = lds128(a0 + q * 512 + lane * 16), x1 = lds128(a0 + 2048 + q * 512 + lane * 16);
                    float2 x2 = lds64(a0 + 4096 + q * 256 + lane * 8);
                    sc[0] += x0.x; sc[1] += x0.y; sc[2] += x0.z; sc[3] += x0.w; sc[4] += x1.x; sc[5] += x1.y; sc[6] += x1.z; sc[7] += x1.w;
                    sc[8] += x2.x; sc[9] += x2.y;
                }
                }
                __syncwarp();
                if (lane == 0) mbar_arrive(bars + 8 * B_SFREE);
                const int lim = 8 * j + (lane >> 2) - 2 * (lane & 3);
#pragma unroll
                for (int i = 2; i < 10; i++) if (8 * ((i >> 1) - 1) + (i & 1) > lim) sc[i] = MASK_VAL;
                float sum;
                softmax10(sc, pf, sum);
                sum += __shfl_xor_sync(~0u, sum, 1);
                sum += __shfl_xor_sync(~0u, sum, 2);
                const float inv = rcp(sum);
                i0 = __shfl_sync(~0u, inv, (lane & 3) * 8); i1 = __shfl_sync(~0u, inv, (lane & 3) * 8 + 4);
                TS(3);
            }
            if (XA_BAR == B_SDONE) { X_REFILL(); }
            TS(4);
            if (s < 63 && !FLAG(0)) x_finish<2>(kp, s + 1, frag, tid, sb);
            TS(5);
            if (s >= 0 && !FLAG(3)) {
                uint4 vf[4]; uint2 vm[4];
                const uint4* vp = &g_kvq[((s & 3) * 32 + h) * (3 * 512) + 1024 + w * 128 + lane];
                const uint2* ap = &g_alpha[((s & 1) * 32 + h) * (3 * 512) + 1024 + w * 128 + lane];
#pragma unroll
                for (int i = 0; i < 4; i++) { vf[i] = ldg_rlx128(vp + i * 32); vm[i] = ldg_rlx64(ap + i * 32); }
                uint32_t ow[4];
#pragma unroll
                for (int u = 0; u < 2; u++) {
                    float o[4] = {0.f, 0.f, 0.f, 0.f};
                    mma1688(o, add_bf16x2(vm[2 * u].x, vm[2 * u + 1].x), add_bf16x2(vm[2 * u].y, vm[2 * u + 1].y), pf[0]);
                    mma16816(o, vf[2 * u].x, vf[2 * u].y, vf[2 * u].z, vf[2 * u].w, pf[1], pf[2]);
                    mma16816(o, vf[2 * u + 1].x, vf[2 * u + 1].y, vf[2 * u + 1].z, vf[2 * u + 1].w, pf[3], pf[4]);
                    ow[2 * u] = pack_bf16(o[0] * i0, o[1] * i1);
                    ow[2 * u + 1] = pack_bf16(o[2] * i0, o[3] * i1);
                }
                const uint32_t xo = sb + O_XO + w * 512;
                stsm4t(xo + (lane & 7) * 64 + (((lane >> 3) ^ ((lane >> 1) & 3)) << 4), ow[0], ow[1], ow[2], ow[3]);
                __syncwarp();
                const uint4 ov = lds128u(xo + (lane >> 2) * 64 + (((lane & 3) ^ ((lane >> 3) & 3)) << 4));
                stg128(&g_ox[(size_t)(s * 32 + j * 8 + (lane >> 2)) * 4096 + h * 128 + w * 32 + (lane & 3) * 8], ov.x, ov.y, ov.z, ov.w);
                __syncwarp();
            }
            TS(6);
        }
        TSDUMP();
    } else {
        asm volatile("setmaxnreg.dec.sync.aligned.u32 96;");
        GT(0);
        asm volatile("barrier.cluster.arrive.release.aligned;" ::: "memory");
#define RED_CLEAR(st)                                                                                           \
        {                                                                                                       \
            unsigned char* zp = redp + ((st) & 3) * 65536 + (role >> 6) * 32768 + red_grp(role & 63) + red_slot(lane >> 3) + (lane & 7) * 16; \
            const uint32_t cb = RED_F32 ? __float_as_uint(64.f * (st)) : (((st) & 4) ? 0x42800000u : 0u);       \
            const uint32_t cz = (!RED_F32 && role >= 64) ? cb : 0u;                                             \
            stg128(zp, cz, cz, cz, cb);                                                                         \
        }
        uint32_t start_target = 0;
        if (w == 0) {
            RED_CLEAR(0); RED_CLEAR(1);
            fence_gpu();
            __syncwarp();
            if (lane == 0) start_target = (atomicAdd(&g_start, 1) & ~127u) + 128;
        }
        mbar_wait(bars + 8 * B_KDONE, 0);
        {
            const int kb0 = (w & 1) * 4 + (w >> 1) * 2;
#pragma unroll
            for (int q = 0; q < 4; q++) {
                const int row = (lane >> 3) + (q & 1) * 4, ch = lane & 7, kb = kb0 + (q >> 1);
                const uint4 v = *(const uint4*)(mem0 + row * 1024 + kh * 512 + kb * 64 + ch * 8);
                sts128u(sb + O_MEM + kb * 1024 + row * 128 + ((ch ^ row) << 4), v);
            }
            fence_async_smem();
            __syncwarp();
            if (lane == 0) mbar_arrive(bars + 8 * (B_MEM0 + (w >> 1)));
        }
        asm volatile("barrier.cluster.wait.acquire.aligned;" ::: "memory");
        if (tid == 0) { uint32_t n = 0; while ((int)(ld_acquire(&g_start) - start_target) < 0) { if (++n > SPIN_LIMIT) __trap(); } }
        mbar_wait(bars + 8 * B_WO, 0);
        GT(1);
        const uint32_t d_r = w >> 1 ? tn.d_r1 : tn.d_r0;
#pragma unroll 1
        for (int s = 0; s < 64; s++) {
            TSI(s);
            OPAQUE_IDS();
            uint4 kf[4], vf[4]; uint2 qf[2];
            {
                const uint4* bp = &g_kvq[((s & 3) * 32 + h) * (3 * 512) + w * 128 + lane];
                const uint32_t tg = ((s >> 2) & 1) ^ 1;
                uint32_t n = 0;
                while (true) {
#pragma unroll
                    for (int i = 0; i < 4; i++) kf[i] = ldg_rlx128(bp + 512 + i * 32);
#pragma unroll
                    for (int u = 0; u < 2; u++) qf[u] = ldg_rlx64((const uint2*)(bp + (2 * u + nh) * 32) + kh);
#pragma unroll
                    for (int i = 0; i < 4; i++) vf[i] = ldg_rlx128(bp + 1024 + i * 32);
                    const uint32_t x = orx2(kf[0].x, kf[1].x, tg) | orx2(kf[2].x, kf[3].x, tg) | orx2(qf[0].x, qf[1].x, tg) |
                                       orx2(vf[0].x, vf[1].x, tg) | orx2(vf[2].x, vf[3].x, tg);
                    if (!__any_sync(~0u, x & 1) || FLAG(0)) break;
                    if (++n > SPIN_LIMIT) __trap();
                }
                if (w == 0) TSV(22, n);
            }
            if (w == 0 && s < 62) RED_CLEAR(s + 2);
            if (s > 0) mbar_wait(bars + 8 * B_SFREE, (s - 1) & 1);
            const uint32_t tag = ((s >> 1) & 1) ^ 1;
            const uint2* ap = &g_alpha[((s & 1) * 32 + h) * (3 * 512) + w * 128 + lane];
            const uint32_t s16 = sb + O_S + tid * 16, s8 = sb + O_S + 4096 + tid * 8;
            TS(0);
            mbar_wait(bars + 8 * B_QKW, (s + 1) & 1);
            TS(1);
            wait_clk(clk(), tn.d_alpha);
            uint2 qa[4], ka[4];
            {
                uint32_t n = 0;
                while (true) {
#pragma unroll
                    for (int i = 0; i < 4; i++) { qa[i] = ldg_rlx64(ap + i * 32); ka[i] = ldg_rlx64(ap + 512 + i * 32); }
                    const uint32_t x = orx2(qa[0].x, ka[0].x, tag) | orx2(qa[1].x, ka[1].x, tag) | orx2(qa[2].x, ka[2].x, tag) | orx2(qa[3].x, ka[3].x, tag);
                    if (!__any_sync(~0u, x & 1)) break;
                    if (++n > SPIN_LIMIT) __trap();
                }
                if (w == 0) TSV(20, n);
            }
            TS(2);
            if (tid == 0) asm volatile("st.relaxed.gpu.global.u32 [%0], %1;" ::"l"((uint32_t*)g_stamp + role), "r"(gtime()) : "memory");
            float sa[5][4];
#pragma unroll
            for (int n = 0; n < 5; n++) sa[n][0] = sa[n][1] = sa[n][2] = sa[n][3] = 0.f;
#pragma unroll
            for (int u = 0; u < 2; u++) {
                const uint32_t q0 = add_bf16x2(qa[2 * u].x, qa[2 * u + 1].x), q1 = add_bf16x2(qa[2 * u].y, qa[2 * u + 1].y);
                const uint32_t k0 = add_bf16x2(ka[2 * u].x, ka[2 * u + 1].x), k1 = add_bf16x2(ka[2 * u].y, ka[2 * u + 1].y);
                mma16816(sa[1], q0, qf[u].x, q1, qf[u].y, kf[2 * u].x, kf[2 * u].y);
                mma16816(sa[0], q0, qf[u].x, q1, qf[u].y, k0, k1);
                mma16816(sa[2], q0, qf[u].x, q1, qf[u].y, kf[2 * u].z, kf[2 * u].w);
                mma16816(sa[3], q0, qf[u].x, q1, qf[u].y, kf[2 * u + 1].x, kf[2 * u + 1].y);
                mma16816(sa[4], q0, qf[u].x, q1, qf[u].y, kf[2 * u + 1].z, kf[2 * u + 1].w);
            }
            uint2 va[4];
            sts128(s16, sa[0][0], sa[0][1], sa[1][0], sa[1][1]);
            sts128(s16 + 2048, sa[2][0], sa[2][1], sa[3][0], sa[3][1]);
            sts64(s8, sa[4][0], sa[4][1]);
            if (AV_POS == 0) {
#pragma unroll
                for (int i = 0; i < 4; i++) va[i] = ldg_rlx64(ap + 1024 + i * 32);
            }
            bar_sync(1, 128);
            TS(15);
            float sc[10];
#pragma unroll
            for (int n = 0; n < 5; n++) { sc[2 * n] = sa[n][0]; sc[2 * n + 1] = sa[n][1]; }
#pragma unroll
            for (int q = 1; q < 4; q++) {
                float4 x0 = lds128(s16 ^ (q * 512)), x1 = lds128((s16 ^ (q * 512)) + 2048); float2 x2 = lds64(s8 ^ (q * 256));
                sc[0] += x0.x; sc[1] += x0.y; sc[2] += x0.z; sc[3] += x0.w; sc[4] += x1.x; sc[5] += x1.y; sc[6] += x1.z; sc[7] += x1.w;
                sc[8] += x2.x; sc[9] += x2.y;
            }
            sts128(s16 + 5120, sa[0][2], sa[0][3], sa[1][2], sa[1][3]);
            sts128(s16 + 5120 + 2048, sa[2][2], sa[2][3], sa[3][2], sa[3][3]);
            sts64(s8 + 5120, sa[4][2], sa[4][3]);
            if (AV_POS == 1) {
#pragma unroll
                for (int i = 0; i < 4; i++) va[i] = ldg_rlx64(ap + 1024 + i * 32);
            }
            __syncwarp();
            if (lane == 0) mbar_arrive(bars + 8 * B_SDONE);
            uint32_t pf[5]; float sum;
            softmax10(sc, pf, sum);
            TS(3);
            float o[2][4];
#pragma unroll
            for (int u = 0; u < 2; u++) {
                o[u][0] = o[u][1] = o[u][2] = o[u][3] = 0.f;
                mma16816(o[u], vf[2 * u].x, vf[2 * u].y, vf[2 * u].z, vf[2 * u].w, pf[1], pf[2]);
            }
#pragma unroll
            for (int u = 0; u < 2; u++) mma16816(o[u], vf[2 * u + 1].x, vf[2 * u + 1].y, vf[2 * u + 1].z, vf[2 * u + 1].w, pf[3], pf[4]);
            sum += __shfl_xor_sync(~0u, sum, 1);
            sum += __shfl_xor_sync(~0u, sum, 2);
            const float inv = rcp(sum);
            const float i0 = __shfl_sync(~0u, inv, (lane & 3) * 8), i1 = __shfl_sync(~0u, inv, (lane & 3) * 8 + 4);
            {
                uint32_t n = 0;
                while (__any_sync(~0u, (orx2(va[0].x, va[1].x, tag) | orx2(va[2].x, va[3].x, tag)) & 1)) {
#pragma unroll
                    for (int i = 0; i < 4; i++) va[i] = ldg_rlx64(ap + 1024 + i * 32);
                    if (++n > SPIN_LIMIT) __trap();
                }
                if (w == 0) TSV(21, n);
            }
#pragma unroll
            for (int u = 0; u < 2; u++)
                mma1688(o[u], add_bf16x2(va[2 * u].x, va[2 * u + 1].x), add_bf16x2(va[2 * u].y, va[2 * u + 1].y), pf[0]);
            TS(4);
            {
                const uint32_t oa = sb + O_O + w * 512 + lane * 4;
                sts32(oa, pack_bf16(o[0][0], o[0][1]));
                sts32(oa + 128, pack_bf16(o[0][2], o[0][3]));
                sts32(oa + 256, pack_bf16(o[1][0], o[1][1]));
                sts32(oa + 384, pack_bf16(o[1][2], o[1][3]));
            }
            fence_async_smem();
            bar_sync(1, 128);
            if (lane == 0) mbar_arrive(bars + 8 * B_SRDY);
            if (s == 0) GT(2);
            if (s == 63) { GT(3); break; }
            TS(5);
            unsigned char* const rb = redp + (s & 3) * 65536;
            unsigned char* const pg = rb + red_grp(j * 16 + (tid >> 3));
#pragma unroll
            for (int hf = 0; hf < 2; hf++) {
                float ca[4], cb[4];
                wg_fence();
                const uint64_t da0 = mkdesc(SM_BASE + O_WO, 16, 1024, 1) + hf * 2048;
#pragma unroll
                for (int ks = 0; ks < 8; ks++) {
                    constexpr uint64_t db0 = mkdesc(SM_BASE + O_O, 128, 128, 0);
                    if (ks == 0) { wg_ss8<0>(ca, da0, db0); wg_ss8<0>(cb, da0 + 1024, db0); }
                    else { wg_ss8<1>(ca, da0 + ks * 128, db0 + ks * 16); wg_ss8<1>(cb, da0 + 1024 + ks * 128, db0 + ks * 16); }
                }
                wg_commit();
                unsigned char* const pa = pg + (lane & 7) * 16 + hf * 512 + (h & 1) * 128;
                unsigned char* const pb = pg + (lane & 7) * 4 + 32768 + hf * 64 + (h & 1) * 32;
                wg_wait<0>();
                asm volatile("red.relaxed.gpu.global.add.noftz.v4.bf16x2 [%0], {%1,%2,%3,%4};" ::"l"(pa), "r"(pack_bf16(ca[0] * i0, ca[1] * i1)),
                             "r"(pack_bf16(ca[2] * i0, ca[3] * i1)), "r"(pack_bf16(cb[0] * i0, cb[1] * i1)), "r"(pack_bf16(cb[2] * i0, 1.f)) : "memory");
                asm volatile("red.relaxed.gpu.global.add.noftz.bf16x2 [%0], %1;" ::"l"(pb), "r"(pack_bf16(cb[3] * i1, 1.f)) : "memory");
                if (__shfl_xor_sync(~0u, tid, 1) == 999) __trap();
                TSV(6 + hf, clk());
            }
            if (lane == 0) mbar_arrive(bars + 8 * B_OPDONE);
            mbar_wait(bars + 8 * B_STAMP, s & 1);
            uint32_t tref;
            asm volatile("ld.shared.u32 %0, [%1];" : "=r"(tref) : "r"(bars + 248) : "memory");
            tref += d_r;
            {
                const unsigned char* pg = rb + red_grp((kh * 2 + (w & 1)) * 16 + (lane >> 3));
                uint32_t u[16];
                uint32_t n = 0;
                const uint32_t target = (s & 4) ? 0x42A00000u : 0x41800000u;
                const unsigned char* pa = pg + (lane & 7) * 16 + (w >> 1) * 512;
                const unsigned char* pb = pg + (lane & 7) * 4 + 32768 + (w >> 1) * 64;
                while ((int)(gtime() - tref) < 0) {}
                TSV(8 + (w >> 1), clk());
                uint4 ra[4], rc[4]; uint32_t re[4], rf[4];
                while (true) {
                    uint32_t x = 0;
#pragma unroll
                    for (int q = 0; q < 4; q++) {
                        ra[q] = ldg_rlx128(pa + q * 2048); rc[q] = ldg_rlx128(pa + q * 2048 + 128);
                        re[q] = ldg_rlx32(pb + q * 2048); rf[q] = ldg_rlx32(pb + q * 2048 + 32);
                    }
#pragma unroll
                    for (int q = 0; q < 4; q++) x |= (ra[q].w ^ target) | (rc[q].w ^ target) | (re[q] ^ target) | (rf[q] ^ target);
                    if (!__any_sync(~0u, x >> 16)) break;
                    if (++n > SPIN_LIMIT) __trap();
                }
#pragma unroll
                for (int q = 0; q < 4; q++) {
                    u[2 * q] = add_bf16x2(ra[q].x, rc[q].x);
                    u[2 * q + 1] = add_bf16x2(ra[q].y, rc[q].y);
                    u[8 + 2 * q] = add_bf16x2(ra[q].z, rc[q].z);
                    u[8 + 2 * q + 1] = add_bf16x2(__byte_perm(ra[q].w, re[q], 0x5410), __byte_perm(rc[q].w, rf[q], 0x5410));
                }
                TSV(10 + (w >> 1), clk());
                const uint32_t ma = sb + O_MEM + ((w & 1) * 4 + (w >> 1) * 2) * 1024 + (lane & 7) * 128 + (((lane >> 3) ^ (lane & 7)) << 4);
                stsm4t(ma, u[0], u[1], u[2], u[3]);
                stsm4t(ma ^ 64, u[4], u[5], u[6], u[7]);
                stsm4t(ma + 1024, u[8], u[9], u[10], u[11]);
                stsm4t((ma ^ 64) + 1024, u[12], u[13], u[14], u[15]);
                fence_async_smem();
                __syncwarp();
                if (lane == 0) mbar_arrive(bars + 8 * (B_MEM0 + (w >> 1)));
                TSV(12 + (w >> 1), clk()); TSV(16 + w, n);
            }
        }
        TSDUMP();
    }
}

constexpr int G_ST = 6;
constexpr uint32_t G_SMEM = G_ST * 32768 + 256;
#define F16(d, o) F4(d, o), F4(d, o + 4), F4(d, o + 8), F4(d, o + 12)
__device__ __forceinline__ void wg_ss128(float (&d)[64], uint64_t da, uint64_t db, int sc) {
    asm volatile("{\n.reg .pred p;\nsetp.ne.b32 p, %66, 0;\nwgmma.mma_async.sync.aligned.m64n128k16.f32.bf16.bf16 "
                 "{%0,%1,%2,%3,%4,%5,%6,%7,%8,%9,%10,%11,%12,%13,%14,%15,%16,%17,%18,%19,%20,%21,%22,%23,%24,%25,%26,%27,%28,%29,%30,%31,"
                 "%32,%33,%34,%35,%36,%37,%38,%39,%40,%41,%42,%43,%44,%45,%46,%47,%48,%49,%50,%51,%52,%53,%54,%55,%56,%57,%58,%59,%60,%61,%62,%63}, "
                 "%64, %65, p, 1, 1, 0, 1;\n}"
                 : F16(d, 0), F16(d, 16), F16(d, 32), F16(d, 48) : "l"(da), "l"(db), "r"(sc));
}

__global__ void __launch_bounds__(384, 1)
out_gemm(const __grid_constant__ CUtensorMap tm_o, const __grid_constant__ CUtensorMap tm_w, bf16* __restrict__ out) {
    extern __shared__ __align__(1024) unsigned char smem_raw[];
    const uint32_t sb = smem_u32(smem_raw), bars = sb + G_ST * 32768;
    const int m0 = (blockIdx.x >> 3) * 128, n0 = (blockIdx.x & 7) * 128;
    const int wgi = __shfl_sync(~0u, threadIdx.x >> 7, 0), tid = threadIdx.x & 127;
    if (threadIdx.x == 0) {
        for (int i = 0; i < G_ST; i++) { mbar_init(bars + 8 * i, 1); mbar_init(bars + 8 * (G_ST + i), 8); }
        fence_async_smem();
    }
    __syncthreads();
    if (wgi == 0) GT(4);
    if (wgi == 2) {
        if (tid == 0) {
            for (int kt = 0; kt < 64; kt++) {
                const int st = kt % G_ST;
                if (kt >= G_ST) mbar_wait(bars + 8 * (G_ST + st), (kt / G_ST - 1) & 1);
                mbar_expect_tx(bars + 8 * st, 32768);
                tma2d(sb + st * 32768, &tm_o, kt * 64, m0, bars + 8 * st);
                tma2d(sb + st * 32768 + 16384, &tm_w, n0, kt * 64, bars + 8 * st);
                tma2d(sb + st * 32768 + 24576, &tm_w, n0 + 64, kt * 64, bars + 8 * st);
            }
        }
    } else {
        float d[64];
        int st = 0, ph = 0;
#pragma unroll 1
        for (int kt = 0; kt < 64; kt++) {
            mbar_wait(bars + 8 * st, ph);
            const uint64_t da = mkdesc(sb + st * 32768 + wgi * 8192, 16, 1024, 1), db = mkdesc(sb + st * 32768 + 16384, 8192, 1024, 1);
            wg_fence();
#pragma unroll
            for (int k = 0; k < 4; k++) wg_ss128(d, da + k * 2, db + k * 128, kt | k);
            wg_commit();
            if (kt > 0) {
                wg_wait<1>();
                if ((tid & 31) == 0) mbar_arrive(bars + 8 * (G_ST + (st == 0 ? G_ST - 1 : st - 1)));
            }
            if (++st == G_ST) { st = 0; ph ^= 1; }
        }
        wg_wait<0>();
        const int row = m0 + wgi * 64 + (tid >> 5) * 16 + ((tid & 31) >> 2);
        bf16* op = out + (size_t)row * 2048 + 1024 + n0 + (tid & 3) * 2;
#pragma unroll
        for (int i = 0; i < 16; i++) {
            *(uint32_t*)(op + i * 8) = pack_bf16(d[4 * i], d[4 * i + 1]);
            *(uint32_t*)(op + 8 * 2048 + i * 8) = pack_bf16(d[4 * i + 2], d[4 * i + 3]);
        }
        if (wgi == 0) GT(5);
    }
}

typedef CUresult (*EncodeFn)(CUtensorMap*, CUtensorMapDataType, cuuint32_t, void*, const cuuint64_t*, const cuuint64_t*,
                             const cuuint32_t*, const cuuint32_t*, CUtensorMapInterleave, CUtensorMapSwizzle,
                             CUtensorMapL2promotion, CUtensorMapFloatOOBfill);

static void make_map(EncodeFn fn, CUtensorMap* m, const void* p, uint64_t cols, uint64_t rows, uint32_t bc, uint32_t br) {
    cuuint64_t dims[2] = {cols, rows}, strides[1] = {cols * 2};
    cuuint32_t box[2] = {bc, br}, es[2] = {1, 1};
    fn(m, CU_TENSOR_MAP_DATA_TYPE_BFLOAT16, 2, (void*)p, dims, strides, box, es, CU_TENSOR_MAP_INTERLEAVE_NONE,
       CU_TENSOR_MAP_SWIZZLE_128B, CU_TENSOR_MAP_L2_PROMOTION_L2_128B, CU_TENSOR_MAP_FLOAT_OOB_FILL_NONE);
}

static Tune h_tune = {450, 900, 1100, 0, 200};

extern "C" void kernel_launch(void* const* d_in, const int* in_sizes, int n_in, void* d_out, int out_size) {
    static bool init = false;
    static CUtensorMap tm_x, tm_wq, tm_wk, tm_wv, tm_wo, tm_o, tm_wo2;
    if (!init) {
        void* fp = nullptr; cudaDriverEntryPointQueryResult qr;
        cudaGetDriverEntryPoint("cuTensorMapEncodeTiled", &fp, cudaEnableDefault, &qr);
        EncodeFn fn = (EncodeFn)fp;
        void* ox = nullptr; cudaGetSymbolAddress(&ox, g_ox);
        {
            cuuint64_t dims[4] = {64, 8, 16, 256}, strides[3] = {2048, 128, 16384};
            cuuint32_t box[4] = {64, 8, 8, 4}, es[4] = {1, 1, 1, 1};
            fn(&tm_x, CU_TENSOR_MAP_DATA_TYPE_BFLOAT16, 4, d_in[3], dims, strides, box, es, CU_TENSOR_MAP_INTERLEAVE_NONE,
               CU_TENSOR_MAP_SWIZZLE_128B, CU_TENSOR_MAP_L2_PROMOTION_L2_128B, CU_TENSOR_MAP_FLOAT_OOB_FILL_NONE);
        }
        make_map(fn, &tm_wq, d_in[5], 4096, 1024, 64, 256);
        make_map(fn, &tm_wk, d_in[6], 4096, 1024, 64, 256);
        make_map(fn, &tm_wv, d_in[7], 4096, 1024, 64, 256);
        make_map(fn, &tm_wo, d_in[8], 1024, 4096, 64, 128);
        make_map(fn, &tm_o, ox, 4096, 2048, 64, 128);
        make_map(fn, &tm_wo2, d_in[8], 1024, 4096, 64, 64);
        cudaFuncSetAttribute(rmt_main, cudaFuncAttributeMaxDynamicSharedMemorySize, MAIN_SMEM);
        cudaFuncSetAttribute(out_gemm, cudaFuncAttributeMaxDynamicSharedMemorySize, G_SMEM);
        init = true;
    }
    rmt_main<<<132, 512, MAIN_SMEM>>>(tm_x, tm_wq, tm_wk, tm_wv, tm_wo, (const bf16*)d_in[4], h_tune);
    out_gemm<<<128, 384, G_SMEM>>>(tm_o, tm_wo2, (bf16*)d_out);
}
```

```cpp
#include <cuda_runtime.h>
#include <cuda_bf16.h>
#include <cuda.h>
#include <stdint.h>

typedef __nv_bfloat16 bf16;

#define DBG_TIMING 0

#define SPIN_LIMIT (1u << 22)

__device__ __forceinline__ uint32_t smem_u32(const void* p) { return (uint32_t)__cvta_generic_to_shared(p); }
__device__ __forceinline__ uint32_t clk() { uint32_t c; asm volatile("mov.u32 %0, %%clock;" : "=r"(c)::"memory"); return c; }
#define SCHED_FENCE() sf ^= (uint32_t)clock64()
__device__ __forceinline__ uint32_t gtime() { uint32_t c; asm volatile("mov.u32 %0, %%globaltimer_lo;" : "=r"(c)::"memory"); return c; }
__device__ __forceinline__ void wait_clk(uint32_t t0, uint32_t d) {
    asm volatile("{\n.reg .pred p;\n.reg .s32 t;\n.reg .b64 c;\nWL:\nmov.u64 c, %%clock64;\ncvt.u32.u64 t, c;\nsub.s32 t, t, %0;\nsetp.lt.s32 p, t, 0;\n@p bra.uni WL;\n}" ::"r"(t0 + d) : "memory");
}
__device__ __forceinline__ void wait_gtime(uint32_t t1) {
    asm volatile("{\n.reg .pred p;\n.reg .s32 t;\n.reg .b64 c;\nWL:\nmov.u64 c, %%globaltimer;\ncvt.u32.u64 t, c;\nsub.s32 t, t, %0;\nsetp.lt.s32 p, t, 0;\n@p bra.uni WL;\n}" ::"r"(t1) : "memory");
}

__device__ __forceinline__ void mbar_init(uint32_t bar, uint32_t cnt) {
    asm volatile("mbarrier.init.shared::cta.b64 [%0], %1;" ::"r"(bar), "r"(cnt) : "memory");
}
__device__ __forceinline__ void mbar_arrive(uint32_t bar) {
    asm volatile("mbarrier.arrive.shared::cta.b64 _, [%0];" ::"r"(bar) : "memory");
}
__device__ __forceinline__ void mbar_expect_tx(uint32_t bar, uint32_t bytes) {
    asm volatile("mbarrier.arrive.expect_tx.shared::cta.b64 _, [%0], %1;" ::"r"(bar), "r"(bytes) : "memory");
}
__device__ __forceinline__ void mbar_wait(uint32_t bar, uint32_t parity) {
    asm volatile(
        "{\n.reg .pred p, q;\n.reg .u32 n;\nmov.u32 n, 0;\n"
        "WL:\nmbarrier.try_wait.parity.shared::cta.b64 p, [%0], %1;\n"
        "add.u32 n, n, 1;\nsetp.gt.u32 q, n, %2;\n@q trap;\n@!p bra.uni WL;\n}" ::"r"(bar), "r"(parity), "n"(SPIN_LIMIT) : "memory");
}
__device__ __forceinline__ void mbar_wait_cluster(uint32_t bar, uint32_t parity) {
    asm volatile(
        "{\n.reg .pred p, q;\n.reg .u32 n;\nmov.u32 n, 0;\n"
        "WL:\nmbarrier.try_wait.parity.acquire.cluster.shared::cta.b64 p, [%0], %1;\n"
        "add.u32 n, n, 1;\nsetp.gt.u32 q, n, %2;\n@q trap;\n@!p bra.uni WL;\n}" ::"r"(bar), "r"(parity), "n"(SPIN_LIMIT) : "memory");
}
__device__ __forceinline__ void tma2d(uint32_t dst, const CUtensorMap* m, int c0, int c1, uint32_t bar) {
    asm volatile("cp.async.bulk.tensor.2d.shared::cluster.global.mbarrier::complete_tx::bytes [%0], [%1, {%3, %4}], [%2];"
                 ::"r"(dst), "l"(m), "r"(bar), "r"(c0), "r"(c1) : "memory");
}
__device__ __forceinline__ void tma4d(uint32_t dst, const CUtensorMap* m, int c2, int c3, uint32_t bar) {
    asm volatile("cp.async.bulk.tensor.4d.shared::cluster.global.mbarrier::complete_tx::bytes [%0], [%1, {%5, %5, %3, %4}], [%2];"
                 ::"r"(dst), "l"(m), "r"(bar), "r"(c2), "r"(c3), "r"(0) : "memory");
}
__device__ __forceinline__ void tma4d_prefetch(const CUtensorMap* m, int c2, int c3) {
    asm volatile("cp.async.bulk.prefetch.tensor.4d.L2.global [%0, {%3, %3, %1, %2}];" ::"l"(m), "r"(c2), "r"(c3), "r"(0) : "memory");
}
__device__ __forceinline__ void tma2d_prefetch(const CUtensorMap* m, int c0, int c1) {
    asm volatile("cp.async.bulk.prefetch.tensor.2d.L2.global [%0, {%1, %2}];" ::"l"(m), "r"(c0), "r"(c1) : "memory");
}
__device__ __forceinline__ void fence_async_smem() { asm volatile("fence.proxy.async.shared::cta;" ::: "memory"); }
__device__ __forceinline__ void fence_gpu() { asm volatile("fence.acq_rel.gpu;" ::: "memory"); }
__device__ __forceinline__ float rcp(float x) { float r; asm("rcp.approx.ftz.f32 %0, %1;" : "=f"(r) : "f"(x)); return r; }
__device__ __forceinline__ void bar_sync(int id, int n) { asm volatile("bar.sync %0, %1;" ::"r"(id), "r"(n) : "memory"); }

__device__ __forceinline__ bool bar_or(int id, int n, uint32_t x) {
    uint32_t r;
    asm volatile("{\n.reg .pred p, q;\n.reg .b32 t;\nand.b32 t, %3, 1;\nsetp.ne.u32 p, t, 0;\nbar.red.or.pred q, %1, %2, p;\nselp.u32 %0, 1, 0, q;\n}"
                 : "=r"(r) : "r"(id), "r"(n), "r"(x) : "memory");
    return __any_sync(~0u, r);
}
__device__ __forceinline__ uint32_t or3(uint32_t a, uint32_t b, uint32_t c) {
    uint32_t r; asm("lop3.b32 %0, %1, %2, %3, 0xFE;" : "=r"(r) : "r"(a), "r"(b), "r"(c)); return r;
}
__device__ __forceinline__ uint32_t pack_bf16(float lo, float hi) {
    uint32_t r; asm("cvt.rn.bf16x2.f32 %0, %1, %2;" : "=r"(r) : "f"(hi), "f"(lo)); return r;
}
__device__ __forceinline__ uint32_t add_bf16x2(uint32_t a, uint32_t b) {
    uint32_t r; asm volatile("add.rn.bf16x2 %0, %1, %2;" : "=r"(r) : "r"(a), "r"(b)); return r;
}
__device__ __forceinline__ uint32_t movm(uint32_t a) {
    uint32_t r; asm volatile("movmatrix.sync.aligned.m8n8.trans.b16 %0, %1;" : "=r"(r) : "r"(a)); return r;
}
__device__ __forceinline__ uint32_t orx(uint32_t acc, uint32_t a, uint32_t t) {
    uint32_t r; asm("lop3.b32 %0, %1, %2, %3, 0xF6;" : "=r"(r) : "r"(acc), "r"(a), "r"(t)); return r;
}
__device__ __forceinline__ uint32_t orx2(uint32_t a, uint32_t b, uint32_t t) {
    uint32_t r; asm("lop3.b32 %0, %1, %2, %3, 0x7E;" : "=r"(r) : "r"(a), "r"(b), "r"(t)); return r;
}
__device__ __forceinline__ float ex2(float x) { float r; asm("ex2.approx.ftz.f32 %0, %1;" : "=f"(r) : "f"(x)); return r; }
__device__ __forceinline__ void ldsm4t(uint32_t (&r)[4], uint32_t a) {
    asm volatile("ldmatrix.sync.aligned.m8n8.x4.trans.shared.b16 {%0,%1,%2,%3}, [%4];"
                 : "=r"(r[0]), "=r"(r[1]), "=r"(r[2]), "=r"(r[3]) : "r"(a) : "memory");
}
__device__ __forceinline__ void ldsm4(uint32_t (&r)[4], uint32_t a) {
    asm volatile("ldmatrix.sync.aligned.m8n8.x4.shared.b16 {%0,%1,%2,%3}, [%4];"
                 : "=r"(r[0]), "=r"(r[1]), "=r"(r[2]), "=r"(r[3]) : "r"(a) : "memory");
}
__device__ __forceinline__ void stsm4t(uint32_t a, uint32_t r0, uint32_t r1, uint32_t r2, uint32_t r3) {
    asm volatile("stmatrix.sync.aligned.m8n8.x4.trans.shared.b16 [%0], {%1,%2,%3,%4};"
                 ::"r"(a), "r"(r0), "r"(r1), "r"(r2), "r"(r3) : "memory");
}
__device__ __forceinline__ void stsm4(uint32_t a, uint32_t r0, uint32_t r1, uint32_t r2, uint32_t r3) {
    asm volatile("stmatrix.sync.aligned.m8n8.x4.shared.b16 [%0], {%1,%2,%3,%4};"
                 ::"r"(a), "r"(r0), "r"(r1), "r"(r2), "r"(r3) : "memory");
}
__device__ __forceinline__ void mma16816(float* c, uint32_t a0, uint32_t a1, uint32_t a2, uint32_t a3, uint32_t b0, uint32_t b1) {
    asm volatile("mma.sync.aligned.m16n8k16.row.col.f32.bf16.bf16.f32 {%0,%1,%2,%3}, {%4,%5,%6,%7}, {%8,%9}, {%0,%1,%2,%3};"
                 : "+f"(c[0]), "+f"(c[1]), "+f"(c[2]), "+f"(c[3]) : "r"(a0), "r"(a1), "r"(a2), "r"(a3), "r"(b0), "r"(b1));
}
__device__ __forceinline__ void mma1688(float* c, uint32_t a0, uint32_t a1, uint32_t b0) {
    asm volatile("mma.sync.aligned.m16n8k8.row.col.f32.bf16.bf16.f32 {%0,%1,%2,%3}, {%4,%5}, {%6}, {%0,%1,%2,%3};"
                 : "+f"(c[0]), "+f"(c[1]), "+f"(c[2]), "+f"(c[3]) : "r"(a0), "r"(a1), "r"(b0));
}
__device__ __forceinline__ void sts128(uint32_t a, float x, float y, float z, float w) {
    asm volatile("st.shared.v4.f32 [%0], {%1,%2,%3,%4};" ::"r"(a), "f"(x), "f"(y), "f"(z), "f"(w) : "memory");
}
__device__ __forceinline__ void sts64(uint32_t a, float x, float y) {
    asm volatile("st.shared.v2.f32 [%0], {%1,%2};" ::"r"(a), "f"(x), "f"(y) : "memory");
}
__device__ __forceinline__ void sts32(uint32_t a, uint32_t x) { asm volatile("st.shared.b32 [%0], %1;" ::"r"(a), "r"(x) : "memory"); }
__device__ __forceinline__ void sts128u(uint32_t a, uint4 v) {
    asm volatile("st.shared.v4.b32 [%0], {%1,%2,%3,%4};" ::"r"(a), "r"(v.x), "r"(v.y), "r"(v.z), "r"(v.w) : "memory");
}
__device__ __forceinline__ float4 lds128(uint32_t a) {
    float4 v; asm volatile("ld.shared.v4.f32 {%0,%1,%2,%3}, [%4];" : "=f"(v.x), "=f"(v.y), "=f"(v.z), "=f"(v.w) : "r"(a) : "memory"); return v;
}
__device__ __forceinline__ uint4 lds128u(uint32_t a) {
    uint4 v; asm volatile("ld.shared.v4.b32 {%0,%1,%2,%3}, [%4];" : "=r"(v.x), "=r"(v.y), "=r"(v.z), "=r"(v.w) : "r"(a) : "memory"); return v;
}
__device__ __forceinline__ float2 lds64(uint32_t a) {
    float2 v; asm volatile("ld.shared.v2.f32 {%0,%1}, [%2];" : "=f"(v.x), "=f"(v.y) : "r"(a) : "memory"); return v;
}
__device__ __forceinline__ uint2 ldg_rlx64(const void* p) {
    uint2 v; asm volatile("ld.relaxed.gpu.global.v2.b32 {%0,%1}, [%2];" : "=r"(v.x), "=r"(v.y) : "l"(p) : "memory"); return v;
}
__device__ __forceinline__ uint4 ldg_rlx128(const void* p) {
    uint4 v; asm volatile("ld.relaxed.gpu.global.v4.b32 {%0,%1,%2,%3}, [%4];" : "=r"(v.x), "=r"(v.y), "=r"(v.z), "=r"(v.w) : "l"(p) : "memory"); return v;
}
__device__ __forceinline__ void stg_rlx64(void* p, uint32_t x, uint32_t y) {
    asm volatile("st.relaxed.gpu.global.v2.b32 [%0], {%1,%2};" ::"l"(p), "r"(x), "r"(y) : "memory");
}
__device__ __forceinline__ void stg_rlx128(void* p, uint32_t x, uint32_t y, uint32_t z, uint32_t w) {
    asm volatile("st.relaxed.gpu.global.v4.b32 [%0], {%1,%2,%3,%4};" ::"l"(p), "r"(x), "r"(y), "r"(z), "r"(w) : "memory");
}
__device__ __forceinline__ uint32_t ldg_rlx32(const void* p) {
    uint32_t v; asm volatile("ld.relaxed.gpu.global.b32 %0, [%1];" : "=r"(v) : "l"(p) : "memory"); return v;
}
__device__ __forceinline__ void stg128(void* p, uint32_t x, uint32_t y, uint32_t z, uint32_t w) {
    asm volatile("st.global.v4.b32 [%0], {%1,%2,%3,%4};" ::"l"(p), "r"(x), "r"(y), "r"(z), "r"(w) : "memory");
}
__device__ __forceinline__ uint32_t ld_acquire(const unsigned* p) {
    uint32_t v; asm volatile("ld.acquire.gpu.global.u32 %0, [%1];" : "=r"(v) : "l"(p) : "memory"); return v;
}
__device__ __forceinline__ void red_add_u32(unsigned* p, uint32_t v) {
    asm volatile("red.relaxed.gpu.global.add.u32 [%0], %1;" ::"l"(p), "r"(v) : "memory");
}
__device__ __forceinline__ void wait_counter(const unsigned* p, uint32_t target) {
    uint32_t n = 0;
    while (ld_acquire(p) < target) { if (++n > SPIN_LIMIT) __trap(); }
}

__device__ __forceinline__ void wg_fence() { asm volatile("wgmma.fence.sync.aligned;" ::: "memory"); }
__device__ __forceinline__ void wg_commit() { asm volatile("wgmma.commit_group.sync.aligned;" ::: "memory"); }
template <int N> __device__ __forceinline__ void wg_wait() { asm volatile("wgmma.wait_group.sync.aligned %0;" ::"n"(N) : "memory"); }
__host__ __device__ constexpr uint64_t mkdesc(uint32_t addr, uint32_t lbo, uint32_t sbo, uint32_t swz) {
    return (uint64_t)((addr & 0x3FFFF) >> 4) | ((uint64_t)(lbo >> 4) << 16) | ((uint64_t)(sbo >> 4) << 32) | ((uint64_t)swz << 62);
}
#define F4(d, o) "+f"(d[o]), "+f"(d[o + 1]), "+f"(d[o + 2]), "+f"(d[o + 3])
template <int SC> __device__ __forceinline__ void wg_rs32(float (&d)[16], const uint32_t (&a)[4], uint64_t db) {
    asm volatile("wgmma.mma_async.sync.aligned.m64n32k16.f32.bf16.bf16 "
                 "{%0,%1,%2,%3,%4,%5,%6,%7,%8,%9,%10,%11,%12,%13,%14,%15}, {%16,%17,%18,%19}, %20, %21, 1, 1, 0;"
                 : F4(d, 0), F4(d, 4), F4(d, 8), F4(d, 12)
                 : "r"(a[0]), "r"(a[1]), "r"(a[2]), "r"(a[3]), "l"(db), "n"(SC));
}
template <int SC> __device__ __forceinline__ void wg_rs40(float (&d)[20], const uint32_t (&a)[4], uint64_t db) {
    asm volatile("wgmma.mma_async.sync.aligned.m64n40k16.f32.bf16.bf16 "
                 "{%0,%1,%2,%3,%4,%5,%6,%7,%8,%9,%10,%11,%12,%13,%14,%15,%16,%17,%18,%19}, {%20,%21,%22,%23}, %24, %25, 1, 1, 0;"
                 : F4(d, 0), F4(d, 4), F4(d, 8), F4(d, 12), F4(d, 16)
                 : "r"(a[0]), "r"(a[1]), "r"(a[2]), "r"(a[3]), "l"(db), "n"(SC));
}
template <int SC> __device__ __forceinline__ void wg_ss40(float (&d)[20], uint64_t da, uint64_t db) {
    asm volatile("wgmma.mma_async.sync.aligned.m64n40k16.f32.bf16.bf16 "
                 "{%0,%1,%2,%3,%4,%5,%6,%7,%8,%9,%10,%11,%12,%13,%14,%15,%16,%17,%18,%19}, %20, %21, %22, 1, 1, 1, 0;"
                 : F4(d, 0), F4(d, 4), F4(d, 8), F4(d, 12), F4(d, 16)
                 : "l"(da), "l"(db), "n"(SC));
}
template <int SC> __device__ __forceinline__ void wg_ss8(float (&d)[4], uint64_t da, uint64_t db) {
    asm volatile("wgmma.mma_async.sync.aligned.m64n8k16.f32.bf16.bf16 {%0,%1,%2,%3}, %4, %5, %6, 1, 1, 1, 1;"
                 : F4(d, 0) : "l"(da), "l"(db), "n"(SC));
}

__device__ uint4 g_kvq[4 * 32 * 3 * 8 * 2 * 32];
__device__ uint2 g_alpha[2 * 32 * 3 * 8 * 2 * 32];
__device__ uint4 g_red[(4 * 65536 + 32768) / 16];
__device__ uint4 g_stamp[32];
__device__ unsigned g_start;
__device__ bf16 g_ox[2048 * 4096];
#define TSI(st) do {} while (0)
#define TS(k) do {} while (0)
#define TSV(k, v) do {} while (0)
#define TSDUMP() do {} while (0)
#define GT(k) do {} while (0)
#define FLAG(b) false

struct Tune { uint32_t d_alpha, d_r0, d_r1, flags, d_st, d_v, spread, extra; };
#define RED_F32 0
#define KQ_POS 1
#define OP_SPLIT 0
#define X_SEQ 0
constexpr int RA = 2;
#define AV_POS 2

constexpr uint32_t SM_BASE = 1024;
constexpr uint32_t O_WO = 0;
constexpr uint32_t O_WV = 65536;
constexpr uint32_t O_XB = 131072;
constexpr uint32_t O_MEM = O_XB + 32768;
constexpr uint32_t O_RECV = O_MEM + 8192;
constexpr uint32_t O_S = O_RECV + 24576;
constexpr uint32_t O_P = O_S + 10240;
constexpr uint32_t O_O = O_P + 1536;
constexpr uint32_t O_XO = O_O + 2048;
constexpr uint32_t O_BAR = O_XO + 2048;
constexpr uint32_t O_DBG = O_BAR + 256;
constexpr uint32_t MAIN_SMEM = O_DBG + (DBG_TIMING ? 4 * 32 * 24 * 4 : 0);
enum { B_WQ0 = 0, B_WQ1, B_WK0, B_WK1, B_WV, B_WO, B_QDONE, B_KDONE, B_XFULL, B_XEMPTY, B_MEM, B_QX, B_U0, B_U1,
       B_RECV, B_QKW = B_RECV + 6, B_SDONE, B_SRDY, B_OPDONE, B_STAMP, B_COUNT };

constexpr float SM_SCALE_LOG2 = 0.08838834764831845f * 1.4426950408889634f;
constexpr float MASK_VAL = -1.0e9f / 0.08838834764831845f;

__host__ __device__ constexpr uint32_t red_slot(int i) { return (uint32_t)((i >> 2) * 32768 + (i & 1) * 128 + ((i >> 1) & 1) * 512); }
__device__ __forceinline__ uint32_t red_grp(int grp) { return (uint32_t)((grp >> 1) * 1024 + (grp & 1) * 256); }
__host__ __device__ constexpr int ks_order(int i) { return (((i >> 3) & 1) * 4 + (i >> 4) * 2 + ((i >> 2) & 1)) * 4 + (i & 3); }
__host__ __device__ constexpr uint64_t xdesc(int ks) { return mkdesc(SM_BASE + O_XB + (ks >> 2) * 1024 + (ks & 3) * 32, 16, 8192, 1); }

__device__ __forceinline__ void x_split(const float* d, uint32_t (&sn)[4], float (&k)[8], int kh) {
#pragma unroll
    for (int i = 0; i < 4; i++) {
        sn[i] = pack_bf16(kh ? d[2 * i] : d[8 + 2 * i], kh ? d[2 * i + 1] : d[8 + 2 * i + 1]);
        k[2 * i] = kh ? d[8 + 2 * i] : d[2 * i]; k[2 * i + 1] = kh ? d[8 + 2 * i + 1] : d[2 * i + 1];
    }
}
__device__ __forceinline__ void x_send(int R, const uint32_t (&sn)[4], int sg, int tid, uint32_t sb, uint32_t mate) {
    const uint32_t par = sg & 1;
    const uint32_t bar = O_BAR + 8 * (B_RECV + R * 2) + 8 * par;
    if (tid == 0) mbar_expect_tx(sb + bar, 2048);
    asm volatile("st.async.shared::cluster.mbarrier::complete_tx::bytes.v4.b32 [%0], {%1,%2,%3,%4}, [%5];"
                 ::"r"(mate + O_RECV + (par * 3 + R) * 2048 + tid * 16), "r"(sn[0]), "r"(sn[1]), "r"(sn[2]), "r"(sn[3]), "r"(mate + bar) : "memory");
}
__device__ __forceinline__ uint32_t add_pack(float a, float b, uint32_t r) {
    return pack_bf16(a + __uint_as_float(r << 16), b + __uint_as_float(r & 0xffff0000u));
}
template <bool TR>
__device__ __forceinline__ void x_finish(int R, const float (&k)[8], int sg, uint32_t frag, int tid, uint32_t sb) {
    const uint32_t par = sg & 1;
    mbar_wait_cluster(sb + O_BAR + 8 * (B_RECV + R * 2) + 8 * par, (sg >> 1) & 1);
    const uint4 r = lds128u(sb + O_RECV + (par * 3 + R) * 2048 + tid * 16);
    uint32_t u0 = add_pack(k[0], k[1], r.x), u1 = add_pack(k[2], k[3], r.y), u2 = add_pack(k[4], k[5], r.z), u3 = add_pack(k[6], k[7], r.w);
    if (TR) { u0 = movm(u0); u1 = movm(u1); u2 = movm(u2); u3 = movm(u3); }
    const uint32_t tag = ((sg >> 2) & 1) ^ 1;
    u0 = (u0 & ~1u) | tag;
    if (R == 0) u2 = (u2 & ~1u) | tag;
    stg_rlx128(&g_kvq[(sg & 3) * (32 * 3 * 512) + frag], u0, u1, u2, u3);
}
template <bool TR>
__device__ __forceinline__ void alpha_write(float d0, float d1, float d2, float d3, uint32_t tag, uint2* ap) {
    uint32_t u0 = pack_bf16(d0, d1), u1 = pack_bf16(d2, d3);
    if (TR) { u0 = movm(u0); u1 = movm(u1); }
    stg_rlx64(ap, (u0 & ~1u) | tag, u1);
}

template <int HF>
__device__ __forceinline__ uint32_t read_mem(unsigned char* redp, int s, int kh, int w, int lane, uint32_t sb, uint32_t dly, uint32_t& sf, uint32_t& t_iss, uint32_t& t_ret) {
    const unsigned char* pg = redp + (s & 3) * 65536 + red_grp((kh * 2 + (w >> 1)) * 16 + (w & 1) * 8 + (lane >> 3));
    const uint32_t ma = (sb + O_MEM + ((w >> 1) * 4 + HF * 2) * 1024 + (lane & 7) * 128 + (((lane >> 3) ^ (lane & 7)) << 4)) ^ ((w & 1) << 6);
    const unsigned char* pa = pg + (lane & 7) * 16 + HF * 512;
    uint32_t u[8], n = 0, tref;
    const uint32_t target = (s & 4) ? 0x42A00000u : 0x41800000u;
    const unsigned char* pb = pg + (lane & 7) * 4 + 32768 + HF * 64;
    mbar_wait(sb + O_BAR + 8 * B_STAMP, s & 1);
    asm volatile("ld.shared.u32 %0, [%1];" : "=r"(tref) : "r"(sb + O_BAR + 248) : "memory");
    tref += dly;
    asm volatile("" : "+l"(pa), "+l"(pb));
    wait_gtime(tref);
    if (DBG_TIMING) t_iss = clk();
    bool redo;
#pragma unroll 1
    do {
        uint4 ra[2], rc[2]; uint32_t re[2], rf[2];
#pragma unroll
        for (int q = 0; q < 2; q++) {
            ra[q] = ldg_rlx128(pa + q * 2048); rc[q] = ldg_rlx128(pa + q * 2048 + 128);
            re[q] = ldg_rlx32(pb + q * 2048); rf[q] = ldg_rlx32(pb + q * 2048 + 32);
        }
        if (++n > SPIN_LIMIT) __trap();
        const bool bad = (orx2(ra[0].w, rc[0].w, target) | orx2(re[0], rf[0], target) | orx2(ra[1].w, rc[1].w, target) | orx2(re[1], rf[1], target)) > 0xffffu;
#pragma unroll
        for (int q = 0; q < 2; q++) {
            u[2 * q] = add_bf16x2(ra[q].x, rc[q].x);
            u[2 * q + 1] = add_bf16x2(ra[q].y, rc[q].y);
            u[4 + 2 * q] = add_bf16x2(ra[q].z, rc[q].z);
            u[4 + 2 * q + 1] = add_bf16x2(__byte_perm(ra[q].w, re[q], 0x5410), __byte_perm(rc[q].w, rf[q], 0x5410));
        }
        stsm4t(ma, u[0], u[1], u[2], u[3]);
        stsm4t(ma + 1024, u[4], u[5], u[6], u[7]);
        if (DBG_TIMING) t_ret = clk();
        redo = __any_sync(~0u, bad);
    } while (redo);
    __syncwarp();
    if (lane == 0) mbar_arrive(sb + O_BAR + 8 * B_MEM);
    fence_async_smem();
    __syncwarp();
    if (lane == 0) mbar_arrive(sb + O_BAR + 8 * B_QKW);
    return n - 1;
}

__global__ void __cluster_dims__(2, 1, 1) __launch_bounds__(512, 1)
rmt_main(const __grid_constant__ CUtensorMap tm_x, const __grid_constant__ CUtensorMap tm_wq, const __grid_constant__ CUtensorMap tm_wk,
         const __grid_constant__ CUtensorMap tm_wv, const __grid_constant__ CUtensorMap tm_wo, const bf16* __restrict__ mem0, const Tune tn) {
    extern __shared__ __align__(1024) unsigned char smem_raw[];
    const uint32_t sb = smem_u32(smem_raw);
    if ((sb & 0x3FFFF) != SM_BASE) __trap();
    const int cid = blockIdx.x >> 1, kh = blockIdx.x & 1;
    const int tpc = cid < 4 ? 62 + cid : cid - 4;
    int h, nh;
    if (tpc < 32) { h = (tpc >> 4) * 8 + (tpc & 7); nh = (tpc >> 3) & 1; }
    else if (tpc < 60) { int u = tpc - 32, r = u % 14; h = 16 + (u / 14) * 7 + r % 7; nh = r / 7; }
    else if (tpc < 62) return;
    else { h = 30 + ((tpc - 62) >> 1); nh = tpc & 1; }
    const int j = nh * 2 + kh, role = h * 4 + j;
    const int wgi = __shfl_sync(~0u, threadIdx.x >> 7, 0);
    const int w = __shfl_sync(~0u, (threadIdx.x >> 5) & 3, 0);
    const int tid = threadIdx.x & 127, lane = tid & 31;
#define OPAQUE_IDS() int tid_ = tid; asm volatile("" : "+r"(tid_)); const int tid = tid_, lane = tid_ & 31; (void)lane
    unsigned char* const redp = (unsigned char*)(((uintptr_t)g_red + 32767) & ~(uintptr_t)32767);
    const uint32_t bars = sb + O_BAR;

    if (threadIdx.x == 0) {
        const uint8_t cnts[B_COUNT] = {1, 1, 1, 1, 1, 1, 4, 4, 1, 12, 8, 4, 4, 4, 1, 1, 1, 1, 1, 1, 16, 4, 4, 4, 1};
#pragma unroll
        for (int i = 0; i < B_COUNT; i++) mbar_init(bars + 8 * i, cnts[i]);
        sts32(bars + 248, 0);
        asm volatile("fence.mbarrier_init.release.cluster;" ::: "memory");
        fence_async_smem();
        const int c0 = h * 128 + nh * 64, r0 = kh * 512;
        for (int i = 0; i < 2; i++) {
            mbar_expect_tx(bars + 8 * (B_WK0 + i), 32768);
            tma2d(sb + O_XB + i * 32768, &tm_wk, c0, r0 + i * 256, bars + 8 * (B_WK0 + i));
            mbar_expect_tx(bars + 8 * (B_WQ0 + i), 32768);
            tma2d(sb + O_WO + i * 32768, &tm_wq, c0, r0 + i * 256, bars + 8 * (B_WQ0 + i));
        }
        mbar_expect_tx(bars + 8 * B_WV, 65536);
        for (int i = 0; i < 2; i++) tma2d(sb + O_WV + i * 32768, &tm_wv, c0, r0 + i * 256, bars + 8 * B_WV);
        for (int i = 0; i < 4; i++) tma2d_prefetch(&tm_wo, j * 256 + i * 64, h * 128);
        tma4d_prefetch(&tm_x, kh * 8, (role >> 1) * 4);
    }
    __syncthreads();
    uint32_t mate;
    asm volatile("mapa.shared::cluster.u32 %0, %1, %2;" : "=r"(mate) : "r"(sb), "r"(kh ^ 1));

    if (wgi < 2) {
        asm volatile("setmaxnreg.inc.sync.aligned.u32 176;");
        uint32_t a[32][4];
        {
            const uint32_t stage = sb + (wgi == 0 ? O_WO : O_XB);
            const uint32_t ad = stage + (((lane >> 4) & 1) * 8 + (lane & 7)) * 128 + (((2 * w + ((lane >> 3) & 1)) ^ (lane & 7)) << 4);
#pragma unroll
            for (int i = 0; i < 2; i++) {
                mbar_wait(bars + 8 * (B_WQ0 + 2 * wgi + i), 0);
#pragma unroll
                for (int ks = 0; ks < 16; ks++) ldsm4t(a[i * 16 + ks], ad + (i * 16 + ks) * 2048);
            }
            __syncwarp();
            if (lane == 0) mbar_arrive(bars + 8 * (B_QDONE + wgi));
        }
        asm volatile("barrier.cluster.arrive.release.aligned;" ::: "memory");
        asm volatile("barrier.cluster.wait.acquire.aligned;" ::: "memory");
        const uint32_t frag = h * (3 * 512) + wgi * 512 + ((nh * 4 + w) * 2 + kh) * 32 + lane;
        const uint32_t mb0 = sb + O_MEM + (lane & 7) * 128 + (((lane >> 3) ^ (lane & 7)) << 4);
#pragma unroll 1
        for (int s = -RA; s < 64; s++) {
            TSI(s);
            float kp[8];
            if (s < 64 - RA) {
                float d[16];
                mbar_wait(bars + 8 * B_XFULL, (s + RA) & 1);
                if (s >= 1) mbar_wait(bars + 8 * B_OPDONE, (s - 1) & 1);
                if (X_SEQ && wgi == 1) mbar_wait(bars + 8 * B_QX, (s + RA) & 1);
                TS(6);
                wg_fence();
#pragma unroll
                for (int ks = 0; ks < 32; ks++) { if (ks == 0) wg_rs32<0>(d, a[ks], xdesc(ks)); else wg_rs32<1>(d, a[ks], xdesc(ks)); }
                wg_commit();
                if (X_SEQ && wgi == 0 && lane == 0) mbar_arrive(bars + 8 * B_QX);
                wg_wait<0>();
                TS(7);
                uint32_t sn[4];
                x_split(d, sn, kp, kh);
                if (!FLAG(0)) x_send(wgi, sn, s + RA, tid, sb, mate);
                TS(4);
            }
            if (lane == 0) mbar_arrive(bars + 8 * B_XEMPTY);
            if (s >= 0) {
                uint2* ap = &g_alpha[(s & 1) * (32 * 3 * 512) + frag];
                asm volatile("" : "+l"(ap));
                float e[2][4];
#pragma unroll
                for (int i = 0; i < 4; i++) e[0][i] = e[1][i] = 0.f;
                mbar_wait(bars + 8 * B_MEM, s & 1);
                TS(0);
#pragma unroll
                for (int ks = 0; ks < 32; ks += 2) {
                    uint32_t b[4];
                    ldsm4(b, (mb0 ^ ((ks & 2) << 5)) + (ks >> 2) * 1024);
                    mma16816(e[0], a[ks][0], a[ks][1], a[ks][2], a[ks][3], b[0], b[1]);
                    mma16816(e[1], a[ks + 1][0], a[ks + 1][1], a[ks + 1][2], a[ks + 1][3], b[2], b[3]);
                }
                TS(2);
                alpha_write<true>(e[0][0] + e[1][0], e[0][1] + e[1][1], e[0][2] + e[1][2], e[0][3] + e[1][3], ((s >> 1) & 1) ^ 1, ap);
                if (lane == 0) mbar_arrive(bars + 8 * B_QKW);
                TS(3);
            }
            if (s < 64 - RA && !FLAG(0)) {
                if (s >= 0) mbar_wait(bars + 8 * B_SDONE, s & 1);
                x_finish<true>(wgi, kp, s + RA, frag, tid, sb);
                TS(5);
            }
        }
        TSDUMP();
    } else if (wgi == 2) {
        asm volatile("setmaxnreg.dec.sync.aligned.u32 64;");
        asm volatile("barrier.cluster.arrive.release.aligned;" ::: "memory");
        if (w == 0) {
            mbar_wait(bars + 8 * B_KDONE, 0);
            if (lane == 0) {
                mbar_expect_tx(bars + 8 * B_XFULL, 32768);
                tma4d(sb + O_XB, &tm_x, kh * 8, 0, bars + 8 * B_XFULL);
            }
            mbar_wait(bars + 8 * B_QDONE, 0);
            if (lane == 0) {
                mbar_expect_tx(bars + 8 * B_WO, 65536);
#pragma unroll
                for (int i = 0; i < 4; i++) tma2d(sb + O_WO + i * 16384, &tm_wo, j * 256 + i * 64, h * 128, bars + 8 * B_WO);
            }
        }
        asm volatile("barrier.cluster.wait.acquire.aligned;" ::: "memory");
        mbar_wait(bars + 8 * B_WV, 0);
        uint32_t sf = 0;
        uint32_t tref = gtime() - 4000;
#pragma unroll 1
        for (int s = -RA; s < 64; s++) {
            TSI(s);
            OPAQUE_IDS();
            const uint32_t frag = h * (3 * 512) + 1024 + ((nh * 4 + w) * 2 + kh) * 32 + lane;
            uint2* ap = &g_alpha[(s & 1) * (32 * 3 * 512) + frag];
            asm volatile("" : "+l"(ap));
            float d[20];
            if (s >= 0) mbar_wait(bars + 8 * B_QKW, s & 1); else mbar_wait(bars + 8 * B_XFULL, (s + RA) & 1);
            TS(0);
            wg_fence();
#pragma unroll
            for (int ks = 0; ks < 32; ks++) {
                constexpr uint64_t da0 = mkdesc(SM_BASE + O_WV, 16, 1024, 1);
                if (ks == 0) wg_ss40<0>(d, da0 + ks * 128, xdesc(ks)); else wg_ss40<1>(d, da0 + ks * 128, xdesc(ks));
            }
            wg_commit();
            wg_wait<0>();
            TS(1);
            if (s >= 0) alpha_write<false>(d[16], d[17], d[18], d[19], ((s >> 1) & 1) ^ 1, ap);
            if (tid == 0 && s >= 0) asm volatile("st.relaxed.gpu.global.u32 [%0], %1;" ::"l"((uint32_t*)g_stamp + role), "r"(gtime()) : "memory");
            if (lane == 0) mbar_arrive(bars + 8 * B_XEMPTY);
            if (s == 63) break;
            uint32_t sn[4]; float kp[8];
            x_split(d, sn, kp, kh);
            TS(2);
            if (w == 0 && s < 63 - RA) {
                if (s >= 0) mbar_wait(bars + 8 * B_SRDY, s & 1);
                mbar_wait(bars + 8 * B_XEMPTY, (s + RA) & 1);
                if (lane == 0) {
                    if (FLAG(2)) mbar_arrive(bars + 8 * B_XFULL);
                    else {
                        mbar_expect_tx(bars + 8 * B_XFULL, 32768);
                        tma4d(sb + O_XB, &tm_x, kh * 8, (s + RA + 1) * 4, bars + 8 * B_XFULL);
                    }
                }
            }
            if (w == 3 && s >= 0) {
                mbar_wait(bars + 8 * B_SDONE, s & 1);
                wait_clk(clk(), tn.d_st);
                uint32_t n = 0, mx, mn;
                do {
                    const uint4 st = ldg_rlx128(&g_stamp[lane]);
                    mx = __reduce_max_sync(~0u, max(max(st.x - tref, st.y - tref), max(st.z - tref, st.w - tref)));
                    mn = __reduce_min_sync(~0u, min(min(st.x - tref, st.y - tref), min(st.z - tref, st.w - tref)));
                } while (mx >= 200000u && ++n < 64);
                tref = mx < 200000u ? tref + mx + (mx - mn > tn.spread ? tn.extra : 1) : gtime();
                if (lane == 0) { sts32(bars + 248, tref); mbar_arrive(bars + 8 * B_STAMP); }
                TSV(12, clk()); TSV(13, n); TSV(14, mx - mn);
            }
            if (s < 64 - RA && !FLAG(0)) {
                if (s >= 0) mbar_wait(bars + 8 * B_OPDONE, s & 1);
                x_send(2, sn, s + RA, tid, sb, mate);
                x_finish<false>(2, kp, s + RA, frag, tid, sb);
            }
            TS(6);
            if (s >= 0) {
                uint32_t t_iss, t_ret;
                const uint32_t n = read_mem<0>(redp, s, kh, w, lane, sb, tn.d_r0, sf, t_iss, t_ret); (void)n;
                TS(5);
                if (w == 0) { TSV(3, t_iss); TSV(4, t_ret); }
                TSV(8 + w, n);
            }
        }
        sts32(bars + 252, sf);
        TSDUMP();
    } else {
        asm volatile("setmaxnreg.dec.sync.aligned.u32 96;");
        GT(0);
        asm volatile("barrier.cluster.arrive.release.aligned;" ::: "memory");
#define RED_CLEAR(st)                                                                                           \
        {                                                                                                       \
            unsigned char* zp = redp + ((st) & 3) * 65536 + (role >> 6) * 32768 + red_grp(role & 63) + red_slot(lane >> 3) + (lane & 7) * 16; \
            const uint32_t cb = RED_F32 ? __float_as_uint(64.f * (st)) : (((st) & 4) ? 0x42800000u : 0u);       \
            const uint32_t cz = (!RED_F32 && role >= 64) ? cb : 0u;                                             \
            stg128(zp, cz, cz, cz, cb);                                                                         \
        }
#define KQ_LOAD()                                                                                          \
        {                                                                                                  \
            const uint4* bq = &g_kvq[((s & 3) * 32 + h) * (3 * 512) + w * 128 + lane];                     \
            _Pragma("unroll") for (int i = 0; i < 4; i++) kf[i] = ldg_rlx128(bq + 512 + i * 32);           \
            _Pragma("unroll") for (int u = 0; u < 2; u++) qf[u] = ldg_rlx64((const uint2*)(bq + (2 * u + nh) * 32) + kh); \
        }
        uint32_t start_target = 0;
        if (w == 0) {
            RED_CLEAR(0); RED_CLEAR(1);
            fence_gpu();
            __syncwarp();
            if (lane == 0) start_target = (atomicAdd(&g_start, 1) & ~127u) + 128;
            start_target = __shfl_sync(~0u, start_target, 0);
        }
        mbar_wait(bars + 8 * B_KDONE, 0);
        {
            const int kb0 = (w & 1) * 4 + (w >> 1) * 2;
#pragma unroll
            for (int q = 0; q < 4; q++) {
                const int row = (lane >> 3) + (q & 1) * 4, ch = lane & 7, kb = kb0 + (q >> 1);
                const uint4 v = *(const uint4*)(mem0 + row * 1024 + kh * 512 + kb * 64 + ch * 8);
                sts128u(sb + O_MEM + kb * 1024 + row * 128 + ((ch ^ row) << 4), v);
            }
            fence_async_smem();
            __syncwarp();
            if (lane < 2) { mbar_arrive(bars + 8 * B_MEM); mbar_arrive(bars + 8 * B_QKW); }
        }
        asm volatile("barrier.cluster.wait.acquire.aligned;" ::: "memory");
        if (w == 0) { uint32_t n = 0; while (__any_sync(~0u, (int)(ld_acquire(&g_start) - start_target) < 0)) { if (++n > SPIN_LIMIT) __trap(); } }
        mbar_wait(bars + 8 * B_WO, 0);
        GT(1);
        uint32_t sf = 0;
        uint4 kf[4]; uint2 qf[2];
        { const int s = 0; KQ_LOAD(); }
#pragma unroll 1
        for (int s = 0; s < 64; s++) {
            TSI(s);
            OPAQUE_IDS();
            const uint4* bp = &g_kvq[((s & 3) * 32 + h) * (3 * 512) + w * 128 + lane];
            const uint32_t tg = ((s >> 2) & 1) ^ 1;
            {
                uint32_t n = 0;
                while (__builtin_expect(__any_sync(~0u, or3(orx2(kf[0].x, kf[1].x, tg), orx2(kf[2].x, kf[3].x, tg), orx2(qf[0].x, qf[1].x, tg)) & 1) && !FLAG(0), 0)) {
                    KQ_LOAD();
                    if (++n > SPIN_LIMIT) __trap();
                }
                if (w == 0) TSV(22, n);
            }
            if (w == 0 && s < 62) RED_CLEAR(s + 2);
            const uint32_t tag = ((s >> 1) & 1) ^ 1;
            const uint2* ap = &g_alpha[((s & 1) * 32 + h) * (3 * 512) + w * 128 + lane];
            uint32_t sw = sb + O_S + w * 2560 + lane * 16, sr = sb + O_S + tid * 4;
            uint32_t pw = sb + O_P + ((lane >> 1) & 1) * 704 + (2 * w + (lane >> 4)) * 16 + ((lane >> 2) & 3) * 4 + (lane & 1) * 2;
            int lim = (lane & 2) ? 8 * j + 2 * w + (lane >> 4) - 2 * ((lane >> 2) & 3) - (lane & 1) : 64;
            uint32_t pr = sb + O_P + lane * 16, oa = sb + O_O + w * 512 + lane * 4;
            asm volatile("" : "+r"(sw), "+r"(sr), "+r"(pw), "+r"(lim), "+r"(pr), "+r"(oa), "+l"(ap), "+l"(bp));
            TS(0);
            mbar_wait(bars + 8 * B_QKW, s & 1);
            TS(1);
            const uint32_t tq = clk();
            wait_clk(tq, tn.d_alpha);
            uint4 vf[4]; uint2 va[4];
#define VF_LOAD() _Pragma("unroll") for (int i = 0; i < 4; i++) vf[i] = ldg_rlx128(bp + 1024 + i * 32);
#define VA_LOAD() _Pragma("unroll") for (int i = 0; i < 4; i++) va[i] = ldg_rlx64(ap + 1024 + i * 32);
            {
                uint32_t nr = 0;
                bool redo;
#pragma unroll 1
                do {
                    uint2 qa[4], ka[4];
#pragma unroll
                    for (int i = 0; i < 4; i++) { qa[i] = ldg_rlx64(ap + i * 32); ka[i] = ldg_rlx64(ap + 512 + i * 32); }
                    if (++nr > SPIN_LIMIT) __trap();
                    float sa[5][4];
#pragma unroll
                    for (int n = 0; n < 5; n++) sa[n][0] = sa[n][1] = sa[n][2] = sa[n][3] = 0.f;
#pragma unroll
                    for (int u = 0; u < 2; u++) {
                        const uint32_t q0 = add_bf16x2(qa[2 * u].x, qa[2 * u + 1].x), q1 = add_bf16x2(qa[2 * u].y, qa[2 * u + 1].y);
                        const uint32_t k0 = add_bf16x2(ka[2 * u].x, ka[2 * u + 1].x), k1 = add_bf16x2(ka[2 * u].y, ka[2 * u + 1].y);
                        mma16816(sa[1], q0, qf[u].x, q1, qf[u].y, kf[2 * u].x, kf[2 * u].y);
                        mma16816(sa[2], q0, qf[u].x, q1, qf[u].y, kf[2 * u].z, kf[2 * u].w);
                        mma16816(sa[3], q0, qf[u].x, q1, qf[u].y, kf[2 * u + 1].x, kf[2 * u + 1].y);
                        mma16816(sa[4], q0, qf[u].x, q1, qf[u].y, kf[2 * u + 1].z, kf[2 * u + 1].w);
                        mma16816(sa[0], q0, qf[u].x, q1, qf[u].y, k0, k1);
                    }
                    redo = __any_sync(~0u, or3(orx2(qa[0].x, ka[0].x, tag), orx2(qa[1].x, ka[1].x, tag),
                                               orx(orx(orx2(qa[2].x, ka[2].x, tag), qa[3].x, tag), ka[3].x, tag)) & 1);
#pragma unroll
                    for (int n = 1; n <= 5; n++) sts128(sw + (n % 5) * 512, sa[n % 5][0], sa[n % 5][1], sa[n % 5][2], sa[n % 5][3]);
                } while (redo);
                if (w == 0) TSV(20, nr - 1);
            }
            VF_LOAD();
            TS(2);
            bar_sync(1, 128);
            if (AV_POS == 0) { VA_LOAD(); SCHED_FENCE(); }
            float sc[5];
            {
                float x[4][5];
#pragma unroll
                for (int q = 0; q < 4; q++)
#pragma unroll
                    for (int n = 0; n < 5; n++) asm volatile("ld.shared.f32 %0, [%1];" : "=f"(x[q][n]) : "r"(sr + q * 2560 + n * 512) : "memory");
                if (AV_POS == 2) wait_clk(tq, tn.d_v);
                if (AV_POS >= 1) { VA_LOAD(); SCHED_FENCE(); }
#pragma unroll
                for (int n = 0; n < 5; n++) sc[n] = (x[0][n] + x[1][n]) + (x[2][n] + x[3][n]);
            }
            if (lane == 0) mbar_arrive(bars + 8 * B_SDONE);
            TS(15);
#pragma unroll
            for (int n = 1; n < 5; n++) if (8 * (n - 1) > lim) sc[n] = MASK_VAL;
            float m = fmaxf(fmaxf(fmaxf(sc[0], sc[1]), fmaxf(sc[2], sc[3])), sc[4]);
            m = fmaxf(m, __shfl_xor_sync(~0u, m, 1));
            m = fmaxf(m, __shfl_xor_sync(~0u, m, 4));
            m = fmaxf(m, __shfl_xor_sync(~0u, m, 8));
            m *= -SM_SCALE_LOG2;
#pragma unroll
            for (int n = 0; n < 5; n++) {
                const uint32_t pv = pack_bf16(ex2(fmaf(sc[n], SM_SCALE_LOG2, m)), 0.f);
                asm volatile("st.shared.u16 [%0], %1;" ::"r"(pw + n * 128), "h"((uint16_t)pv) : "memory");
            }
            bar_sync(1, 128);
            TS(3);
            uint32_t pf[4], p0, px[4], px0;
            ldsm4(pf, pr + 128);
            asm volatile("ld.shared.u32 %0, [%1];" : "=r"(p0) : "r"(oa - w * 512 + (O_P - O_O)) : "memory");
            ldsm4(px, pr + 128 + 704);
            asm volatile("ld.shared.u32 %0, [%1];" : "=r"(px0) : "r"(oa - w * 512 + (O_P - O_O) + 704) : "memory");
            if (lane == 0) mbar_arrive(bars + 8 * B_SRDY);
            SCHED_FENCE();
            uint32_t vm[4];
#define PV(o, i0, i1, pf, p0)                                                                                                    \
            {                                                                                                                \
                float sm[4] = {0.f, 0.f, 0.f, 0.f};                                                                          \
                _Pragma("unroll") for (int u = 0; u < 2; u++) o[u][0] = o[u][1] = o[u][2] = o[u][3] = 0.f;                   \
                _Pragma("unroll") for (int c = 0; c < 2; c++) {                                                              \
                    mma16816(sm, 0x3f803f80u, 0x3f803f80u, 0x3f803f80u, 0x3f803f80u, pf[2 * c], pf[2 * c + 1]);              \
                    _Pragma("unroll") for (int u = 0; u < 2; u++)                                                            \
                        mma16816(o[u], vf[2 * u + c].x, vf[2 * u + c].y, vf[2 * u + c].z, vf[2 * u + c].w, pf[2 * c], pf[2 * c + 1]); \
                }                                                                                                            \
                mma1688(sm, 0x3f803f80u, 0x3f803f80u, p0);                                                                   \
                _Pragma("unroll") for (int u = 0; u < 2; u++) mma1688(o[u], vm[2 * u], vm[2 * u + 1], p0);                   \
                i0 = rcp(sm[0]); i1 = rcp(sm[1]);                                                                            \
            }
            float o[2][4], i0, i1;
            unsigned char* pa; unsigned char* pb;
            {
                unsigned char* const pg = redp + (s & 3) * 65536 + red_grp(j * 16 + (tid >> 3));
                pa = pg + (lane & 7) * 16 + (RED_F32 ? 0 : (h & 1) * 128);
                pb = pg + 32768 + (RED_F32 ? (lane & 7) * 16 : (lane & 7) * 4 + (h & 1) * 32);
            }
#define V_BAD() __any_sync(~0u, or3(orx2(va[0].x, va[1].x, tag), orx2(va[2].x, va[3].x, tag),  \
                                    FLAG(0) ? 0 : orx(orx(orx2(vf[0].x, vf[1].x, tg), vf[2].x, tg), vf[3].x, tg)) & 1)
#define O_MEMROWS()                                                                             \
            _Pragma("unroll") for (int u = 0; u < 2; u++) {                                     \
                vm[2 * u] = add_bf16x2(va[2 * u].x, va[2 * u + 1].x); vm[2 * u + 1] = add_bf16x2(va[2 * u].y, va[2 * u + 1].y); } \
            PV(o, i0, i1, pf, p0);                                                              \
            sts32(oa, pack_bf16(o[0][0], o[0][1]));                                             \
            sts32(oa + 128, pack_bf16(o[0][2], o[0][3]));                                       \
            sts32(oa + 256, pack_bf16(o[1][0], o[1][1]));                                       \
            sts32(oa + 384, pack_bf16(o[1][2], o[1][3]));
            {
                const bool redo = V_BAD();
                O_MEMROWS();
                uint32_t nr = 0;
                if (__builtin_expect(redo, 0)) {
                    do { VA_LOAD(); VF_LOAD(); if (++nr > SPIN_LIMIT) __trap(); } while (V_BAD());
                    O_MEMROWS();
                }
                if (w == 0) TSV(21, nr);
            }
            TS(4);
            SCHED_FENCE();
            float ox[2][4], ix0, ix1;
            PV(ox, ix0, ix1, px, px0);
            fence_async_smem();
            asm volatile("" : "+l"(pa), "+l"(pb));
            bar_sync(1, 128);
            if (s == 0) GT(2);
            TS(5);
            if (s < 63) {
            float cc[4][4];
#define OP_ISSUE(t0, t1)                                                                                   \
            wg_fence();                                                                                    \
            _Pragma("unroll") for (int ks = 0; ks < 8; ks++)                                               \
                _Pragma("unroll") for (int t = t0; t < t1; t++) {                                          \
                    constexpr uint64_t da0 = mkdesc(SM_BASE + O_WO, 16, 1024, 1), db0 = mkdesc(SM_BASE + O_O, 128, 128, 0); \
                    if (ks == 0) wg_ss8<0>(cc[t], da0 + t * 1024, db0); else wg_ss8<1>(cc[t], da0 + t * 1024 + ks * 128, db0 + ks * 16); \
                }                                                                                          \
            wg_commit();
            if (!OP_SPLIT) {
                OP_ISSUE(0, 4);
                if (KQ_POS == 0) { const int s1 = s + 1; { const int s = s1; KQ_LOAD(); } SCHED_FENCE(); }
                wg_wait<0>();
            }
#pragma unroll
            for (int hf = 0; hf < 2; hf++) {
                if (OP_SPLIT) { OP_ISSUE(2 * hf, 2 * hf + 2); wg_wait<0>(); }
                float (&ca)[4] = cc[2 * hf]; float (&cb)[4] = cc[2 * hf + 1];
                asm volatile("red.relaxed.gpu.global.add.noftz.v4.bf16x2 [%0], {%1,%2,%3,%4};" ::"l"(pa + hf * 512), "r"(pack_bf16(ca[0] * i0, ca[1] * i1)),
                             "r"(pack_bf16(ca[2] * i0, ca[3] * i1)), "r"(pack_bf16(cb[0] * i0, cb[1] * i1)), "r"(pack_bf16(cb[2] * i0, 1.f)) : "memory");
                asm volatile("red.relaxed.gpu.global.add.noftz.bf16x2 [%0], %1;" ::"l"(pb + hf * 64), "r"(pack_bf16(cb[3] * i1, 1.f)) : "memory");
                if (OP_SPLIT || hf == 1) SCHED_FENCE();
                TSV(6 + hf, clk());
            }
            if (lane == 0) mbar_arrive(bars + 8 * B_OPDONE);
            }
            if (!FLAG(3)) {
                const uint32_t xo = sb + O_XO + w * 512;
                stsm4t(xo + (lane & 7) * 64 + (((lane >> 3) ^ ((lane >> 1) & 3)) << 4), pack_bf16(ox[0][0] * ix0, ox[0][1] * ix1),
                       pack_bf16(ox[0][2] * ix0, ox[0][3] * ix1), pack_bf16(ox[1][0] * ix0, ox[1][1] * ix1), pack_bf16(ox[1][2] * ix0, ox[1][3] * ix1));
                __syncwarp();
                const uint4 ov = lds128u(xo + (lane >> 2) * 64 + (((lane & 3) ^ ((lane >> 3) & 3)) << 4));
                stg128(&g_ox[(size_t)(s * 32 + j * 8 + (lane >> 2)) * 4096 + h * 128 + w * 32 + (lane & 3) * 8], ov.x, ov.y, ov.z, ov.w);
            }
            TS(8);
            if (s == 63) { GT(3); break; }
            if (KQ_POS == 1) { const int s1 = s + 1; { const int s = s1; KQ_LOAD(); } }
            {
                uint32_t t_iss, t_ret;
                const uint32_t n = read_mem<1>(redp, s, kh, w, lane, sb, tn.d_r1, sf, t_iss, t_ret); (void)n;
                TS(11);
                if (w == 0) { TSV(9, t_iss); TSV(10, t_ret); }
                TSV(16 + w, n);
            }
            if (KQ_POS == 2) { const int s1 = s + 1; { const int s = s1; KQ_LOAD(); } }
        }
        sts32(bars + 252, sf);
        TSDUMP();
    }
}

constexpr int G_ST = 6;
constexpr uint32_t G_SMEM = G_ST * 32768 + 256;
#define F16(d, o) F4(d, o), F4(d, o + 4), F4(d, o + 8), F4(d, o + 12)
__device__ __forceinline__ void wg_ss128(float (&d)[64], uint64_t da, uint64_t db, int sc) {
    asm volatile("{\n.reg .pred p;\nsetp.ne.b32 p, %66, 0;\nwgmma.mma_async.sync.aligned.m64n128k16.f32.bf16.bf16 "
                 "{%0,%1,%2,%3,%4,%5,%6,%7,%8,%9,%10,%11,%12,%13,%14,%15,%16,%17,%18,%19,%20,%21,%22,%23,%24,%25,%26,%27,%28,%29,%30,%31,"
                 "%32,%33,%34,%35,%36,%37,%38,%39,%40,%41,%42,%43,%44,%45,%46,%47,%48,%49,%50,%51,%52,%53,%54,%55,%56,%57,%58,%59,%60,%61,%62,%63}, "
                 "%64, %65, p, 1, 1, 0, 1;\n}"
                 : F16(d, 0), F16(d, 16), F16(d, 32), F16(d, 48) : "l"(da), "l"(db), "r"(sc));
}

__global__ void __launch_bounds__(384, 1)
out_gemm(const __grid_constant__ CUtensorMap tm_o, const __grid_constant__ CUtensorMap tm_w, bf16* __restrict__ out) {
    extern __shared__ __align__(1024) unsigned char smem_raw[];
    const uint32_t sb = smem_u32(smem_raw), bars = sb + G_ST * 32768;
    const int m0 = (blockIdx.x >> 3) * 128, n0 = (blockIdx.x & 7) * 128;
    const int wgi = __shfl_sync(~0u, threadIdx.x >> 7, 0), tid = threadIdx.x & 127;
    if (threadIdx.x == 0) {
        for (int i = 0; i < G_ST; i++) { mbar_init(bars + 8 * i, 1); mbar_init(bars + 8 * (G_ST + i), 8); }
        fence_async_smem();
    }
    __syncthreads();
    if (wgi == 0) GT(4);
    if (wgi == 2) {
        if (tid == 0) {
            for (int kt = 0; kt < 64; kt++) {
                const int st = kt % G_ST;
                if (kt >= G_ST) mbar_wait(bars + 8 * (G_ST + st), (kt / G_ST - 1) & 1);
                mbar_expect_tx(bars + 8 * st, 32768);
                tma2d(sb + st * 32768, &tm_o, kt * 64, m0, bars + 8 * st);
                tma2d(sb + st * 32768 + 16384, &tm_w, n0, kt * 64, bars + 8 * st);
                tma2d(sb + st * 32768 + 24576, &tm_w, n0 + 64, kt * 64, bars + 8 * st);
            }
        }
    } else {
        float d[64];
        int st = 0, ph = 0;
#pragma unroll 1
        for (int kt = 0; kt < 64; kt++) {
            mbar_wait(bars + 8 * st, ph);
            const uint64_t da = mkdesc(sb + st * 32768 + wgi * 8192, 16, 1024, 1), db = mkdesc(sb + st * 32768 + 16384, 8192, 1024, 1);
            wg_fence();
#pragma unroll
            for (int k = 0; k < 4; k++) wg_ss128(d, da + k * 2, db + k * 128, kt | k);
            wg_commit();
            if (kt > 0) {
                wg_wait<1>();
                if ((tid & 31) == 0) mbar_arrive(bars + 8 * (G_ST + (st == 0 ? G_ST - 1 : st - 1)));
            }
            if (++st == G_ST) { st = 0; ph ^= 1; }
        }
        wg_wait<0>();
        const int row = m0 + wgi * 64 + (tid >> 5) * 16 + ((tid & 31) >> 2);
        bf16* op = out + (size_t)row * 2048 + 1024 + n0 + (tid & 3) * 2;
#pragma unroll
        for (int i = 0; i < 16; i++) {
            *(uint32_t*)(op + i * 8) = pack_bf16(d[4 * i], d[4 * i + 1]);
            *(uint32_t*)(op + 8 * 2048 + i * 8) = pack_bf16(d[4 * i + 2], d[4 * i + 3]);
        }
        if (wgi == 0) GT(5);
    }
}

typedef CUresult (*EncodeFn)(CUtensorMap*, CUtensorMapDataType, cuuint32_t, void*, const cuuint64_t*, const cuuint64_t*,
                             const cuuint32_t*, const cuuint32_t*, CUtensorMapInterleave, CUtensorMapSwizzle,
                             CUtensorMapL2promotion, CUtensorMapFloatOOBfill);

static void make_map(EncodeFn fn, CUtensorMap* m, const void* p, uint64_t cols, uint64_t rows, uint32_t bc, uint32_t br) {
    cuuint64_t dims[2] = {cols, rows}, strides[1] = {cols * 2};
    cuuint32_t box[2] = {bc, br}, es[2] = {1, 1};
    fn(m, CU_TENSOR_MAP_DATA_TYPE_BFLOAT16, 2, (void*)p, dims, strides, box, es, CU_TENSOR_MAP_INTERLEAVE_NONE,
       CU_TENSOR_MAP_SWIZZLE_128B, CU_TENSOR_MAP_L2_PROMOTION_L2_128B, CU_TENSOR_MAP_FLOAT_OOB_FILL_NONE);
}

static Tune h_tune = {350, 1150, 1150, 0, 100, 1200, 400, 300};

extern "C" void kernel_launch(void* const* d_in, const int* in_sizes, int n_in, void* d_out, int out_size) {
    static bool init = false;
    static CUtensorMap tm_x, tm_wq, tm_wk, tm_wv, tm_wo, tm_o, tm_wo2;
    if (!init) {
        void* fp = nullptr; cudaDriverEntryPointQueryResult qr;
        cudaGetDriverEntryPoint("cuTensorMapEncodeTiled", &fp, cudaEnableDefault, &qr);
        EncodeFn fn = (EncodeFn)fp;
        void* ox = nullptr; cudaGetSymbolAddress(&ox, g_ox);
        {
            cuuint64_t dims[4] = {64, 8, 16, 256}, strides[3] = {2048, 128, 16384};
            cuuint32_t box[4] = {64, 8, 8, 4}, es[4] = {1, 1, 1, 1};
            fn(&tm_x, CU_TENSOR_MAP_DATA_TYPE_BFLOAT16, 4, d_in[3], dims, strides, box, es, CU_TENSOR_MAP_INTERLEAVE_NONE,
               CU_TENSOR_MAP_SWIZZLE_128B, CU_TENSOR_MAP_L2_PROMOTION_L2_128B, CU_TENSOR_MAP_FLOAT_OOB_FILL_NONE);
        }
        make_map(fn, &tm_wq, d_in[5], 4096, 1024, 64, 256);
        make_map(fn, &tm_wk, d_in[6], 4096, 1024, 64, 256);
        make_map(fn, &tm_wv, d_in[7], 4096, 1024, 64, 256);
        make_map(fn, &tm_wo, d_in[8], 1024, 4096, 64, 128);
        make_map(fn, &tm_o, ox, 4096, 2048, 64, 128);
        make_map(fn, &tm_wo2, d_in[8], 1024, 4096, 64, 64);
        cudaFuncSetAttribute(rmt_main, cudaFuncAttributeMaxDynamicSharedMemorySize, MAIN_SMEM);
        cudaFuncSetAttribute(out_gemm, cudaFuncAttributeMaxDynamicSharedMemorySize, G_SMEM);
        init = true;
    }
    rmt_main<<<132, 512, MAIN_SMEM>>>(tm_x, tm_wq, tm_wk, tm_wv, tm_wo, (const bf16*)d_in[4], h_tune);
    out_gemm<<<128, 384, G_SMEM>>>(tm_o, tm_wo2, (bf16*)d_out);
}
```

```cpp
#include <cuda_runtime.h>
#include <cuda_bf16.h>
#include <cuda.h>
#include <stdint.h>

typedef __nv_bfloat16 bf16;

#define DBG_TIMING 0

#define SPIN_LIMIT (1u << 22)

__device__ __forceinline__ uint32_t smem_u32(const void* p) { return (uint32_t)__cvta_generic_to_shared(p); }
__device__ __forceinline__ uint32_t clk() { uint32_t c; asm volatile("mov.u32 %0, %%clock;" : "=r"(c)::"memory"); return c; }
#define SCHED_FENCE() sf ^= (uint32_t)clock64()
__device__ __forceinline__ uint32_t gtime() { uint32_t c; asm volatile("mov.u32 %0, %%globaltimer_lo;" : "=r"(c)::"memory"); return c; }
__device__ __forceinline__ void wait_clk(uint32_t t0, uint32_t d) {
    asm volatile("{\n.reg .pred p;\n.reg .s32 t;\n.reg .b64 c;\nWL:\nmov.u64 c, %%clock64;\ncvt.u32.u64 t, c;\nsub.s32 t, t, %0;\nsetp.lt.s32 p, t, 0;\n@p bra.uni WL;\n}" ::"r"(t0 + d) : "memory");
}
__device__ __forceinline__ void wait_gtime(uint32_t t1) {
    asm volatile("{\n.reg .pred p;\n.reg .s32 t;\n.reg .b64 c;\nWL:\nmov.u64 c, %%globaltimer;\ncvt.u32.u64 t, c;\nsub.s32 t, t, %0;\nsetp.lt.s32 p, t, 0;\n@p bra.uni WL;\n}" ::"r"(t1) : "memory");
}

__device__ __forceinline__ void mbar_init(uint32_t bar, uint32_t cnt) {
    asm volatile("mbarrier.init.shared::cta.b64 [%0], %1;" ::"r"(bar), "r"(cnt) : "memory");
}
__device__ __forceinline__ void mbar_arrive(uint32_t bar) {
    asm volatile("mbarrier.arrive.shared::cta.b64 _, [%0];" ::"r"(bar) : "memory");
}
__device__ __forceinline__ void mbar_expect_tx(uint32_t bar, uint32_t bytes) {
    asm volatile("mbarrier.arrive.expect_tx.shared::cta.b64 _, [%0], %1;" ::"r"(bar), "r"(bytes) : "memory");
}
__device__ __forceinline__ void mbar_wait(uint32_t bar, uint32_t parity) {
    asm volatile(
        "{\n.reg .pred p, q;\n.reg .u32 n;\nmov.u32 n, 0;\n"
        "WL:\nmbarrier.try_wait.parity.shared::cta.b64 p, [%0], %1;\n"
        "add.u32 n, n, 1;\nsetp.gt.u32 q, n, %2;\n@q trap;\n@!p bra.uni WL;\n}" ::"r"(bar), "r"(parity), "n"(SPIN_LIMIT) : "memory");
}
__device__ __forceinline__ void mbar_wait_cluster(uint32_t bar, uint32_t parity) {
    asm volatile(
        "{\n.reg .pred p, q;\n.reg .u32 n;\nmov.u32 n, 0;\n"
        "WL:\nmbarrier.try_wait.parity.acquire.cluster.shared::cta.b64 p, [%0], %1;\n"
        "add.u32 n, n, 1;\nsetp.gt.u32 q, n, %2;\n@q trap;\n@!p bra.uni WL;\n}" ::"r"(bar), "r"(parity), "n"(SPIN_LIMIT) : "memory");
}
__device__ __forceinline__ void tma2d(uint32_t dst, const CUtensorMap* m, int c0, int c1, uint32_t bar) {
    asm volatile("cp.async.bulk.tensor.2d.shared::cluster.global.mbarrier::complete_tx::bytes [%0], [%1, {%3, %4}], [%2];"
                 ::"r"(dst), "l"(m), "r"(bar), "r"(c0), "r"(c1) : "memory");
}
__device__ __forceinline__ void tma4d(uint32_t dst, const CUtensorMap* m, int c2, int c3, uint32_t bar) {
    asm volatile("cp.async.bulk.tensor.4d.shared::cluster.global.mbarrier::complete_tx::bytes [%0], [%1, {%5, %5, %3, %4}], [%2];"
                 ::"r"(dst), "l"(m), "r"(bar), "r"(c2), "r"(c3), "r"(0) : "memory");
}
__device__ __forceinline__ void bulk_g2s(uint32_t dst, const void* src, uint32_t bytes, uint32_t bar) {
    asm volatile("cp.async.bulk.shared::cluster.global.mbarrier::complete_tx::bytes [%0], [%1], %2, [%3];"
                 ::"r"(dst), "l"(src), "r"(bytes), "r"(bar) : "memory");
}
__device__ __forceinline__ void tma4d_prefetch(const CUtensorMap* m, int c2, int c3) {
    asm volatile("cp.async.bulk.prefetch.tensor.4d.L2.global [%0, {%3, %3, %1, %2}];" ::"l"(m), "r"(c2), "r"(c3), "r"(0) : "memory");
}
__device__ __forceinline__ void tma2d_prefetch(const CUtensorMap* m, int c0, int c1) {
    asm volatile("cp.async.bulk.prefetch.tensor.2d.L2.global [%0, {%1, %2}];" ::"l"(m), "r"(c0), "r"(c1) : "memory");
}
__device__ __forceinline__ void fence_async_smem() { asm volatile("fence.proxy.async.shared::cta;" ::: "memory"); }
__device__ __forceinline__ void fence_gpu() { asm volatile("fence.acq_rel.gpu;" ::: "memory"); }
__device__ __forceinline__ float rcp(float x) { float r; asm("rcp.approx.ftz.f32 %0, %1;" : "=f"(r) : "f"(x)); return r; }
__device__ __forceinline__ void bar_sync(int id, int n) { asm volatile("bar.sync %0, %1;" ::"r"(id), "r"(n) : "memory"); }

__device__ __forceinline__ bool bar_or(int id, int n, uint32_t x) {
    uint32_t r;
    asm volatile("{\n.reg .pred p, q;\n.reg .b32 t;\nand.b32 t, %3, 1;\nsetp.ne.u32 p, t, 0;\nbar.red.or.pred q, %1, %2, p;\nselp.u32 %0, 1, 0, q;\n}"
                 : "=r"(r) : "r"(id), "r"(n), "r"(x) : "memory");
    return __any_sync(~0u, r);
}
__device__ __forceinline__ uint32_t or3(uint32_t a, uint32_t b, uint32_t c) {
    uint32_t r; asm("lop3.b32 %0, %1, %2, %3, 0xFE;" : "=r"(r) : "r"(a), "r"(b), "r"(c)); return r;
}
__device__ __forceinline__ uint32_t pack_bf16(float lo, float hi) {
    uint32_t r; asm("cvt.rn.bf16x2.f32 %0, %1, %2;" : "=r"(r) : "f"(hi), "f"(lo)); return r;
}
__device__ __forceinline__ uint32_t add_bf16x2(uint32_t a, uint32_t b) {
    uint32_t r; asm volatile("add.rn.bf16x2 %0, %1, %2;" : "=r"(r) : "r"(a), "r"(b)); return r;
}
__device__ __forceinline__ uint32_t movm(uint32_t a) {
    uint32_t r; asm volatile("movmatrix.sync.aligned.m8n8.trans.b16 %0, %1;" : "=r"(r) : "r"(a)); return r;
}
__device__ __forceinline__ uint32_t orx(uint32_t acc, uint32_t a, uint32_t t) {
    uint32_t r; asm("lop3.b32 %0, %1, %2, %3, 0xF6;" : "=r"(r) : "r"(acc), "r"(a), "r"(t)); return r;
}
__device__ __forceinline__ uint32_t orx2(uint32_t a, uint32_t b, uint32_t t) {
    uint32_t r; asm("lop3.b32 %0, %1, %2, %3, 0x7E;" : "=r"(r) : "r"(a), "r"(b), "r"(t)); return r;
}
__device__ __forceinline__ float ex2(float x) { float r; asm("ex2.approx.ftz.f32 %0, %1;" : "=f"(r) : "f"(x)); return r; }
__device__ __forceinline__ void ldsm4t(uint32_t (&r)[4], uint32_t a) {
    asm volatile("ldmatrix.sync.aligned.m8n8.x4.trans.shared.b16 {%0,%1,%2,%3}, [%4];"
                 : "=r"(r[0]), "=r"(r[1]), "=r"(r[2]), "=r"(r[3]) : "r"(a) : "memory");
}
__device__ __forceinline__ void ldsm4(uint32_t (&r)[4], uint32_t a) {
    asm volatile("ldmatrix.sync.aligned.m8n8.x4.shared.b16 {%0,%1,%2,%3}, [%4];"
                 : "=r"(r[0]), "=r"(r[1]), "=r"(r[2]), "=r"(r[3]) : "r"(a) : "memory");
}
__device__ __forceinline__ void stsm4t(uint32_t a, uint32_t r0, uint32_t r1, uint32_t r2, uint32_t r3) {
    asm volatile("stmatrix.sync.aligned.m8n8.x4.trans.shared.b16 [%0], {%1,%2,%3,%4};"
                 ::"r"(a), "r"(r0), "r"(r1), "r"(r2), "r"(r3) : "memory");
}
__device__ __forceinline__ void stsm4(uint32_t a, uint32_t r0, uint32_t r1, uint32_t r2, uint32_t r3) {
    asm volatile("stmatrix.sync.aligned.m8n8.x4.shared.b16 [%0], {%1,%2,%3,%4};"
                 ::"r"(a), "r"(r0), "r"(r1), "r"(r2), "r"(r3) : "memory");
}
__device__ __forceinline__ void mma16816(float* c, uint32_t a0, uint32_t a1, uint32_t a2, uint32_t a3, uint32_t b0, uint32_t b1) {
    asm volatile("mma.sync.aligned.m16n8k16.row.col.f32.bf16.bf16.f32 {%0,%1,%2,%3}, {%4,%5,%6,%7}, {%8,%9}, {%0,%1,%2,%3};"
                 : "+f"(c[0]), "+f"(c[1]), "+f"(c[2]), "+f"(c[3]) : "r"(a0), "r"(a1), "r"(a2), "r"(a3), "r"(b0), "r"(b1));
}
__device__ __forceinline__ void mma1688(float* c, uint32_t a0, uint32_t a1, uint32_t b0) {
    asm volatile("mma.sync.aligned.m16n8k8.row.col.f32.bf16.bf16.f32 {%0,%1,%2,%3}, {%4,%5}, {%6}, {%0,%1,%2,%3};"
                 : "+f"(c[0]), "+f"(c[1]), "+f"(c[2]), "+f"(c[3]) : "r"(a0), "r"(a1), "r"(b0));
}
__device__ __forceinline__ void sts128(uint32_t a, float x, float y, float z, float w) {
    asm volatile("st.shared.v4.f32 [%0], {%1,%2,%3,%4};" ::"r"(a), "f"(x), "f"(y), "f"(z), "f"(w) : "memory");
}
__device__ __forceinline__ void sts64(uint32_t a, float x, float y) {
    asm volatile("st.shared.v2.f32 [%0], {%1,%2};" ::"r"(a), "f"(x), "f"(y) : "memory");
}
__device__ __forceinline__ void sts32(uint32_t a, uint32_t x) { asm volatile("st.shared.b32 [%0], %1;" ::"r"(a), "r"(x) : "memory"); }
__device__ __forceinline__ void sts128u(uint32_t a, uint4 v) {
    asm volatile("st.shared.v4.b32 [%0], {%1,%2,%3,%4};" ::"r"(a), "r"(v.x), "r"(v.y), "r"(v.z), "r"(v.w) : "memory");
}
__device__ __forceinline__ float4 lds128(uint32_t a) {
    float4 v; asm volatile("ld.shared.v4.f32 {%0,%1,%2,%3}, [%4];" : "=f"(v.x), "=f"(v.y), "=f"(v.z), "=f"(v.w) : "r"(a) : "memory"); return v;
}
__device__ __forceinline__ uint4 lds128u(uint32_t a) {
    uint4 v; asm volatile("ld.shared.v4.b32 {%0,%1,%2,%3}, [%4];" : "=r"(v.x), "=r"(v.y), "=r"(v.z), "=r"(v.w) : "r"(a) : "memory"); return v;
}
__device__ __forceinline__ uint2 lds64u(uint32_t a) {
    uint2 v; asm volatile("ld.shared.v2.b32 {%0,%1}, [%2];" : "=r"(v.x), "=r"(v.y) : "r"(a) : "memory"); return v;
}
__device__ __forceinline__ float2 lds64(uint32_t a) {
    float2 v; asm volatile("ld.shared.v2.f32 {%0,%1}, [%2];" : "=f"(v.x), "=f"(v.y) : "r"(a) : "memory"); return v;
}
__device__ __forceinline__ uint2 ldg_rlx64(const void* p) {
    uint2 v; asm volatile("ld.relaxed.gpu.global.v2.b32 {%0,%1}, [%2];" : "=r"(v.x), "=r"(v.y) : "l"(p) : "memory"); return v;
}
__device__ __forceinline__ uint4 ldg_rlx128(const void* p) {
    uint4 v; asm volatile("ld.relaxed.gpu.global.v4.b32 {%0,%1,%2,%3}, [%4];" : "=r"(v.x), "=r"(v.y), "=r"(v.z), "=r"(v.w) : "l"(p) : "memory"); return v;
}
__device__ __forceinline__ void stg_rlx64(void* p, uint32_t x, uint32_t y) {
    asm volatile("st.relaxed.gpu.global.v2.b32 [%0], {%1,%2};" ::"l"(p), "r"(x), "r"(y) : "memory");
}
__device__ __forceinline__ void stg_rlx128(void* p, uint32_t x, uint32_t y, uint32_t z, uint32_t w) {
    asm volatile("st.relaxed.gpu.global.v4.b32 [%0], {%1,%2,%3,%4};" ::"l"(p), "r"(x), "r"(y), "r"(z), "r"(w) : "memory");
}
__device__ __forceinline__ uint32_t ldg_rlx32(const void* p) {
    uint32_t v; asm volatile("ld.relaxed.gpu.global.b32 %0, [%1];" : "=r"(v) : "l"(p) : "memory"); return v;
}
__device__ __forceinline__ void stg128(void* p, uint32_t x, uint32_t y, uint32_t z, uint32_t w) {
    asm volatile("st.global.v4.b32 [%0], {%1,%2,%3,%4};" ::"l"(p), "r"(x), "r"(y), "r"(z), "r"(w) : "memory");
}
__device__ __forceinline__ uint32_t ld_acquire(const unsigned* p) {
    uint32_t v; asm volatile("ld.acquire.gpu.global.u32 %0, [%1];" : "=r"(v) : "l"(p) : "memory"); return v;
}
__device__ __forceinline__ void red_add_u32(unsigned* p, uint32_t v) {
    asm volatile("red.relaxed.gpu.global.add.u32 [%0], %1;" ::"l"(p), "r"(v) : "memory");
}
__device__ __forceinline__ void wait_counter(const unsigned* p, uint32_t target) {
    uint32_t n = 0;
    while (ld_acquire(p) < target) { if (++n > SPIN_LIMIT) __trap(); }
}

__device__ __forceinline__ void wg_fence() { asm volatile("wgmma.fence.sync.aligned;" ::: "memory"); }
__device__ __forceinline__ void wg_commit() { asm volatile("wgmma.commit_group.sync.aligned;" ::: "memory"); }
template <int N> __device__ __forceinline__ void wg_wait() { asm volatile("wgmma.wait_group.sync.aligned %0;" ::"n"(N) : "memory"); }
__host__ __device__ constexpr uint64_t mkdesc(uint32_t addr, uint32_t lbo, uint32_t sbo, uint32_t swz) {
    return (uint64_t)((addr & 0x3FFFF) >> 4) | ((uint64_t)(lbo >> 4) << 16) | ((uint64_t)(sbo >> 4) << 32) | ((uint64_t)swz << 62);
}
#define F4(d, o) "+f"(d[o]), "+f"(d[o + 1]), "+f"(d[o + 2]), "+f"(d[o + 3])
template <int SC> __device__ __forceinline__ void wg_rs32(float (&d)[16], const uint32_t (&a)[4], uint64_t db) {
    asm volatile("wgmma.mma_async.sync.aligned.m64n32k16.f32.bf16.bf16 "
                 "{%0,%1,%2,%3,%4,%5,%6,%7,%8,%9,%10,%11,%12,%13,%14,%15}, {%16,%17,%18,%19}, %20, %21, 1, 1, 0;"
                 : F4(d, 0), F4(d, 4), F4(d, 8), F4(d, 12)
                 : "r"(a[0]), "r"(a[1]), "r"(a[2]), "r"(a[3]), "l"(db), "n"(SC));
}
template <int SC> __device__ __forceinline__ void wg_rs40(float (&d)[20], const uint32_t (&a)[4], uint64_t db) {
    asm volatile("wgmma.mma_async.sync.aligned.m64n40k16.f32.bf16.bf16 "
                 "{%0,%1,%2,%3,%4,%5,%6,%7,%8,%9,%10,%11,%12,%13,%14,%15,%16,%17,%18,%19}, {%20,%21,%22,%23}, %24, %25, 1, 1, 0;"
                 : F4(d, 0), F4(d, 4), F4(d, 8), F4(d, 12), F4(d, 16)
                 : "r"(a[0]), "r"(a[1]), "r"(a[2]), "r"(a[3]), "l"(db), "n"(SC));
}
template <int SC> __device__ __forceinline__ void wg_ss40(float (&d)[20], uint64_t da, uint64_t db) {
    asm volatile("wgmma.mma_async.sync.aligned.m64n40k16.f32.bf16.bf16 "
                 "{%0,%1,%2,%3,%4,%5,%6,%7,%8,%9,%10,%11,%12,%13,%14,%15,%16,%17,%18,%19}, %20, %21, %22, 1, 1, 1, 0;"
                 : F4(d, 0), F4(d, 4), F4(d, 8), F4(d, 12), F4(d, 16)
                 : "l"(da), "l"(db), "n"(SC));
}
template <int SC> __device__ __forceinline__ void wg_ss8(float (&d)[4], uint64_t da, uint64_t db) {
    asm volatile("wgmma.mma_async.sync.aligned.m64n8k16.f32.bf16.bf16 {%0,%1,%2,%3}, %4, %5, %6, 1, 1, 1, 1;"
                 : F4(d, 0) : "l"(da), "l"(db), "n"(SC));
}

__device__ uint4 g_kvq[4 * 32 * 3 * 8 * 2 * 32];
__device__ uint2 g_alpha[2 * 32 * 3 * 8 * 2 * 32];
__device__ uint4 g_red[5 * 32768 / 16];
__device__ uint4 g_stamp[32];
__device__ uint4 g_qst[128 * 2];
__device__ unsigned g_start;
__device__ bf16 g_ox[2048 * 4096];
constexpr int DBG_N = 12;
#define TSI(st) do {} while (0)
#define TS(k) do {} while (0)
#define TSV(k, v) do {} while (0)
#define TSDUMP() do {} while (0)
#define GT(k) do {} while (0)
#define FLAG(b) false

struct Tune { uint32_t d_alpha, d_r0, d_r1, flags, d_st, d_v, spread, extra; };
#define QKW_EARLY 1
constexpr int RA = 2;
#define AV_POS 2

constexpr uint32_t SM_BASE = 1024;
constexpr uint32_t O_WO = 0;
constexpr uint32_t O_WV = 65536;
constexpr uint32_t O_XB = 131072;
constexpr uint32_t O_MEM = O_XB + 32768;
constexpr uint32_t O_RECV = O_MEM + 8192;
constexpr uint32_t O_KVQ = O_RECV + 12288;
constexpr uint32_t O_STG = O_KVQ + 18432;
constexpr uint32_t O_S = O_STG + 8192;
constexpr uint32_t O_XO = O_STG + 16384;
constexpr uint32_t O_P = O_S + 10240;
constexpr uint32_t O_O = O_P + 1536;
constexpr uint32_t O_VM = O_O + 2048;
constexpr uint32_t O_QST = O_VM + 2048;
constexpr uint32_t O_BAR = O_QST + 128;
constexpr uint32_t O_DBG = O_BAR + 256;
constexpr uint32_t MAIN_SMEM = O_DBG + (DBG_TIMING ? 4 * DBG_N * 24 * 4 : 0);
enum { B_WQ0 = 0, B_WQ1, B_WK0, B_WK1, B_WV, B_WO, B_QDONE, B_KDONE, B_XFULL, B_XEMPTY, B_MEM, B_RFULL, B_AFULL, B_KVFULL,
       B_RECV, B_QKW = B_RECV + 6, B_SDONE, B_SRDY, B_OPDONE, B_COUNT };

constexpr float SM_SCALE_LOG2 = 0.08838834764831845f * 1.4426950408889634f;
constexpr float MASK_VAL = -1.0e9f / 0.08838834764831845f;

__device__ __forceinline__ uint32_t red_grp(int grp) { return (uint32_t)((grp >> 1) * 1024 + (grp & 1) * 256); }
__host__ __device__ constexpr uint64_t xdesc(int ks) { return mkdesc(SM_BASE + O_XB + (ks >> 2) * 1024 + (ks & 3) * 32, 16, 8192, 1); }

__device__ __forceinline__ void x_split(const float* d, uint32_t (&sn)[4], uint32_t (&kp)[4], int kh) {
#pragma unroll
    for (int i = 0; i < 4; i++) {
        const uint32_t lo = pack_bf16(d[2 * i], d[2 * i + 1]), hi = pack_bf16(d[8 + 2 * i], d[8 + 2 * i + 1]);
        sn[i] = kh ? lo : hi; kp[i] = kh ? hi : lo;
    }
}
__device__ __forceinline__ void x_send(int R, const uint32_t (&sn)[4], int sg, int tid, uint32_t sb, uint32_t mate) {
    const uint32_t par = sg & 1;
    const uint32_t bar = O_BAR + 8 * (B_RECV + R * 2) + 8 * par;
    if (tid == 0) mbar_expect_tx(sb + bar, 2048);
    asm volatile("st.async.shared::cluster.mbarrier::complete_tx::bytes.v4.b32 [%0], {%1,%2,%3,%4}, [%5];"
                 ::"r"(mate + O_RECV + (par * 3 + R) * 2048 + tid * 16), "r"(sn[0]), "r"(sn[1]), "r"(sn[2]), "r"(sn[3]), "r"(mate + bar) : "memory");
}
__device__ __forceinline__ void x_wait(int R, int sg, uint32_t sb) {
    mbar_wait_cluster(sb + O_BAR + 8 * (B_RECV + R * 2) + 8 * (sg & 1), (sg >> 1) & 1);
}
template <int R>
__device__ __forceinline__ void x_finish(const uint32_t (&kp)[4], int sg, int h, int mt, int kh, int tid, uint32_t sb) {
    const uint4 r = lds128u(sb + O_RECV + ((sg & 1) * 3 + R) * 2048 + tid * 16);
    uint32_t u0 = add_bf16x2(kp[0], r.x), u1 = add_bf16x2(kp[1], r.y), u2 = add_bf16x2(kp[2], r.z), u3 = add_bf16x2(kp[3], r.w);
    if (R < 2) { u0 = movm(u0); u1 = movm(u1); u2 = movm(u2); u3 = movm(u3); }
    const uint32_t tag = ((sg >> 2) & 1) ^ 1;
    u0 = (u0 & ~1u) | tag;
    uint4* const hb = &g_kvq[((sg & 3) * 32 + h) * (3 * 512)];
    if (R == 0) {
        uint2* p = (uint2*)hb + (kh * 16 + mt) * 32 + (tid & 31);
        asm volatile("{\n.reg .pred p;\nsetp.lt.s32 p, %5, 64;\n@p st.relaxed.gpu.global.v2.b32 [%0], {%1,%2};\n@p st.relaxed.gpu.global.v2.b32 [%0+2048], {%3,%4};\n}"
                     ::"l"(p), "r"(u0), "r"(u1), "r"((u2 & ~1u) | tag), "r"(u3), "r"(sg) : "memory");
    } else {
        asm volatile("{\n.reg .pred p;\nsetp.lt.s32 p, %5, 64;\n@p st.relaxed.gpu.global.v4.b32 [%0], {%1,%2,%3,%4};\n}"
                     ::"l"(hb + R * 512 + (mt * 2 + kh) * 32 + (tid & 31)), "r"(u0), "r"(u1), "r"(u2), "r"(u3), "r"(sg) : "memory");
    }
}

__device__ __forceinline__ uint32_t convert_mem(const unsigned char* redp, int s, int kh, int jj, int w, int lane, uint32_t sb) {
    const uint32_t off = red_grp(jj * 16 + w * 4 + (lane >> 3)), o16 = off + (lane & 7) * 16, o8 = off + 512 + ((lane >> 3) & 1) * 64 + (lane & 7) * 8;
    uint32_t ma = sb + O_MEM + (jj * 4 + (lane >> 4)) * 1024 + (lane & 7) * 128 + (((2 * w + ((lane >> 3) & 1)) ^ (lane & 7)) << 4);
    uint32_t a16 = sb + O_STG + o16, a8 = sb + O_STG + o8;
    const uint32_t target = (s & 4) ? 0x42C00000u : 0x42000000u;
    asm volatile("" : "+r"(ma), "+r"(a16), "+r"(a8));
    mbar_wait(sb + O_BAR + 8 * B_RFULL, s & 1);
    uint4 ra = lds128u(a16), rb = lds128u(a16 + 128);
    uint2 rc = lds64u(a8);
    uint32_t n = 0;
    while (true) {
        stsm4t(ma, ra.x, ra.y, ra.z, __byte_perm(ra.w, rc.x, 0x5410));
        stsm4t(ma + 2048, rb.x, rb.y, rb.z, __byte_perm(rb.w, rc.x, 0x7610));
        if (__builtin_expect(!__any_sync(~0u, orx(orx2(ra.w, rb.w, target), rc.y, target) > 0xffffu), 1)) break;
        const unsigned char* pg = redp + (s & 3) * 32768 + kh * 16384;
        ra = ldg_rlx128(pg + o16); rb = ldg_rlx128(pg + o16 + 128); rc = ldg_rlx64(pg + o8);
        if (++n > SPIN_LIMIT) __trap();
    }
    __syncwarp();
    if (lane == 0) mbar_arrive(sb + O_BAR + 8 * B_MEM);
    fence_async_smem();
    __syncwarp();
    if (lane == 0) mbar_arrive(sb + O_BAR + 8 * B_QKW);
    return n;
}

__global__ void __cluster_dims__(2, 1, 1) __launch_bounds__(512, 1)
rmt_main(const __grid_constant__ CUtensorMap tm_x, const __grid_constant__ CUtensorMap tm_wq, const __grid_constant__ CUtensorMap tm_wk,
         const __grid_constant__ CUtensorMap tm_wv, const __grid_constant__ CUtensorMap tm_wo, const bf16* __restrict__ mem0, const Tune tn) {
    extern __shared__ __align__(1024) unsigned char smem_raw[];
    const uint32_t sb = smem_u32(smem_raw);
    if ((sb & 0x3FFFF) != SM_BASE) __trap();
    const int cid = blockIdx.x >> 1, kh = blockIdx.x & 1;
    const int tpc = cid < 4 ? 62 + cid : cid - 4;
    int h, nh;
    if (tpc < 32) { h = (tpc >> 4) * 8 + (tpc & 7); nh = (tpc >> 3) & 1; }
    else if (tpc < 60) { int u = tpc - 32, r = u % 14; h = 16 + (u / 14) * 7 + r % 7; nh = r / 7; }
    else if (tpc < 62) return;
    else { h = 30 + ((tpc - 62) >> 1); nh = tpc & 1; }
    const int j = nh * 2 + kh, role = h * 4 + j;
    const int wgi = __shfl_sync(~0u, threadIdx.x >> 7, 0);
    const int w = __shfl_sync(~0u, (threadIdx.x >> 5) & 3, 0);
    const int tid = threadIdx.x & 127, lane = tid & 31;
#define OPAQUE_IDS() int tid_ = tid; asm volatile("" : "+r"(tid_)); const int tid = tid_, lane = tid_ & 31; (void)lane
    unsigned char* const redp = (unsigned char*)(((uintptr_t)g_red + 32767) & ~(uintptr_t)32767);
    const uint32_t bars = sb + O_BAR;

    if (threadIdx.x == 0) {
        const uint8_t cnts[B_COUNT] = {1, 1, 1, 1, 1, 1, 4, 4, 1, 12, 8, 1, 1, 1, 1, 1, 1, 1, 1, 1, 16, 4, 4, 4};
#pragma unroll
        for (int i = 0; i < B_COUNT; i++) mbar_init(bars + 8 * i, cnts[i]);
        asm volatile("fence.mbarrier_init.release.cluster;" ::: "memory");
        fence_async_smem();
        const int c0 = h * 128 + nh * 64, r0 = kh * 512;
        for (int i = 0; i < 2; i++) {
            mbar_expect_tx(bars + 8 * (B_WK0 + i), 32768);
            tma2d(sb + O_XB + i * 32768, &tm_wk, c0, r0 + i * 256, bars + 8 * (B_WK0 + i));
            mbar_expect_tx(bars + 8 * (B_WQ0 + i), 32768);
            tma2d(sb + O_WO + i * 32768, &tm_wq, c0, r0 + i * 256, bars + 8 * (B_WQ0 + i));
        }
        mbar_expect_tx(bars + 8 * B_WV, 65536);
        for (int i = 0; i < 2; i++) tma2d(sb + O_WV + i * 32768, &tm_wv, c0, r0 + i * 256, bars + 8 * B_WV);
        for (int i = 0; i < 4; i++) tma2d_prefetch(&tm_wo, j * 256 + i * 64, h * 128);
        tma4d_prefetch(&tm_x, kh * 8, (role >> 1) * 4);
    }
    __syncthreads();
    uint32_t mate;
    asm volatile("mapa.shared::cluster.u32 %0, %1, %2;" : "=r"(mate) : "r"(sb), "r"(kh ^ 1));

    if (wgi < 2) {
        asm volatile("setmaxnreg.inc.sync.aligned.u32 176;");
        uint32_t a[32][4];
        {
            const uint32_t stage = sb + (wgi == 0 ? O_WO : O_XB);
            const uint32_t ad = stage + (((lane >> 4) & 1) * 8 + (lane & 7)) * 128 + (((2 * w + ((lane >> 3) & 1)) ^ (lane & 7)) << 4);
#pragma unroll
            for (int i = 0; i < 2; i++) {
                mbar_wait(bars + 8 * (B_WQ0 + 2 * wgi + i), 0);
#pragma unroll
                for (int ks = 0; ks < 16; ks++) ldsm4t(a[i * 16 + ks], ad + (i * 16 + ks) * 2048);
            }
            __syncwarp();
            if (lane == 0) mbar_arrive(bars + 8 * (B_QDONE + wgi));
        }
        asm volatile("barrier.cluster.arrive.release.aligned;" ::: "memory");
        asm volatile("barrier.cluster.wait.acquire.aligned;" ::: "memory");
        uint32_t kp[4], sf = 0;
#define X_PASS(d)                                                                                          \
        wg_fence();                                                                                        \
        _Pragma("unroll") for (int ks = 0; ks < 32; ks++) { if (ks == 0) wg_rs32<0>(d, a[ks], xdesc(ks)); else wg_rs32<1>(d, a[ks], xdesc(ks)); } \
        wg_commit();                                                                                       \
        wg_wait<0>();
#define QK_LOOP(R)                                                                                         \
        _Pragma("unroll 1") for (int sg = 0; sg < RA; sg++) {                                              \
            float d[16]; uint32_t sn[4];                                                                   \
            if (sg > 0) { x_wait(R, sg - 1, sb); x_finish<R>(kp, sg - 1, h, nh * 4 + w, kh, tid, sb); }    \
            mbar_wait(bars + 8 * B_XFULL, sg & 1);                                                         \
            X_PASS(d);                                                                                     \
            x_split(d, sn, kp, kh);                                                                        \
            x_send(R, sn, sg, tid, sb, mate);                                                              \
            if (lane == 0) mbar_arrive(bars + 8 * B_XEMPTY);                                               \
        }                                                                                                  \
        _Pragma("unroll 1") for (int s = 0; s < 64; s++) {                                                 \
            TSI(s);                                                                                        \
            {                                                                                              \
                float d[16]; uint32_t sn[4], kc[4];                                                        \
                x_wait(R, s + RA - 1, sb);                                                                 \
                mbar_wait(bars + 8 * B_XFULL, (s + RA) & 1);                                               \
                mbar_wait(bars + 8 * B_OPDONE, s & 1);                                                     \
                if (R == 1) { x_finish<R>(kp, s + RA - 1, h, nh * 4 + w, kh, tid, sb); TS(5); }            \
                TS(6);                                                                                     \
                X_PASS(d);                                                                                 \
                TS(7);                                                                                     \
                x_split(d, sn, kc, kh);                                                                    \
                x_send(R, sn, s + RA, tid, sb, mate);                                                      \
                if (lane == 0) mbar_arrive(bars + 8 * B_XEMPTY);                                           \
                TS(4);                                                                                     \
                if (R == 0) { x_finish<R>(kp, s + RA - 1, h, nh * 4 + w, kh, tid, sb); TS(5); }            \
                _Pragma("unroll") for (int i = 0; i < 4; i++) kp[i] = kc[i];                               \
            }                                                                                              \
            uint2* ap = &g_alpha[((s & 1) * 32 + h) * (3 * 512) + R * 512 + ((nh * 4 + w) * 2 + kh) * 32 + lane]; \
            uint32_t mb0 = sb + O_MEM + (lane & 7) * 128 + (((lane >> 3) ^ (lane & 7)) << 4), mb1 = mb0 ^ 64; \
            asm volatile("mov.b32 %0, %0;\nmov.b32 %1, %1;" : "+r"(mb0), "+r"(mb1), "+l"(ap));            \
            float e[2][4];                                                                                 \
            _Pragma("unroll") for (int i = 0; i < 4; i++) e[0][i] = e[1][i] = 0.f;                         \
            mbar_wait(bars + 8 * B_MEM, s & 1);                                                            \
            TS(0);                                                                                         \
            _Pragma("unroll") for (int ks = 0; ks < 32; ks += 2) {                                         \
                uint32_t b[4];                                                                             \
                ldsm4(b, ((ks & 2) ? mb1 : mb0) + (ks >> 2) * 1024);                                       \
                mma16816(e[0], a[ks][0], a[ks][1], a[ks][2], a[ks][3], b[0], b[1]);                        \
                mma16816(e[1], a[ks + 1][0], a[ks + 1][1], a[ks + 1][2], a[ks + 1][3], b[2], b[3]);        \
            }                                                                                              \
            TS(2);                                                                                         \
            if (lane < 8) asm volatile("st.relaxed.gpu.global.u32 [%0], %1;" ::"l"((uint32_t*)g_qst + role * 8 + lane), "r"(gtime()) : "memory"); \
            uint32_t u0 = pack_bf16(e[0][0] + e[1][0], e[0][1] + e[1][1]), u1 = pack_bf16(e[0][2] + e[1][2], e[0][3] + e[1][3]); \
            u0 = movm(u0); u1 = movm(u1);                                                                  \
            if (QKW_EARLY) { SCHED_FENCE(); if (lane == 0) mbar_arrive(bars + 8 * B_QKW); }                \
            stg_rlx64(ap, (u0 & ~1u) | (((s >> 1) & 1) ^ 1), u1);                                          \
            if (!QKW_EARLY && lane == 0) mbar_arrive(bars + 8 * B_QKW);                                    \
            TS(3);                                                                                         \
        }                                                                                                  \
        x_wait(R, 63 + RA, sb);
        if (wgi == 0) { QK_LOOP(0); } else { QK_LOOP(1); }
        if (QKW_EARLY) sts32(bars + 252, sf);
        TSDUMP();
    } else if (wgi == 2) {
        asm volatile("setmaxnreg.dec.sync.aligned.u32 64;");
        asm volatile("barrier.cluster.arrive.release.aligned;" ::: "memory");
        if (w == 0) {
            mbar_wait(bars + 8 * B_KDONE, 0);
            if (lane == 0) {
                mbar_expect_tx(bars + 8 * B_XFULL, 32768);
                tma4d(sb + O_XB, &tm_x, kh * 8, 0, bars + 8 * B_XFULL);
            }
            mbar_wait(bars + 8 * B_QDONE, 0);
            if (lane == 0) {
                mbar_expect_tx(bars + 8 * B_WO, 65536);
#pragma unroll
                for (int i = 0; i < 4; i++) tma2d(sb + O_WO + i * 16384, &tm_wo, j * 256 + i * 64, h * 128, bars + 8 * B_WO);
            }
        }
        asm volatile("barrier.cluster.wait.acquire.aligned;" ::: "memory");
        mbar_wait(bars + 8 * B_WV, 0);
        sts128u(sb + O_VM + tid * 16, make_uint4(0, 0, 0, 0));
        uint32_t tref = gtime() - 4000;
#define V_PASS(d)                                                                                          \
        wg_fence();                                                                                        \
        _Pragma("unroll") for (int ks = 0; ks < 32; ks++) {                                                \
            constexpr uint64_t da0 = mkdesc(SM_BASE + O_WV, 16, 1024, 1);                                  \
            if (ks == 0) wg_ss40<0>(d, da0 + ks * 128, xdesc(ks)); else wg_ss40<1>(d, da0 + ks * 128, xdesc(ks)); \
        }                                                                                                  \
        wg_commit();                                                                                       \
        wg_wait<0>();
#define X_REFILL(sg)                                                                                       \
        if (lane == 0) {                                                                                   \
            mbar_expect_tx(bars + 8 * B_XFULL, 32768);                                                     \
            tma4d(sb + O_XB, &tm_x, kh * 8, (sg) * 4, bars + 8 * B_XFULL);       \
        }
#pragma unroll 1
        for (int sg = 0; sg < RA; sg++) {
            float d[20]; uint32_t sn[4], kp[4];
            mbar_wait(bars + 8 * B_XFULL, sg & 1);
            V_PASS(d);
            if (lane == 0) mbar_arrive(bars + 8 * B_XEMPTY);
            if (w == 0) { mbar_wait(bars + 8 * B_XEMPTY, sg & 1); X_REFILL(sg + 1); }
            x_split(d, sn, kp, kh);
            x_send(2, sn, sg, tid, sb, mate);
            x_wait(2, sg, sb);
            x_finish<2>(kp, sg, h, nh * 4 + w, kh, tid, sb);
        }
#pragma unroll 1
        for (int s = 0; s < 64; s++) {
            TSI(s);
            OPAQUE_IDS();
            uint2* ap = &g_alpha[((s & 1) * 32 + h) * (3 * 512) + 1024 + ((nh * 4 + w) * 2 + kh) * 32 + lane];
            asm volatile("" : "+l"(ap));
            float d[20];
            mbar_wait(bars + 8 * B_QKW, s & 1);
            TS(0);
            V_PASS(d);
            TS(1);
            stg_rlx64(ap, (pack_bf16(d[16], d[17]) & ~1u) | (((s >> 1) & 1) ^ 1), pack_bf16(d[18], d[19]));
            const uint32_t tv = gtime();
            if (tid == 0) asm volatile("st.relaxed.gpu.global.u32 [%0], %1;" ::"l"((uint32_t*)g_stamp + role), "r"(tv) : "memory");
            if (lane == 0) mbar_arrive(bars + 8 * B_XEMPTY);
            uint32_t sn[4], kp[4];
            x_split(d, sn, kp, kh);
            {
                const uint2* vp = &g_alpha[((s & 1) * 32 + h) * (3 * 512) + 1024 + w * 128 + lane];
                const uint32_t tag = ((s >> 1) & 1) ^ 1;
                mbar_wait(bars + 8 * B_AFULL, s & 1);
                int dt;
                asm volatile("ld.shared.u32 %0, [%1];" : "=r"(dt) : "r"(sb + O_QST + lane * 4) : "memory");
                dt = min(__reduce_max_sync(~0u, dt - (int)tv), 0);
                asm volatile("" : "+l"(vp));
                wait_gtime(tv + dt + tn.d_v);
                uint32_t n = 0, bad;
                do {
                    uint2 va[4];
#pragma unroll
                    for (int i = 0; i < 4; i++) va[i] = ldg_rlx64(vp + i * 32);
                    if (++n > SPIN_LIMIT) __trap();
                    bad = (orx2(va[0].x, va[1].x, tag) | orx2(va[2].x, va[3].x, tag)) & 1;
                    sts128u(sb + O_VM + tid * 16, make_uint4((add_bf16x2(va[0].x, va[1].x) & ~1u) | ((~s ^ bad) & 1), add_bf16x2(va[0].y, va[1].y),
                                                             add_bf16x2(va[2].x, va[3].x), add_bf16x2(va[2].y, va[3].y)));
                } while (__any_sync(~0u, bad));
                TS(2);
                TSV(16 + w, n - 1);
            }
            if (s == 63) break;
            if (w == 0) {
                mbar_wait(bars + 8 * B_XEMPTY, (s + RA) & 1);
                X_REFILL(s + RA + 1);
                if (lane == 0 && nh == 0 && ((h ^ s) & 7) == 0 && s < 61 - RA) tma4d_prefetch(&tm_x, kh * 8, (s + RA + 3) * 4);
                mbar_wait(bars + 8 * B_SRDY, s & 1);
                if (lane == 0) {
                    const uint4* hb = &g_kvq[(((s + 1) & 3) * 32 + h) * (3 * 512)];
                    mbar_expect_tx(bars + 8 * B_KVFULL, 18432);
                    bulk_g2s(sb + O_KVQ, hb + 512, 16384, bars + 8 * B_KVFULL);
                    bulk_g2s(sb + O_KVQ + 16384, hb + j * 128, 2048, bars + 8 * B_KVFULL);
                }
            }
            if (w == 3) {
                wait_clk(clk(), tn.d_st);
                uint32_t n = 0, mx, mn;
                do {
                    const uint4 st = ldg_rlx128(&g_stamp[lane]);
                    mx = __reduce_max_sync(~0u, max(max(st.x - tref, st.y - tref), max(st.z - tref, st.w - tref)));
                    mn = __reduce_min_sync(~0u, min(min(st.x - tref, st.y - tref), min(st.z - tref, st.w - tref)));
                } while (mx >= 200000u && ++n < 64);
                tref = mx < 200000u ? tref + mx + (mx - mn > tn.spread ? tn.extra : 1) : gtime();
                TSV(12, clk()); TSV(13, n); TSV(14, mx - mn);
            }
            mbar_wait(bars + 8 * B_OPDONE, (s + 1) & 1);
            x_send(2, sn, s + RA, tid, sb, mate);
            if (w == 3) {
                wait_gtime(tref + tn.d_r0);
                if (lane == 0) {
                    mbar_expect_tx(bars + 8 * B_RFULL, 16384);
                    bulk_g2s(sb + O_STG, redp + (s & 3) * 32768 + kh * 16384, 16384, bars + 8 * B_RFULL);
                }
                TSV(3, clk());
            }
            x_wait(2, s + RA, sb);
            x_finish<2>(kp, s + RA, h, nh * 4 + w, kh, tid, sb);
            TS(6);
            if (DBG_TIMING) { mbar_wait(bars + 8 * B_RFULL, s & 1); TS(4); }
            const uint32_t n = convert_mem(redp, s, kh, 0, w, lane, sb); (void)n;
            TS(5);
            TSV(8 + w, n);
        }
        TSDUMP();
    } else {
        asm volatile("setmaxnreg.dec.sync.aligned.u32 96;");
        GT(0);
        asm volatile("barrier.cluster.arrive.release.aligned;" ::: "memory");
#define RED_CLEAR(st)                                                                                           \
        if (lane < 16) {                                                                                        \
            const uint32_t cb = ((st) & 4) ? 0x42800000u : 0u;                                                  \
            stg128(redp + ((st) & 3) * 32768 + role * 256 + lane * 16, 0, (role & 2) ? cb : 0u, 0, cb);        \
        }
#define KQ_BAD(tg) __any_sync(~0u, or3(orx2(kf[0].x, kf[1].x, tg), orx2(kf[2].x, kf[3].x, tg), orx2(qf[0].x, qf[1].x, tg)) & 1)
#define KQ_POLL(st)                                                                                             \
        {                                                                                                       \
            const uint4* hb = &g_kvq[(((st) & 3) * 32 + h) * (3 * 512)];                                        \
            uint32_t n_ = 0;                                                                                    \
            do {                                                                                                \
                _Pragma("unroll") for (int i = 0; i < 4; i++) kf[i] = ldg_rlx128(hb + 512 + w * 128 + i * 32 + lane); \
                _Pragma("unroll") for (int u = 0; u < 2; u++) qf[u] = ldg_rlx64((const uint2*)hb + j * 256 + (2 * w + u) * 32 + lane); \
                if (++n_ > SPIN_LIMIT) __trap();                                                                \
            } while (KQ_BAD((((st) >> 2) & 1) ^ 1));                                                \
        }
        uint32_t start_target = 0;
        if (w == 0) {
            RED_CLEAR(0); RED_CLEAR(1); RED_CLEAR(2);
            fence_gpu();
            __syncwarp();
            if (lane == 0) start_target = (atomicAdd(&g_start, 1) & ~127u) + 128;
            start_target = __shfl_sync(~0u, start_target, 0);
        }
        mbar_wait(bars + 8 * B_KDONE, 0);
        {
            const int kb0 = (w & 1) * 4 + (w >> 1) * 2;
#pragma unroll
            for (int q = 0; q < 4; q++) {
                const int row = (lane >> 3) + (q & 1) * 4, ch = lane & 7, kb = kb0 + (q >> 1);
                const uint4 v = *(const uint4*)(mem0 + row * 1024 + kh * 512 + kb * 64 + ch * 8);
                sts128u(sb + O_MEM + kb * 1024 + row * 128 + ((ch ^ row) << 4), v);
            }
            fence_async_smem();
            __syncwarp();
            if (lane < 2) { mbar_arrive(bars + 8 * B_MEM); mbar_arrive(bars + 8 * B_QKW); }
            if (lane == 0) mbar_arrive(bars + 8 * B_OPDONE);
        }
        asm volatile("barrier.cluster.wait.acquire.aligned;" ::: "memory");
        if (w == 0) { uint32_t n = 0; while (__any_sync(~0u, (int)(ld_acquire(&g_start) - start_target) < 0)) { if (++n > SPIN_LIMIT) __trap(); } }
        mbar_wait(bars + 8 * B_WO, 0);
        GT(1);
        uint32_t sf = 0;
        uint4 kf[4]; uint2 qf[2];
        KQ_POLL(0);
#pragma unroll
        for (int i = 0; i < 4; i++) sts128u(sb + O_KVQ + 8192 + w * 2048 + i * 512 + lane * 16, make_uint4(0, 0, 0, 0));
#pragma unroll 1
        for (int s = 0; s < 64; s++) {
            TSI(s);
            OPAQUE_IDS();
            const uint32_t tg = ((s >> 2) & 1) ^ 1;
            const uint32_t tag = ((s >> 1) & 1) ^ 1;
            const uint2* ap = &g_alpha[((s & 1) * 32 + h) * (3 * 512) + w * 128 + lane];
            uint32_t sw = sb + O_S + w * 2560 + lane * 16, sr = sb + O_S + tid * 4;
            uint32_t pw = sb + O_P + ((lane >> 1) & 1) * 704 + (2 * w + (lane >> 4)) * 16 + ((lane >> 2) & 3) * 4 + (lane & 1) * 2;
            int lim = (lane & 2) ? 8 * j + 2 * w + (lane >> 4) - 2 * ((lane >> 2) & 3) - (lane & 1) : 64;
            uint32_t pr = sb + O_P + lane * 16, oa = sb + O_O + w * 512 + lane * 4;
            uint32_t aa = sb + O_STG + w * 1024 + lane * 8, vv = sb + O_KVQ + 8192 + w * 2048 + lane * 16;
            unsigned char* pa = redp + (s & 3) * 32768 + red_grp(j * 16 + (tid >> 3));
            unsigned char* pb = pa + 512 + ((lane >> 3) & 1) * 64 + (lane & 7) * 8;
            pa += (lane & 7) * 16;
            asm volatile("" : "+r"(sw), "+r"(sr), "+r"(pw), "+r"(lim), "+r"(pr), "+r"(oa), "+r"(aa), "+r"(vv), "+l"(ap), "+l"(pa), "+l"(pb));
            TS(0);
            mbar_wait(bars + 8 * B_QKW, s & 1);
            TS(1);
            if (w == 0) {
                wait_clk(clk(), tn.d_alpha);
                if (lane == 0) {
                    mbar_expect_tx(bars + 8 * B_AFULL, 8192 + 128);
                    bulk_g2s(sb + O_STG, ap, 8192, bars + 8 * B_AFULL);
                    bulk_g2s(sb + O_QST, &g_qst[h * 8], 128, bars + 8 * B_AFULL);
                }
            }
            mbar_wait(bars + 8 * B_AFULL, s & 1);
            TS(12);
            uint4 vf[4];
            {
                uint2 qa[4], ka[4];
#pragma unroll
                for (int i = 0; i < 4; i++) { qa[i] = lds64u(aa + i * 256); ka[i] = lds64u(aa + 4096 + i * 256); }
#define QK_BAD() __any_sync(~0u, or3(orx2(qa[0].x, ka[0].x, tag), orx2(qa[1].x, ka[1].x, tag), orx(orx(orx2(qa[2].x, ka[2].x, tag), qa[3].x, tag), ka[3].x, tag)) & 1)
#define SCORES()                                                                                                                  \
                {                                                                                                                 \
                    float sa[5][4];                                                                                               \
                    _Pragma("unroll") for (int n = 0; n < 5; n++) sa[n][0] = sa[n][1] = sa[n][2] = sa[n][3] = 0.f;                \
                    _Pragma("unroll") for (int u = 0; u < 2; u++) {                                                               \
                        const uint32_t q0 = add_bf16x2(qa[2 * u].x, qa[2 * u + 1].x), q1 = add_bf16x2(qa[2 * u].y, qa[2 * u + 1].y); \
                        const uint32_t k0 = add_bf16x2(ka[2 * u].x, ka[2 * u + 1].x), k1 = add_bf16x2(ka[2 * u].y, ka[2 * u + 1].y); \
                        mma16816(sa[1], q0, qf[u].x, q1, qf[u].y, kf[2 * u].x, kf[2 * u].y);                                      \
                        mma16816(sa[2], q0, qf[u].x, q1, qf[u].y, kf[2 * u].z, kf[2 * u].w);                                      \
                        mma16816(sa[3], q0, qf[u].x, q1, qf[u].y, kf[2 * u + 1].x, kf[2 * u + 1].y);                              \
                        mma16816(sa[4], q0, qf[u].x, q1, qf[u].y, kf[2 * u + 1].z, kf[2 * u + 1].w);                              \
                        mma16816(sa[0], q0, qf[u].x, q1, qf[u].y, k0, k1);                                                        \
                        if (u == 0) SCHED_FENCE();                                                                                \
                    }                                                                                                             \
                    _Pragma("unroll") for (int n = 1; n <= 5; n++) sts128(sw + (n % 5) * 512, sa[n % 5][0], sa[n % 5][1], sa[n % 5][2], sa[n % 5][3]); \
                }
                SCORES();
                uint32_t nr = 0;
                if (__builtin_expect(QK_BAD(), 0)) {
                    do {
#pragma unroll
                        for (int i = 0; i < 4; i++) { qa[i] = ldg_rlx64(ap + i * 32); ka[i] = ldg_rlx64(ap + 512 + i * 32); }
                        if (++nr > SPIN_LIMIT) __trap();
                    } while (QK_BAD());
                    SCORES();
                }
                if (w == 0) TSV(20, nr);
            }
            TS(2);
            bar_sync(1, 128);
            float sc[5];
            {
                float x[4][5];
#pragma unroll
                for (int q = 0; q < 4; q++)
#pragma unroll
                    for (int n = 0; n < 5; n++) asm volatile("ld.shared.f32 %0, [%1];" : "=f"(x[q][n]) : "r"(sr + q * 2560 + n * 512) : "memory");
#pragma unroll
                for (int n = 0; n < 5; n++) sc[n] = (x[0][n] + x[1][n]) + (x[2][n] + x[3][n]);
            }
            TS(15);
#pragma unroll
            for (int n = 1; n < 5; n++) if (8 * (n - 1) > lim) sc[n] = MASK_VAL;
            float m = fmaxf(fmaxf(fmaxf(sc[0], sc[1]), fmaxf(sc[2], sc[3])), sc[4]);
            m = fmaxf(m, __shfl_xor_sync(~0u, m, 1));
            m = fmaxf(m, __shfl_xor_sync(~0u, m, 4));
            m = fmaxf(m, __shfl_xor_sync(~0u, m, 8));
            m *= -SM_SCALE_LOG2;
            SCHED_FENCE();
#pragma unroll
            for (int i = 0; i < 4; i++) vf[i] = lds128u(vv + i * 512);
#pragma unroll
            for (int n = 0; n < 5; n++) {
                const uint32_t pv = pack_bf16(ex2(fmaf(sc[n], SM_SCALE_LOG2, m)), 0.f);
                asm volatile("st.shared.u16 [%0], %1;" ::"r"(pw + n * 128), "h"((uint16_t)pv) : "memory");
            }
            bar_sync(1, 128);
            TS(3);
            uint32_t pf[4], p0, px[4], px0;
            ldsm4(pf, pr + 128);
            asm volatile("ld.shared.u32 %0, [%1];" : "=r"(p0) : "r"(oa - w * 512 + (O_P - O_O)) : "memory");
            ldsm4(px, pr + 128 + 704);
            asm volatile("ld.shared.u32 %0, [%1];" : "=r"(px0) : "r"(oa - w * 512 + (O_P - O_O) + 704) : "memory");
            if (lane == 0) mbar_arrive(bars + 8 * B_SRDY);
            uint4 vm = lds128u(sb + O_VM + tid * 16);
            if (__builtin_expect(__any_sync(~0u, orx(orx(orx2(vf[0].x, vf[1].x, tg), vf[2].x, tg), vf[3].x, tg) & 1), 0)) {
                const uint4* vp = &g_kvq[((s & 3) * 32 + h) * (3 * 512) + 1024 + w * 128 + lane];
                uint32_t nr = 0;
                do {
#pragma unroll
                    for (int i = 0; i < 4; i++) vf[i] = ldg_rlx128(vp + i * 32);
                    if (++nr > SPIN_LIMIT) __trap();
                } while (__any_sync(~0u, orx(orx(orx2(vf[0].x, vf[1].x, tg), vf[2].x, tg), vf[3].x, tg) & 1));
            }
            float o[2][4], ox[2][4], sm[4], sx[4];
#pragma unroll
            for (int i = 0; i < 4; i++) o[0][i] = o[1][i] = ox[0][i] = ox[1][i] = sm[i] = sx[i] = 0.f;
            constexpr uint32_t ONE2 = 0x3f803f80u;
#pragma unroll
            for (int c = 0; c < 2; c++) {
#pragma unroll
                for (int u = 0; u < 2; u++) mma16816(o[u], vf[2 * u + c].x, vf[2 * u + c].y, vf[2 * u + c].z, vf[2 * u + c].w, pf[2 * c], pf[2 * c + 1]);
#pragma unroll
                for (int u = 0; u < 2; u++) mma16816(ox[u], vf[2 * u + c].x, vf[2 * u + c].y, vf[2 * u + c].z, vf[2 * u + c].w, px[2 * c], px[2 * c + 1]);
            }
            {
                uint32_t nr = 0;
                while (__any_sync(~0u, (vm.x ^ ~s) & 1)) { vm = lds128u(sb + O_VM + tid * 16); if (++nr > SPIN_LIMIT) __trap(); }
                if (w == 0) TSV(21, nr);
            }
            mma1688(o[0], vm.x, vm.y, p0);
            mma1688(o[1], vm.z, vm.w, p0);
            mma1688(sm, ONE2, ONE2, p0);
            mma1688(sx, ONE2, ONE2, px0);
            SCHED_FENCE();
            sts32(oa, pack_bf16(o[0][0], o[0][1]));
            sts32(oa + 128, pack_bf16(o[0][2], o[0][3]));
            sts32(oa + 256, pack_bf16(o[1][0], o[1][1]));
            sts32(oa + 384, pack_bf16(o[1][2], o[1][3]));
            mma1688(ox[0], vm.x, vm.y, px0);
            mma1688(ox[1], vm.z, vm.w, px0);
#pragma unroll
            for (int c = 0; c < 2; c++) {
                mma16816(sm, ONE2, ONE2, ONE2, ONE2, pf[2 * c], pf[2 * c + 1]);
                mma16816(sx, ONE2, ONE2, ONE2, ONE2, px[2 * c], px[2 * c + 1]);
            }
            SCHED_FENCE();
            TS(4);
            fence_async_smem();
            bar_sync(1, 128);
            if (s == 0) GT(2);
            TS(5);
            {
            float cc[4][4];
            wg_fence();
#pragma unroll
            for (int ks = 0; ks < 8; ks++)
#pragma unroll
                for (int t = 0; t < 4; t++) {
                    constexpr uint64_t da0 = mkdesc(SM_BASE + O_WO, 16, 1024, 1), db0 = mkdesc(SM_BASE + O_O, 128, 128, 0);
                    if (ks == 0) wg_ss8<0>(cc[t], da0 + t * 1024, db0); else wg_ss8<1>(cc[t], da0 + t * 1024 + ks * 128, db0 + ks * 16);
                }
            wg_commit();
            const float i0 = rcp(sm[0]), i1 = rcp(sm[1]);
            wg_wait<0>();
            TS(6);
#pragma unroll
            for (int hf = 0; hf < 2; hf++)
                asm volatile("red.relaxed.gpu.global.add.noftz.v4.bf16x2 [%0], {%1,%2,%3,%4};" ::"l"(pa + hf * 128),
                             "r"(pack_bf16(cc[2 * hf][0] * i0, cc[2 * hf][1] * i1)), "r"(pack_bf16(cc[2 * hf][2] * i0, cc[2 * hf][3] * i1)),
                             "r"(pack_bf16(cc[2 * hf + 1][0] * i0, cc[2 * hf + 1][1] * i1)), "r"(pack_bf16(cc[2 * hf + 1][2] * i0, 1.f)) : "memory");
            asm volatile("red.relaxed.gpu.global.add.noftz.v2.bf16x2 [%0], {%1,%2};" ::"l"(pb), "r"(pack_bf16(cc[1][3] * i1, cc[3][3] * i1)), "r"(0x3f800000u) : "memory");
            SCHED_FENCE();
            TS(7);
            if (lane == 0) mbar_arrive(bars + 8 * B_OPDONE);
            }
            if (!FLAG(3)) {
                const float ix0 = rcp(sx[0]), ix1 = rcp(sx[1]);
                const uint32_t xo = sb + O_XO + w * 512;
                stsm4t(xo + (lane & 7) * 64 + (((lane >> 3) ^ ((lane >> 1) & 3)) << 4), pack_bf16(ox[0][0] * ix0, ox[0][1] * ix1),
                       pack_bf16(ox[0][2] * ix0, ox[0][3] * ix1), pack_bf16(ox[1][0] * ix0, ox[1][1] * ix1), pack_bf16(ox[1][2] * ix0, ox[1][3] * ix1));
                __syncwarp();
                const uint4 ov = lds128u(xo + (lane >> 2) * 64 + (((lane & 3) ^ ((lane >> 3) & 3)) << 4));
                stg128(&g_ox[(size_t)(s * 32 + j * 8 + (lane >> 2)) * 4096 + h * 128 + w * 32 + (lane & 3) * 8], ov.x, ov.y, ov.z, ov.w);
            }
            TS(8);
            if (s == 63) { GT(3); break; }
            mbar_wait(bars + 8 * B_KVFULL, s & 1);
#pragma unroll
            for (int i = 0; i < 4; i++) kf[i] = lds128u(vv - 8192 + i * 512);
#pragma unroll
            for (int u = 0; u < 2; u++) qf[u] = lds64u(sb + O_KVQ + 16384 + (2 * w + u) * 256 + lane * 8);
            if (__builtin_expect(KQ_BAD((((s + 1) >> 2) & 1) ^ 1), 0)) { KQ_POLL(s + 1); if (w == 0) TSV(22, 1); }
            TS(9);
            {
                const uint32_t n = convert_mem(redp, s, kh, 1, w, lane, sb); (void)n;
                TS(11);
                TSV(16 + w, n);
            }
            if (w == 0 && s < 61) RED_CLEAR(s + 3);
        }
        sts32(bars + 252, sf);
        TSDUMP();
    }
}

constexpr int G_ST = 6;
constexpr uint32_t G_SMEM = G_ST * 32768 + 256;
#define F16(d, o) F4(d, o), F4(d, o + 4), F4(d, o + 8), F4(d, o + 12)
__device__ __forceinline__ void wg_ss128(float (&d)[64], uint64_t da, uint64_t db, int sc) {
    asm volatile("{\n.reg .pred p;\nsetp.ne.b32 p, %66, 0;\nwgmma.mma_async.sync.aligned.m64n128k16.f32.bf16.bf16 "
                 "{%0,%1,%2,%3,%4,%5,%6,%7,%8,%9,%10,%11,%12,%13,%14,%15,%16,%17,%18,%19,%20,%21,%22,%23,%24,%25,%26,%27,%28,%29,%30,%31,"
                 "%32,%33,%34,%35,%36,%37,%38,%39,%40,%41,%42,%43,%44,%45,%46,%47,%48,%49,%50,%51,%52,%53,%54,%55,%56,%57,%58,%59,%60,%61,%62,%63}, "
                 "%64, %65, p, 1, 1, 0, 1;\n}"
                 : F16(d, 0), F16(d, 16), F16(d, 32), F16(d, 48) : "l"(da), "l"(db), "r"(sc));
}

__global__ void __launch_bounds__(384, 1)
out_gemm(const __grid_constant__ CUtensorMap tm_o, const __grid_constant__ CUtensorMap tm_w, bf16* __restrict__ out) {
    extern __shared__ __align__(1024) unsigned char smem_raw[];
    const uint32_t sb = smem_u32(smem_raw), bars = sb + G_ST * 32768;
    const int m0 = (blockIdx.x >> 3) * 128, n0 = (blockIdx.x & 7) * 128;
    const int wgi = __shfl_sync(~0u, threadIdx.x >> 7, 0), tid = threadIdx.x & 127;
    if (threadIdx.x == 0) {
        for (int i = 0; i < G_ST; i++) { mbar_init(bars + 8 * i, 1); mbar_init(bars + 8 * (G_ST + i), 8); }
        fence_async_smem();
    }
    __syncthreads();
    if (wgi == 0) GT(4);
    if (wgi == 2) {
        if (tid == 0) {
            for (int kt = 0; kt < 64; kt++) {
                const int st = kt % G_ST;
                if (kt >= G_ST) mbar_wait(bars + 8 * (G_ST + st), (kt / G_ST - 1) & 1);
                mbar_expect_tx(bars + 8 * st, 32768);
                tma2d(sb + st * 32768, &tm_o, kt * 64, m0, bars + 8 * st);
                tma2d(sb + st * 32768 + 16384, &tm_w, n0, kt * 64, bars + 8 * st);
                tma2d(sb + st * 32768 + 24576, &tm_w, n0 + 64, kt * 64, bars + 8 * st);
            }
        }
    } else {
        float d[64];
        int st = 0, ph = 0;
#pragma unroll 1
        for (int kt = 0; kt < 64; kt++) {
            mbar_wait(bars + 8 * st, ph);
            const uint64_t da = mkdesc(sb + st * 32768 + wgi * 8192, 16, 1024, 1), db = mkdesc(sb + st * 32768 + 16384, 8192, 1024, 1);
            wg_fence();
#pragma unroll
            for (int k = 0; k < 4; k++) wg_ss128(d, da + k * 2, db + k * 128, kt | k);
            wg_commit();
            if (kt > 0) {
                wg_wait<1>();
                if ((tid & 31) == 0) mbar_arrive(bars + 8 * (G_ST + (st == 0 ? G_ST - 1 : st - 1)));
            }
            if (++st == G_ST) { st = 0; ph ^= 1; }
        }
        wg_wait<0>();
        const int row = m0 + wgi * 64 + (tid >> 5) * 16 + ((tid & 31) >> 2);
        bf16* op = out + (size_t)row * 2048 + 1024 + n0 + (tid & 3) * 2;
#pragma unroll
        for (int i = 0; i < 16; i++) {
            *(uint32_t*)(op + i * 8) = pack_bf16(d[4 * i], d[4 * i + 1]);
            *(uint32_t*)(op + 8 * 2048 + i * 8) = pack_bf16(d[4 * i + 2], d[4 * i + 3]);
        }
        if (wgi == 0) GT(5);
    }
}

typedef CUresult (*EncodeFn)(CUtensorMap*, CUtensorMapDataType, cuuint32_t, void*, const cuuint64_t*, const cuuint64_t*,
                             const cuuint32_t*, const cuuint32_t*, CUtensorMapInterleave, CUtensorMapSwizzle,
                             CUtensorMapL2promotion, CUtensorMapFloatOOBfill);

static void make_map(EncodeFn fn, CUtensorMap* m, const void* p, uint64_t cols, uint64_t rows, uint32_t bc, uint32_t br) {
    cuuint64_t dims[2] = {cols, rows}, strides[1] = {cols * 2};
    cuuint32_t box[2] = {bc, br}, es[2] = {1, 1};
    fn(m, CU_TENSOR_MAP_DATA_TYPE_BFLOAT16, 2, (void*)p, dims, strides, box, es, CU_TENSOR_MAP_INTERLEAVE_NONE,
       CU_TENSOR_MAP_SWIZZLE_128B, CU_TENSOR_MAP_L2_PROMOTION_L2_128B, CU_TENSOR_MAP_FLOAT_OOB_FILL_NONE);
}

static Tune h_tune = {300, 1150, 1, 0, 0, 704, 4000, 300};

extern "C" void kernel_launch(void* const* d_in, const int* in_sizes, int n_in, void* d_out, int out_size) {
    static bool init = false;
    static CUtensorMap tm_x, tm_wq, tm_wk, tm_wv, tm_wo, tm_o, tm_wo2;
    if (!init) {
        void* fp = nullptr; cudaDriverEntryPointQueryResult qr;
        cudaGetDriverEntryPoint("cuTensorMapEncodeTiled", &fp, cudaEnableDefault, &qr);
        EncodeFn fn = (EncodeFn)fp;
        void* ox = nullptr; cudaGetSymbolAddress(&ox, g_ox);
        {
            cuuint64_t dims[4] = {64, 8, 16, 256}, strides[3] = {2048, 128, 16384};
            cuuint32_t box[4] = {64, 8, 8, 4}, es[4] = {1, 1, 1, 1};
            fn(&tm_x, CU_TENSOR_MAP_DATA_TYPE_BFLOAT16, 4, d_in[3], dims, strides, box, es, CU_TENSOR_MAP_INTERLEAVE_NONE,
               CU_TENSOR_MAP_SWIZZLE_128B, CU_TENSOR_MAP_L2_PROMOTION_L2_128B, CU_TENSOR_MAP_FLOAT_OOB_FILL_NONE);
        }
        make_map(fn, &tm_wq, d_in[5], 4096, 1024, 64, 256);
        make_map(fn, &tm_wk, d_in[6], 4096, 1024, 64, 256);
        make_map(fn, &tm_wv, d_in[7], 4096, 1024, 64, 256);
        make_map(fn, &tm_wo, d_in[8], 1024, 4096, 64, 128);
        make_map(fn, &tm_o, ox, 4096, 2048, 64, 128);
        make_map(fn, &tm_wo2, d_in[8], 1024, 4096, 64, 64);
        cudaFuncSetAttribute(rmt_main, cudaFuncAttributeMaxDynamicSharedMemorySize, MAIN_SMEM);
        cudaFuncSetAttribute(out_gemm, cudaFuncAttributeMaxDynamicSharedMemorySize, G_SMEM);
        init = true;
    }
    rmt_main<<<132, 512, MAIN_SMEM>>>(tm_x, tm_wq, tm_wk, tm_wv, tm_wo, (const bf16*)d_in[4], h_tune);
    out_gemm<<<128, 384, G_SMEM>>>(tm_o, tm_wo2, (bf16*)d_out);
}
```

```cpp
#include <cuda_runtime.h>
#include <cuda_bf16.h>
#include <cuda.h>
#include <stdint.h>

typedef __nv_bfloat16 bf16;

#define DBG_TIMING 0

#define SPIN_LIMIT (1u << 22)

__device__ __forceinline__ uint32_t smem_u32(const void* p) { return (uint32_t)__cvta_generic_to_shared(p); }
__device__ __forceinline__ uint32_t clk() { uint32_t c; asm volatile("mov.u32 %0, %%clock;" : "=r"(c)::"memory"); return c; }
#define SCHED_FENCE() sf ^= (uint32_t)clock64()
__device__ __forceinline__ uint32_t gtime() { uint32_t c; asm volatile("mov.u32 %0, %%globaltimer_lo;" : "=r"(c)::"memory"); return c; }
__device__ __forceinline__ void wait_clk(uint32_t t0, uint32_t d) {
    asm volatile("{\n.reg .pred p;\n.reg .s32 t;\n.reg .b64 c;\nWL:\nmov.u64 c, %%clock64;\ncvt.u32.u64 t, c;\nsub.s32 t, t, %0;\nsetp.lt.s32 p, t, 0;\n@p bra.uni WL;\n}" ::"r"(t0 + d) : "memory");
}
__device__ __forceinline__ void wait_gtime(uint32_t t1) {
    asm volatile("{\n.reg .pred p;\n.reg .s32 t;\n.reg .b64 c;\nWL:\nmov.u64 c, %%globaltimer;\ncvt.u32.u64 t, c;\nsub.s32 t, t, %0;\nsetp.lt.s32 p, t, 0;\n@p bra.uni WL;\n}" ::"r"(t1) : "memory");
}

__device__ __forceinline__ void mbar_init(uint32_t bar, uint32_t cnt) {
    asm volatile("mbarrier.init.shared::cta.b64 [%0], %1;" ::"r"(bar), "r"(cnt) : "memory");
}
__device__ __forceinline__ void mbar_arrive(uint32_t bar) {
    asm volatile("mbarrier.arrive.shared::cta.b64 _, [%0];" ::"r"(bar) : "memory");
}
__device__ __forceinline__ void mbar_expect_tx(uint32_t bar, uint32_t bytes) {
    asm volatile("mbarrier.arrive.expect_tx.shared::cta.b64 _, [%0], %1;" ::"r"(bar), "r"(bytes) : "memory");
}
__device__ __forceinline__ void mbar_wait(uint32_t bar, uint32_t parity) {
    asm volatile(
        "{\n.reg .pred p, q;\n.reg .u32 n;\nmov.u32 n, 0;\n"
        "WL:\nmbarrier.try_wait.parity.shared::cta.b64 p, [%0], %1;\n"
        "add.u32 n, n, 1;\nsetp.gt.u32 q, n, %2;\n@q trap;\n@!p bra.uni WL;\n}" ::"r"(bar), "r"(parity), "n"(SPIN_LIMIT) : "memory");
}
__device__ __forceinline__ void mbar_wait_cluster(uint32_t bar, uint32_t parity) {
    asm volatile(
        "{\n.reg .pred p, q;\n.reg .u32 n;\nmov.u32 n, 0;\n"
        "WL:\nmbarrier.try_wait.parity.acquire.cluster.shared::cta.b64 p, [%0], %1;\n"
        "add.u32 n, n, 1;\nsetp.gt.u32 q, n, %2;\n@q trap;\n@!p bra.uni WL;\n}" ::"r"(bar), "r"(parity), "n"(SPIN_LIMIT) : "memory");
}
__device__ __forceinline__ void tma2d(uint32_t dst, const CUtensorMap* m, int c0, int c1, uint32_t bar) {
    asm volatile("cp.async.bulk.tensor.2d.shared::cluster.global.mbarrier::complete_tx::bytes [%0], [%1, {%3, %4}], [%2];"
                 ::"r"(dst), "l"(m), "r"(bar), "r"(c0), "r"(c1) : "memory");
}
__device__ __forceinline__ void tma4d(uint32_t dst, const CUtensorMap* m, int c2, int c3, uint32_t bar) {
    asm volatile("cp.async.bulk.tensor.4d.shared::cluster.global.mbarrier::complete_tx::bytes [%0], [%1, {%5, %5, %3, %4}], [%2];"
                 ::"r"(dst), "l"(m), "r"(bar), "r"(c2), "r"(c3), "r"(0) : "memory");
}
__device__ __forceinline__ void bulk_g2s(uint32_t dst, const void* src, uint32_t bytes, uint32_t bar) {
    asm volatile("cp.async.bulk.shared::cluster.global.mbarrier::complete_tx::bytes [%0], [%1], %2, [%3];"
                 ::"r"(dst), "l"(src), "r"(bytes), "r"(bar) : "memory");
}
__device__ __forceinline__ void tma4d_prefetch(const CUtensorMap* m, int c2, int c3) {
    asm volatile("cp.async.bulk.prefetch.tensor.4d.L2.global [%0, {%3, %3, %1, %2}];" ::"l"(m), "r"(c2), "r"(c3), "r"(0) : "memory");
}
__device__ __forceinline__ void tma2d_prefetch(const CUtensorMap* m, int c0, int c1) {
    asm volatile("cp.async.bulk.prefetch.tensor.2d.L2.global [%0, {%1, %2}];" ::"l"(m), "r"(c0), "r"(c1) : "memory");
}
__device__ __forceinline__ void fence_async_smem() { asm volatile("fence.proxy.async.shared::cta;" ::: "memory"); }
__device__ __forceinline__ void fence_gpu() { asm volatile("fence.acq_rel.gpu;" ::: "memory"); }
__device__ __forceinline__ float rcp(float x) { float r; asm("rcp.approx.ftz.f32 %0, %1;" : "=f"(r) : "f"(x)); return r; }
__device__ __forceinline__ void bar_sync(int id, int n) { asm volatile("bar.sync %0, %1;" ::"r"(id), "r"(n) : "memory"); }

__device__ __forceinline__ bool bar_or(int id, int n, uint32_t x) {
    uint32_t r;
    asm volatile("{\n.reg .pred p, q;\n.reg .b32 t;\nand.b32 t, %3, 1;\nsetp.ne.u32 p, t, 0;\nbar.red.or.pred q, %1, %2, p;\nselp.u32 %0, 1, 0, q;\n}"
                 : "=r"(r) : "r"(id), "r"(n), "r"(x) : "memory");
    return __any_sync(~0u, r);
}
__device__ __forceinline__ uint32_t or3(uint32_t a, uint32_t b, uint32_t c) {
    uint32_t r; asm("lop3.b32 %0, %1, %2, %3, 0xFE;" : "=r"(r) : "r"(a), "r"(b), "r"(c)); return r;
}
__device__ __forceinline__ uint32_t pack_bf16(float lo, float hi) {
    uint32_t r; asm("cvt.rn.bf16x2.f32 %0, %1, %2;" : "=r"(r) : "f"(hi), "f"(lo)); return r;
}
__device__ __forceinline__ uint32_t add_bf16x2(uint32_t a, uint32_t b) {
    uint32_t r; asm volatile("add.rn.bf16x2 %0, %1, %2;" : "=r"(r) : "r"(a), "r"(b)); return r;
}
__device__ __forceinline__ uint32_t movm(uint32_t a) {
    uint32_t r; asm volatile("movmatrix.sync.aligned.m8n8.trans.b16 %0, %1;" : "=r"(r) : "r"(a)); return r;
}
__device__ __forceinline__ uint32_t orx(uint32_t acc, uint32_t a, uint32_t t) {
    uint32_t r; asm("lop3.b32 %0, %1, %2, %3, 0xF6;" : "=r"(r) : "r"(acc), "r"(a), "r"(t)); return r;
}
__device__ __forceinline__ uint32_t orx2(uint32_t a, uint32_t b, uint32_t t) {
    uint32_t r; asm("lop3.b32 %0, %1, %2, %3, 0x7E;" : "=r"(r) : "r"(a), "r"(b), "r"(t)); return r;
}
__device__ __forceinline__ float ex2(float x) { float r; asm("ex2.approx.ftz.f32 %0, %1;" : "=f"(r) : "f"(x)); return r; }
__device__ __forceinline__ void ldsm4t(uint32_t (&r)[4], uint32_t a) {
    asm volatile("ldmatrix.sync.aligned.m8n8.x4.trans.shared.b16 {%0,%1,%2,%3}, [%4];"
                 : "=r"(r[0]), "=r"(r[1]), "=r"(r[2]), "=r"(r[3]) : "r"(a) : "memory");
}
__device__ __forceinline__ void ldsm4(uint32_t (&r)[4], uint32_t a) {
    asm volatile("ldmatrix.sync.aligned.m8n8.x4.shared.b16 {%0,%1,%2,%3}, [%4];"
                 : "=r"(r[0]), "=r"(r[1]), "=r"(r[2]), "=r"(r[3]) : "r"(a) : "memory");
}
__device__ __forceinline__ void stsm4t(uint32_t a, uint32_t r0, uint32_t r1, uint32_t r2, uint32_t r3) {
    asm volatile("stmatrix.sync.aligned.m8n8.x4.trans.shared.b16 [%0], {%1,%2,%3,%4};"
                 ::"r"(a), "r"(r0), "r"(r1), "r"(r2), "r"(r3) : "memory");
}
__device__ __forceinline__ void stsm4(uint32_t a, uint32_t r0, uint32_t r1, uint32_t r2, uint32_t r3) {
    asm volatile("stmatrix.sync.aligned.m8n8.x4.shared.b16 [%0], {%1,%2,%3,%4};"
                 ::"r"(a), "r"(r0), "r"(r1), "r"(r2), "r"(r3) : "memory");
}
__device__ __forceinline__ void mma16816(float* c, uint32_t a0, uint32_t a1, uint32_t a2, uint32_t a3, uint32_t b0, uint32_t b1) {
    asm volatile("mma.sync.aligned.m16n8k16.row.col.f32.bf16.bf16.f32 {%0,%1,%2,%3}, {%4,%5,%6,%7}, {%8,%9}, {%0,%1,%2,%3};"
                 : "+f"(c[0]), "+f"(c[1]), "+f"(c[2]), "+f"(c[3]) : "r"(a0), "r"(a1), "r"(a2), "r"(a3), "r"(b0), "r"(b1));
}
__device__ __forceinline__ void mma1688(float* c, uint32_t a0, uint32_t a1, uint32_t b0) {
    asm volatile("mma.sync.aligned.m16n8k8.row.col.f32.bf16.bf16.f32 {%0,%1,%2,%3}, {%4,%5}, {%6}, {%0,%1,%2,%3};"
                 : "+f"(c[0]), "+f"(c[1]), "+f"(c[2]), "+f"(c[3]) : "r"(a0), "r"(a1), "r"(b0));
}
__device__ __forceinline__ void sts128(uint32_t a, float x, float y, float z, float w) {
    asm volatile("st.shared.v4.f32 [%0], {%1,%2,%3,%4};" ::"r"(a), "f"(x), "f"(y), "f"(z), "f"(w) : "memory");
}
__device__ __forceinline__ void sts64(uint32_t a, float x, float y) {
    asm volatile("st.shared.v2.f32 [%0], {%1,%2};" ::"r"(a), "f"(x), "f"(y) : "memory");
}
__device__ __forceinline__ void sts32(uint32_t a, uint32_t x) { asm volatile("st.shared.b32 [%0], %1;" ::"r"(a), "r"(x) : "memory"); }
__device__ __forceinline__ void sts128u(uint32_t a, uint4 v) {
    asm volatile("st.shared.v4.b32 [%0], {%1,%2,%3,%4};" ::"r"(a), "r"(v.x), "r"(v.y), "r"(v.z), "r"(v.w) : "memory");
}
__device__ __forceinline__ float4 lds128(uint32_t a) {
    float4 v; asm volatile("ld.shared.v4.f32 {%0,%1,%2,%3}, [%4];" : "=f"(v.x), "=f"(v.y), "=f"(v.z), "=f"(v.w) : "r"(a) : "memory"); return v;
}
__device__ __forceinline__ uint4 lds128u(uint32_t a) {
    uint4 v; asm volatile("ld.shared.v4.b32 {%0,%1,%2,%3}, [%4];" : "=r"(v.x), "=r"(v.y), "=r"(v.z), "=r"(v.w) : "r"(a) : "memory"); return v;
}
__device__ __forceinline__ uint2 lds64u(uint32_t a) {
    uint2 v; asm volatile("ld.shared.v2.b32 {%0,%1}, [%2];" : "=r"(v.x), "=r"(v.y) : "r"(a) : "memory"); return v;
}
__device__ __forceinline__ float2 lds64(uint32_t a) {
    float2 v; asm volatile("ld.shared.v2.f32 {%0,%1}, [%2];" : "=f"(v.x), "=f"(v.y) : "r"(a) : "memory"); return v;
}
__device__ __forceinline__ uint2 ldg_rlx64(const void* p) {
    uint2 v; asm volatile("ld.relaxed.gpu.global.v2.b32 {%0,%1}, [%2];" : "=r"(v.x), "=r"(v.y) : "l"(p) : "memory"); return v;
}
__device__ __forceinline__ uint4 ldg_rlx128(const void* p) {
    uint4 v; asm volatile("ld.relaxed.gpu.global.v4.b32 {%0,%1,%2,%3}, [%4];" : "=r"(v.x), "=r"(v.y), "=r"(v.z), "=r"(v.w) : "l"(p) : "memory"); return v;
}
__device__ __forceinline__ void stg_rlx64(void* p, uint32_t x, uint32_t y) {
    asm volatile("st.relaxed.gpu.global.v2.b32 [%0], {%1,%2};" ::"l"(p), "r"(x), "r"(y) : "memory");
}
__device__ __forceinline__ void stg_rlx128(void* p, uint32_t x, uint32_t y, uint32_t z, uint32_t w) {
    asm volatile("st.relaxed.gpu.global.v4.b32 [%0], {%1,%2,%3,%4};" ::"l"(p), "r"(x), "r"(y), "r"(z), "r"(w) : "memory");
}
__device__ __forceinline__ uint32_t ldg_rlx32(const void* p) {
    uint32_t v; asm volatile("ld.relaxed.gpu.global.b32 %0, [%1];" : "=r"(v) : "l"(p) : "memory"); return v;
}
__device__ __forceinline__ void stg128(void* p, uint32_t x, uint32_t y, uint32_t z, uint32_t w) {
    asm volatile("st.global.v4.b32 [%0], {%1,%2,%3,%4};" ::"l"(p), "r"(x), "r"(y), "r"(z), "r"(w) : "memory");
}
__device__ __forceinline__ uint32_t ld_acquire(const unsigned* p) {
    uint32_t v; asm volatile("ld.acquire.gpu.global.u32 %0, [%1];" : "=r"(v) : "l"(p) : "memory"); return v;
}
__device__ __forceinline__ void red_add_u32(unsigned* p, uint32_t v) {
    asm volatile("red.relaxed.gpu.global.add.u32 [%0], %1;" ::"l"(p), "r"(v) : "memory");
}
__device__ __forceinline__ void wait_counter(const unsigned* p, uint32_t target) {
    uint32_t n = 0;
    while (ld_acquire(p) < target) { if (++n > SPIN_LIMIT) __trap(); }
}

__device__ __forceinline__ void wg_fence() { asm volatile("wgmma.fence.sync.aligned;" ::: "memory"); }
__device__ __forceinline__ void wg_commit() { asm volatile("wgmma.commit_group.sync.aligned;" ::: "memory"); }
template <int N> __device__ __forceinline__ void wg_wait() { asm volatile("wgmma.wait_group.sync.aligned %0;" ::"n"(N) : "memory"); }
__host__ __device__ constexpr uint64_t mkdesc(uint32_t addr, uint32_t lbo, uint32_t sbo, uint32_t swz) {
    return (uint64_t)((addr & 0x3FFFF) >> 4) | ((uint64_t)(lbo >> 4) << 16) | ((uint64_t)(sbo >> 4) << 32) | ((uint64_t)swz << 62);
}
#define F4(d, o) "+f"(d[o]), "+f"(d[o + 1]), "+f"(d[o + 2]), "+f"(d[o + 3])
template <int SC> __device__ __forceinline__ void wg_rs32(float (&d)[16], const uint32_t (&a)[4], uint64_t db) {
    asm volatile("wgmma.mma_async.sync.aligned.m64n32k16.f32.bf16.bf16 "
                 "{%0,%1,%2,%3,%4,%5,%6,%7,%8,%9,%10,%11,%12,%13,%14,%15}, {%16,%17,%18,%19}, %20, %21, 1, 1, 0;"
                 : F4(d, 0), F4(d, 4), F4(d, 8), F4(d, 12)
                 : "r"(a[0]), "r"(a[1]), "r"(a[2]), "r"(a[3]), "l"(db), "n"(SC));
}
template <int SC> __device__ __forceinline__ void wg_rs40(float (&d)[20], const uint32_t (&a)[4], uint64_t db) {
    asm volatile("wgmma.mma_async.sync.aligned.m64n40k16.f32.bf16.bf16 "
                 "{%0,%1,%2,%3,%4,%5,%6,%7,%8,%9,%10,%11,%12,%13,%14,%15,%16,%17,%18,%19}, {%20,%21,%22,%23}, %24, %25, 1, 1, 0;"
                 : F4(d, 0), F4(d, 4), F4(d, 8), F4(d, 12), F4(d, 16)
                 : "r"(a[0]), "r"(a[1]), "r"(a[2]), "r"(a[3]), "l"(db), "n"(SC));
}
template <int SC> __device__ __forceinline__ void wg_ss40(float (&d)[20], uint64_t da, uint64_t db) {
    asm volatile("wgmma.mma_async.sync.aligned.m64n40k16.f32.bf16.bf16 "
                 "{%0,%1,%2,%3,%4,%5,%6,%7,%8,%9,%10,%11,%12,%13,%14,%15,%16,%17,%18,%19}, %20, %21, %22, 1, 1, 1, 0;"
                 : F4(d, 0), F4(d, 4), F4(d, 8), F4(d, 12), F4(d, 16)
                 : "l"(da), "l"(db), "n"(SC));
}
template <int SC> __device__ __forceinline__ void wg_ss8(float (&d)[4], uint64_t da, uint64_t db) {
    asm volatile("wgmma.mma_async.sync.aligned.m64n8k16.f32.bf16.bf16 {%0,%1,%2,%3}, %4, %5, %6, 1, 1, 1, 1;"
                 : F4(d, 0) : "l"(da), "l"(db), "n"(SC));
}

__device__ uint4 g_fy[2048 * 128];

constexpr uint32_t FT_F16 = 0, FT_B1F = 2048, FT_B1I = 4096, FT_C = 6144, FT_A8 = 8192, FT_TWC = 8704, FT_TWB = FT_TWC + 8192,
                   FT_SIZE = FT_TWB + 16384;
constexpr uint32_t FW_PITCH = 1168, FG_SIZE = 32768 + 32 * FW_PITCH;

__device__ __forceinline__ float2 wroot(int e) {
    float s, c; sincospif((float)(e & 2047) * (-1.f / 1024.f), &s, &c); return make_float2(c, s);
}
__device__ __forceinline__ float2 wroot_fast(int e) {
    float s, c; __sincosf((float)(((e + 1024) & 2047) - 1024) * (-3.14159265358979f / 1024.f), &s, &c); return make_float2(c, s);
}
__device__ __forceinline__ uint4 afrag(float2 a, float2 b) {
    return make_uint4(pack_bf16(a.x, -a.y), pack_bf16(a.y, a.x), pack_bf16(b.x, -b.y), pack_bf16(b.y, b.x));
}
__device__ __forceinline__ uint4 conjfrag(uint4 v) { return make_uint4(v.x ^ 0x80000000u, v.y ^ 0x8000u, v.z ^ 0x80000000u, v.w ^ 0x8000u); }
__device__ __forceinline__ uint4 negfrag(uint4 v) { return make_uint4(v.x ^ 0x80008000u, v.y ^ 0x80008000u, v.z ^ 0x80008000u, v.w ^ 0x80008000u); }
__device__ __forceinline__ uint32_t comp(const uint4& v, int i) { return i == 0 ? v.x : i == 1 ? v.y : i == 2 ? v.z : v.w; }
__device__ __forceinline__ void setcomp(uint4& v, int i, uint32_t x) { if (i == 0) v.x = x; else if (i == 1) v.y = x; else if (i == 2) v.z = x; else v.w = x; }
__device__ __forceinline__ float2 cmul(float2 a, float2 b) { return make_float2(a.x * b.x - a.y * b.y, a.x * b.y + a.y * b.x); }
__device__ __forceinline__ float2 cmulc(float2 a, float2 b) { return make_float2(a.x * b.x + a.y * b.y, a.y * b.x - a.x * b.y); }

__device__ __forceinline__ void fft_tables(uint32_t tb, int tid, int nthr) {
    for (int i = tid; i < 128; i += nthr) {
        const int lane = i & 31, q = i >> 5, g = lane >> 2, t = lane & 3, o = 8 * (q >> 1) + g, in = 8 * (q & 1) + t;
        sts128u(tb + FT_F16 + i * 16, afrag(wroot(128 * o * in), wroot(128 * o * (in + 4))));
        sts128u(tb + FT_B1F + i * 16, afrag(wroot(64 * (1 + 2 * o) * in), wroot(64 * (1 + 2 * o) * (in + 4))));
        sts128u(tb + FT_B1I + i * 16, afrag(wroot(-64 * o * (1 + 2 * in)), wroot(-64 * o * (1 + 2 * (in + 4)))));
        uint4 v;
        for (int r = 0; r < 4; r++) {
            const float2 a = wroot(128 * (4 * t + r) * (4 * (g >> 1) + q));
            setcomp(v, r, (g & 1) ? pack_bf16(a.y, a.x) : pack_bf16(a.x, -a.y));
        }
        sts128u(tb + FT_C + i * 16, v);
        if (q == 0) sts128u(tb + FT_A8 + lane * 16, afrag(wroot(256 * g * t), wroot(256 * g * (t + 4))));
    }
    for (int i = tid; i < 512; i += nthr) {
        const int lane = i & 31, r = (i >> 5) & 3, phi = 8 * (i >> 7) + (lane >> 2), c = 4 * (lane & 3) + r;
        const float2 a = wroot(4 * c * phi), b = wroot(2 * (phi + 32 * c));
        sts128(tb + FT_TWC + i * 16, a.x, a.y, b.x, b.y);
    }
    for (int i = tid; i < 1024; i += nthr) {
        const int lane = i & 31, r = (i >> 5) & 3, mt = (i >> 7) & 1, fa = (i >> 8) & 1, hf = i >> 9;
        const int phi = fa + 2 * (8 * mt + (lane >> 2)), psi = (hf && phi) ? phi - 32 : phi, c = 8 * (lane & 1) + r;
        const float2 a = wroot(4 * c * psi), b = wroot(4 * (c + 4) * psi);
        sts128(tb + FT_TWB + i * 16, a.x, a.y, b.x, b.y);
    }
}

template <bool TW>
__device__ __forceinline__ void dft16(uint4 (&out)[4], const uint4 (&in)[4], const uint4 (&m)[4], uint32_t twa, uint32_t cj) {
#pragma unroll
    for (int i = 0; i < 4; i++)
#pragma unroll
        for (int mt = 0; mt < 2; mt++) {
            float c[4] = {0.f, 0.f, 0.f, 0.f};
            mma16816(c, m[2 * mt].x, m[2 * mt].y, m[2 * mt].z, m[2 * mt].w, comp(in[0], i), comp(in[1], i));
            mma16816(c, m[2 * mt + 1].x, m[2 * mt + 1].y, m[2 * mt + 1].z, m[2 * mt + 1].w, comp(in[2], i), comp(in[3], i));
            if (TW) {
                const float4 tw = lds128(twa + (mt * 4 + i) * 512);
                const float2 a = cmul(make_float2(c[0], c[2]), make_float2(tw.x, tw.y)), b = cmul(make_float2(c[1], c[3]), make_float2(tw.z, tw.w));
                setcomp(out[2 * mt], i, pack_bf16(a.x, a.y) ^ cj);
                setcomp(out[2 * mt + 1], i, pack_bf16(b.x, b.y) ^ cj);
            } else {
                setcomp(out[2 * mt], i, pack_bf16(c[0], c[2]));
                setcomp(out[2 * mt + 1], i, pack_bf16(c[1], c[3]));
            }
        }
}

template <bool INV>
__device__ __forceinline__ void fft_col(int item, const uint4* __restrict__ src, int sp, uint4* __restrict__ dst, int dp,
                                        uint32_t tb, uint32_t buf, int w, int lane, int bar) {
    const int s2 = item >> 4, cb = (item & 15) * 8, g = lane >> 2, t = lane & 3;
    uint4 in[2][4], f[4], m[4], out[4];
#pragma unroll
    for (int q = 0; q < 2; q++)
#pragma unroll
        for (int i = 0; i < 4; i++) {
            const uint4* p = src + (size_t)((16 * (t + 4 * i) + 2 * w + q) * 8 + s2) * sp + cb + g;
            in[q][i] = INV ? __ldcg(p) : __ldg(p);
        }
#pragma unroll
    for (int i = 0; i < 4; i++) { f[i] = lds128u(tb + FT_F16 + i * 512 + lane * 16); if (INV) f[i] = conjfrag(f[i]); }
#pragma unroll
    for (int q = 0; q < 2; q++) {
        const int u = 2 * w + q;
        if (INV) {
#pragma unroll
            for (int i = 0; i < 4; i++) {
                const int a = -(8 * (8 * (i >> 1) + g) + s2), b = u + 16 * (8 * (i & 1) + t);
                m[i] = afrag(wroot_fast(a * b), wroot_fast(a * (b + 64)));
            }
            dft16<false>(out, in[q], m, 0, 0);
        } else dft16<false>(out, in[q], f, 0, 0);
#pragma unroll
        for (int i = 0; i < 4; i++)
            sts128u(buf + ((8 * (i >> 1) + g) * 16 + u) * 128 + (((2 * t + (i & 1)) ^ (((u & 3) << 1) | (g & 1))) << 4), out[i]);
    }
    bar_sync(bar, 256);
#pragma unroll
    for (int q = 0; q < 2; q++)
#pragma unroll
        for (int i = 0; i < 4; i++) in[q][i] = lds128u(buf + ((2 * w + q) * 16 + t + 4 * i) * 128 + ((g ^ ((t << 1) | q)) << 4));
    bar_sync(bar, 256);
#pragma unroll
    for (int q = 0; q < 2; q++) {
        const int v = 2 * w + q;
        if (!INV) {
#pragma unroll
            for (int i = 0; i < 4; i++) {
                const int a = v + 16 * (8 * (i >> 1) + g), b = 8 * (8 * (i & 1) + t) + s2;
                m[i] = afrag(wroot_fast(a * b), wroot_fast(a * (b + 32)));
            }
            dft16<false>(out, in[q], m, 0, 0);
        } else dft16<false>(out, in[q], f, 0, 0);
#pragma unroll
        for (int i = 0; i < 4; i++) dst[(size_t)((16 * (8 * (i >> 1) + g) + v) * 8 + s2) * dp + cb + 2 * t + (i & 1)] = out[i];
    }
}

__device__ __forceinline__ uint32_t p2addr(int hf, int k2, int fa, int b, int c4) {
    const int sw = (k2 & 1) | (b & 2) | ((fa & ~hf & 1) << 2);
    return (uint32_t)((((hf * 8 + k2) * 2 + fa) * 8 + (b >> 1)) * 128 + (((((b & 1) << 2) | c4) ^ sw) << 4));
}
__device__ __forceinline__ float ldw(uint32_t row, int pos) {
    uint16_t v; asm volatile("ld.shared.u16 %0, [%1];" : "=h"(v) : "r"(row + pos + ((pos >> 8) << 5)) : "memory");
    return __uint_as_float((uint32_t)v << 16);
}

__device__ __forceinline__ void fft_mid(int k1, const unsigned char* __restrict__ wr, const unsigned char* __restrict__ wi,
                                        uint32_t tb, uint32_t buf, int w, int lane, int bar) {
    const int g = lane >> 2, t = lane & 3, k1b = (256 - k1) & 255;
    const uint32_t wb = buf + 32768;
    uint4 in[2][4], m[4], out[4];
#pragma unroll
    for (int q = 0; q < 2; q++)
#pragma unroll
        for (int i = 0; i < 4; i++) in[q][i] = __ldcg(&g_fy[((q ? k1b : k1) * 8 + t + 4 * (i & 1)) * 128 + (i >> 1) * 64 + w * 8 + g]);
#pragma unroll
    for (int r = 0; r < 4; r++) {
        const unsigned char* p = ((r & 1) ? wi : wr) + ((((r >> 1) ? k1b : k1) + 256 * w) * 1026 & ~15);
        const uint32_t d = wb + (r * 8 + w) * FW_PITCH;
#pragma unroll
        for (int c = lane; c < 65; c += 32)
            asm volatile("cp.async.cg.shared.global [%0], [%1], 16;" ::"r"(d + c * 16 + (c >> 4) * 32), "l"(p + c * 16) : "memory");
    }
    asm volatile("cp.async.commit_group;" ::: "memory");
    m[0] = m[1] = m[2] = lds128u(tb + FT_A8 + lane * 16);
    m[3] = negfrag(m[0]);
#pragma unroll
    for (int q = 0; q < 2; q++) {
        dft16<false>(out, in[q], m, 0, 0);
#pragma unroll
        for (int i = 0; i < 4; i++) sts128u(buf + p2addr(q, g, i >> 1, 2 * w + (t >> 1), 2 * (t & 1) + (i & 1)), out[i]);
    }
    bar_sync(bar, 256);
    const int hB = w >> 2, faB = (w >> 1) & 1;
#pragma unroll
    for (int i = 0; i < 4; i++) m[i] = lds128u(tb + (faB ? FT_B1F : FT_F16) + i * 512 + lane * 16);
#pragma unroll
    for (int q = 0; q < 2; q++) {
        const int kp = 4 * (w & 1) + 2 * q;
#pragma unroll
        for (int i = 0; i < 4; i++) in[0][i] = lds128u(buf + p2addr(hB, kp + (g >> 2), faB, t + 4 * i, g & 3));
        dft16<true>(out, in[0], m, tb + FT_TWB + (w >> 1) * 4096 + lane * 16, hB ? 0x80000000u : 0u);
        __syncwarp();
#pragma unroll
        for (int i = 0; i < 4; i++) sts128u(buf + p2addr(hB, kp + (t >> 1), faB, 8 * (i >> 1) + g, 2 * (t & 1) + (i & 1)), out[i]);
    }
    asm volatile("cp.async.wait_group 0;" ::: "memory");
    bar_sync(bar, 256);
    {
        const int phi = 8 * (w & 3) + g, php = (32 - phi) & 31;
        const uint32_t cjm = (g & 1) ? 0x8000u : 0x80000000u;
        float4 tw[4];
#pragma unroll
        for (int i = 0; i < 4; i++) { m[i] = lds128u(tb + FT_C + i * 512 + lane * 16); tw[i] = lds128(tb + FT_TWC + ((w & 3) * 4 + i) * 512 + lane * 16); }
        const int o0 = (2 * k1) & 15, o1 = (2 * k1b) & 15;
#pragma unroll 1
        for (int q = 0; q < 4; q++) {
            const int k2 = 4 * (w >> 2) + q, k2p = k1 ? 7 - k2 : (8 - k2) & 7;
            const uint32_t a0 = buf + p2addr(0, k2, phi & 1, phi >> 1, t), a1 = buf + p2addr(1, k2p, php & 1, php >> 1, t);
            const uint32_t r0 = wb + k2 * FW_PITCH, r1 = wb + (16 + k2p) * FW_PITCH;
            uint4 x = lds128u(a0), y = lds128u(a1), x2, y2;
#pragma unroll
            for (int i = 0; i < 4; i++) {
                float c[4] = {0.f, 0.f, 0.f, 0.f};
                mma16816(c, x.x, y.x, x.y, y.y, m[i].x, m[i].y);
                mma16816(c, x.z, y.z, x.w, y.w, m[i].z, m[i].w);
                const int f = phi + 32 * (4 * t + i);
                float2 g1 = make_float2(ldw(r0, o0 + 2 * f), ldw(r0 + 8 * FW_PITCH, o0 + 2 * f));
                float2 g2 = make_float2(ldw(r1, o1 + 1024 - 2 * f), ldw(r1 + 8 * FW_PITCH, o1 + 1024 - 2 * f));
                if (i == 0 && f == 0) {
                    g1.x = 0.5f * (g1.x + ldw(r1, o1)); g1.y = 0.5f * (g1.y - ldw(r1 + 8 * FW_PITCH, o1));
                    g2.x = 0.5f * (g2.x + ldw(r0, o0 + 1024)); g2.y = 0.5f * (g2.y - ldw(r0 + 8 * FW_PITCH, o0 + 1024));
                }
                constexpr float SC = 1.f / (4.f * 2048.f * 512.f);
                const float2 tau = make_float2(tw[i].z, tw[i].w);
                const float2 e = make_float2((c[0] + c[2]) * SC, (c[1] + c[3]) * SC);
                const float2 o = cmul(make_float2((c[1] - c[3]) * SC, (c[2] - c[0]) * SC), tau);
                const float2 y1 = cmul(make_float2(e.x + o.x, e.y + o.y), g1), yb = cmulc(make_float2(e.x - o.x, e.y - o.y), g2);
                const float2 e2 = make_float2(y1.x + yb.x, y1.y + yb.y), o2 = cmulc(make_float2(yb.y - y1.y, y1.x - yb.x), tau);
                setcomp(x2, i, pack_bf16(e2.x + o2.x, e2.y + o2.y));
                setcomp(y2, i, pack_bf16(e2.x - o2.x, e2.y - o2.y));
            }
#pragma unroll
            for (int i = 0; i < 4; i++) {
                float c[4] = {0.f, 0.f, 0.f, 0.f};
                mma16816(c, x2.x, y2.x, x2.y, y2.y, m[i].x ^ cjm, m[i].y ^ cjm);
                mma16816(c, x2.z, y2.z, x2.w, y2.w, m[i].z ^ cjm, m[i].w ^ cjm);
                const float2 a = cmulc(make_float2(c[0], c[1]), make_float2(tw[i].x, tw[i].y)), b = cmulc(make_float2(c[2], c[3]), make_float2(tw[i].x, tw[i].y));
                setcomp(x, i, pack_bf16(a.x, a.y));
                setcomp(y, i, pack_bf16(b.x, -b.y));
            }
            sts128u(a0, x);
            sts128u(a1, y);
        }
    }
    bar_sync(bar, 256);
#pragma unroll
    for (int i = 0; i < 4; i++) { m[i] = lds128u(tb + (faB ? FT_B1I : FT_F16) + i * 512 + lane * 16); if (!faB) m[i] = conjfrag(m[i]); }
#pragma unroll
    for (int q = 0; q < 2; q++) {
        const int kp = 4 * (w & 1) + 2 * q;
#pragma unroll
        for (int i = 0; i < 4; i++) in[0][i] = lds128u(buf + p2addr(hB, kp + (g >> 2), faB, t + 4 * i, g & 3));
        dft16<false>(out, in[0], m, 0, 0);
        __syncwarp();
#pragma unroll
        for (int i = 0; i < 4; i++) sts128u(buf + p2addr(hB, kp + (t >> 1), faB, 8 * (i >> 1) + g, 2 * (t & 1) + (i & 1)), out[i]);
    }
    bar_sync(bar, 256);
#pragma unroll
    for (int q = 0; q < 2; q++)
#pragma unroll
        for (int i = 0; i < 4; i++) in[q][i] = lds128u(buf + p2addr(q, t + 4 * (i & 1), i >> 1, 2 * w + (g >> 2), g & 3));
    bar_sync(bar, 256);
    m[0] = m[1] = m[2] = conjfrag(lds128u(tb + FT_A8 + lane * 16));
    m[3] = negfrag(m[0]);
#pragma unroll
    for (int q = 0; q < 2; q++) {
        if (q == 1 && k1b == k1) break;
        dft16<false>(out, in[q], m, 0, 0);
#pragma unroll
        for (int i = 0; i < 4; i++) g_fy[((q ? k1b : k1) * 8 + g) * 128 + (i >> 1) * 64 + w * 8 + 2 * t + (i & 1)] = out[i];
    }
}

template <int PASS>
__global__ void __launch_bounds__(256) fft_pass(const uint4* __restrict__ x, const unsigned char* __restrict__ wr,
                                                const unsigned char* __restrict__ wi, uint4* __restrict__ out) {
    extern __shared__ __align__(1024) unsigned char smem_raw[];
    const uint32_t tb = smem_u32(smem_raw), buf = tb + FT_SIZE;
    fft_tables(tb, threadIdx.x, 256);
    __syncthreads();
    const int w = threadIdx.x >> 5, lane = threadIdx.x & 31;
    if (PASS == 0) fft_col<false>(blockIdx.x, x, 128, g_fy, 128, tb, buf, w, lane, 1);
    if (PASS == 1) fft_mid(blockIdx.x, wr, wi, tb, buf, w, lane, 1);
    if (PASS == 2) fft_col<true>(blockIdx.x, g_fy, 128, out, 256, tb, buf, w, lane, 1);
}

__device__ uint4 g_kvq[4 * 32 * 3 * 8 * 2 * 32];
__device__ uint2 g_alpha[2 * 32 * 3 * 8 * 2 * 32];
__device__ uint4 g_red[5 * 32768 / 16];
__device__ uint4 g_stamp[32];
__device__ uint4 g_qst[128 * 2];
__device__ unsigned g_start;
__device__ bf16 g_ox[2048 * 4096];
constexpr int DBG_N = 12;
#define TSI(st) do {} while (0)
#define TS(k) do {} while (0)
#define TSV(k, v) do {} while (0)
#define TSDUMP() do {} while (0)
#define GT(k) do {} while (0)
#define FLAG(b) false

struct Tune { uint32_t d_alpha, d_r0, d_r1, flags, d_st, d_v, spread, extra; };
#define QKW_EARLY 1
constexpr int RA = 2;
#define AV_POS 2

constexpr uint32_t SM_BASE = 1024;
constexpr uint32_t O_WO = 0;
constexpr uint32_t O_WV = 65536;
constexpr uint32_t O_XB = 131072;
constexpr uint32_t O_MEM = O_XB + 32768;
constexpr uint32_t O_RECV = O_MEM + 8192;
constexpr uint32_t O_KVQ = O_RECV + 12288;
constexpr uint32_t O_STG = O_KVQ + 18432;
constexpr uint32_t O_S = O_STG + 8192;
constexpr uint32_t O_XO = O_STG + 16384;
constexpr uint32_t O_P = O_S + 10240;
constexpr uint32_t O_O = O_P + 1536;
constexpr uint32_t O_VM = O_O + 2048;
constexpr uint32_t O_QST = O_VM + 2048;
constexpr uint32_t O_BAR = O_QST + 128;
constexpr uint32_t O_DBG = O_BAR + 256;
constexpr uint32_t MAIN_SMEM = O_DBG + (DBG_TIMING ? 4 * DBG_N * 24 * 4 : 0);
enum { B_WQ0 = 0, B_WQ1, B_WK0, B_WK1, B_WV, B_WO, B_QDONE, B_KDONE, B_XFULL, B_XEMPTY, B_MEM, B_RFULL, B_AFULL, B_KVFULL,
       B_RECV, B_QKW = B_RECV + 6, B_SDONE, B_SRDY, B_OPDONE, B_COUNT };

constexpr float SM_SCALE_LOG2 = 0.08838834764831845f * 1.4426950408889634f;
constexpr float MASK_VAL = -1.0e9f / 0.08838834764831845f;

__device__ __forceinline__ uint32_t red_grp(int grp) { return (uint32_t)((grp >> 1) * 1024 + (grp & 1) * 256); }
__host__ __device__ constexpr uint64_t xdesc(int ks) { return mkdesc(SM_BASE + O_XB + (ks >> 2) * 1024 + (ks & 3) * 32, 16, 8192, 1); }

__device__ __forceinline__ void x_split(const float* d, uint32_t (&sn)[4], uint32_t (&kp)[4], int kh) {
#pragma unroll
    for (int i = 0; i < 4; i++) {
        const uint32_t lo = pack_bf16(d[2 * i], d[2 * i + 1]), hi = pack_bf16(d[8 + 2 * i], d[8 + 2 * i + 1]);
        sn[i] = kh ? lo : hi; kp[i] = kh ? hi : lo;
    }
}
__device__ __forceinline__ void x_send(int R, const uint32_t (&sn)[4], int sg, int tid, uint32_t sb, uint32_t mate) {
    const uint32_t par = sg & 1;
    const uint32_t bar = O_BAR + 8 * (B_RECV + R * 2) + 8 * par;
    if (tid == 0) mbar_expect_tx(sb + bar, 2048);
    asm volatile("st.async.shared::cluster.mbarrier::complete_tx::bytes.v4.b32 [%0], {%1,%2,%3,%4}, [%5];"
                 ::"r"(mate + O_RECV + (par * 3 + R) * 2048 + tid * 16), "r"(sn[0]), "r"(sn[1]), "r"(sn[2]), "r"(sn[3]), "r"(mate + bar) : "memory");
}
__device__ __forceinline__ void x_wait(int R, int sg, uint32_t sb) {
    mbar_wait_cluster(sb + O_BAR + 8 * (B_RECV + R * 2) + 8 * (sg & 1), (sg >> 1) & 1);
}
template <int R>
__device__ __forceinline__ void x_finish(const uint32_t (&kp)[4], int sg, int h, int mt, int kh, int tid, uint32_t sb) {
    const uint4 r = lds128u(sb + O_RECV + ((sg & 1) * 3 + R) * 2048 + tid * 16);
    uint32_t u0 = add_bf16x2(kp[0], r.x), u1 = add_bf16x2(kp[1], r.y), u2 = add_bf16x2(kp[2], r.z), u3 = add_bf16x2(kp[3], r.w);
    if (R < 2) { u0 = movm(u0); u1 = movm(u1); u2 = movm(u2); u3 = movm(u3); }
    const uint32_t tag = ((sg >> 2) & 1) ^ 1;
    u0 = (u0 & ~1u) | tag;
    uint4* const hb = &g_kvq[((sg & 3) * 32 + h) * (3 * 512)];
    if (R == 0) {
        uint2* p = (uint2*)hb + (kh * 16 + mt) * 32 + (tid & 31);
        asm volatile("{\n.reg .pred p;\nsetp.lt.s32 p, %5, 64;\n@p st.relaxed.gpu.global.v2.b32 [%0], {%1,%2};\n@p st.relaxed.gpu.global.v2.b32 [%0+2048], {%3,%4};\n}"
                     ::"l"(p), "r"(u0), "r"(u1), "r"((u2 & ~1u) | tag), "r"(u3), "r"(sg) : "memory");
    } else {
        asm volatile("{\n.reg .pred p;\nsetp.lt.s32 p, %5, 64;\n@p st.relaxed.gpu.global.v4.b32 [%0], {%1,%2,%3,%4};\n}"
                     ::"l"(hb + R * 512 + (mt * 2 + kh) * 32 + (tid & 31)), "r"(u0), "r"(u1), "r"(u2), "r"(u3), "r"(sg) : "memory");
    }
}

__device__ __forceinline__ uint32_t convert_mem(const unsigned char* redp, int s, int kh, int jj, int w, int lane, uint32_t sb) {
    const uint32_t off = red_grp(jj * 16 + w * 4 + (lane >> 3)), o16 = off + (lane & 7) * 16, o8 = off + 512 + ((lane >> 3) & 1) * 64 + (lane & 7) * 8;
    uint32_t ma = sb + O_MEM + (jj * 4 + (lane >> 4)) * 1024 + (lane & 7) * 128 + (((2 * w + ((lane >> 3) & 1)) ^ (lane & 7)) << 4);
    uint32_t a16 = sb + O_STG + o16, a8 = sb + O_STG + o8;
    const uint32_t target = (s & 4) ? 0x42C00000u : 0x42000000u;
    asm volatile("" : "+r"(ma), "+r"(a16), "+r"(a8));
    mbar_wait(sb + O_BAR + 8 * B_RFULL, s & 1);
    uint4 ra = lds128u(a16), rb = lds128u(a16 + 128);
    uint2 rc = lds64u(a8);
    uint32_t n = 0;
    while (true) {
        stsm4t(ma, ra.x, ra.y, ra.z, __byte_perm(ra.w, rc.x, 0x5410));
        stsm4t(ma + 2048, rb.x, rb.y, rb.z, __byte_perm(rb.w, rc.x, 0x7610));
        if (__builtin_expect(!__any_sync(~0u, orx(orx2(ra.w, rb.w, target), rc.y, target) > 0xffffu), 1)) break;
        const unsigned char* pg = redp + (s & 3) * 32768 + kh * 16384;
        ra = ldg_rlx128(pg + o16); rb = ldg_rlx128(pg + o16 + 128); rc = ldg_rlx64(pg + o8);
        if (++n > SPIN_LIMIT) __trap();
    }
    __syncwarp();
    if (lane == 0) mbar_arrive(sb + O_BAR + 8 * B_MEM);
    fence_async_smem();
    __syncwarp();
    if (lane == 0) mbar_arrive(sb + O_BAR + 8 * B_QKW);
    return n;
}

__global__ void __cluster_dims__(2, 1, 1) __launch_bounds__(512, 1)
rmt_main(const __grid_constant__ CUtensorMap tm_x, const __grid_constant__ CUtensorMap tm_wq, const __grid_constant__ CUtensorMap tm_wk,
         const __grid_constant__ CUtensorMap tm_wv, const __grid_constant__ CUtensorMap tm_wo, const bf16* __restrict__ mem0, const Tune tn) {
    extern __shared__ __align__(1024) unsigned char smem_raw[];
    const uint32_t sb = smem_u32(smem_raw);
    if ((sb & 0x3FFFF) != SM_BASE) __trap();
    const int cid = blockIdx.x >> 1, kh = blockIdx.x & 1;
    const int tpc = cid < 4 ? 62 + cid : cid - 4;
    int h, nh;
    if (tpc < 32) { h = (tpc >> 4) * 8 + (tpc & 7); nh = (tpc >> 3) & 1; }
    else if (tpc < 60) { int u = tpc - 32, r = u % 14; h = 16 + (u / 14) * 7 + r % 7; nh = r / 7; }
    else if (tpc < 62) return;
    else { h = 30 + ((tpc - 62) >> 1); nh = tpc & 1; }
    const int j = nh * 2 + kh, role = h * 4 + j;
    const int wgi = __shfl_sync(~0u, threadIdx.x >> 7, 0);
    const int w = __shfl_sync(~0u, (threadIdx.x >> 5) & 3, 0);
    const int tid = threadIdx.x & 127, lane = tid & 31;
#define OPAQUE_IDS() int tid_ = tid; asm volatile("" : "+r"(tid_)); const int tid = tid_, lane = tid_ & 31; (void)lane
    unsigned char* const redp = (unsigned char*)(((uintptr_t)g_red + 32767) & ~(uintptr_t)32767);
    const uint32_t bars = sb + O_BAR;

    if (threadIdx.x == 0) {
        const uint8_t cnts[B_COUNT] = {1, 1, 1, 1, 1, 1, 4, 4, 1, 12, 8, 1, 1, 1, 1, 1, 1, 1, 1, 1, 16, 4, 4, 4};
#pragma unroll
        for (int i = 0; i < B_COUNT; i++) mbar_init(bars + 8 * i, cnts[i]);
        asm volatile("fence.mbarrier_init.release.cluster;" ::: "memory");
        fence_async_smem();
        const int c0 = h * 128 + nh * 64, r0 = kh * 512;
        for (int i = 0; i < 2; i++) {
            mbar_expect_tx(bars + 8 * (B_WK0 + i), 32768);
            tma2d(sb + O_XB + i * 32768, &tm_wk, c0, r0 + i * 256, bars + 8 * (B_WK0 + i));
            mbar_expect_tx(bars + 8 * (B_WQ0 + i), 32768);
            tma2d(sb + O_WO + i * 32768, &tm_wq, c0, r0 + i * 256, bars + 8 * (B_WQ0 + i));
        }
        mbar_expect_tx(bars + 8 * B_WV, 65536);
        for (int i = 0; i < 2; i++) tma2d(sb + O_WV + i * 32768, &tm_wv, c0, r0 + i * 256, bars + 8 * B_WV);
        for (int i = 0; i < 4; i++) tma2d_prefetch(&tm_wo, j * 256 + i * 64, h * 128);
        tma4d_prefetch(&tm_x, kh * 8, (role >> 1) * 4);
    }
    __syncthreads();
    uint32_t mate;
    asm volatile("mapa.shared::cluster.u32 %0, %1, %2;" : "=r"(mate) : "r"(sb), "r"(kh ^ 1));

    if (wgi < 2) {
        asm volatile("setmaxnreg.inc.sync.aligned.u32 176;");
        uint32_t a[32][4];
        {
            const uint32_t stage = sb + (wgi == 0 ? O_WO : O_XB);
            const uint32_t ad = stage + (((lane >> 4) & 1) * 8 + (lane & 7)) * 128 + (((2 * w + ((lane >> 3) & 1)) ^ (lane & 7)) << 4);
#pragma unroll
            for (int i = 0; i < 2; i++) {
                mbar_wait(bars + 8 * (B_WQ0 + 2 * wgi + i), 0);
#pragma unroll
                for (int ks = 0; ks < 16; ks++) ldsm4t(a[i * 16 + ks], ad + (i * 16 + ks) * 2048);
            }
            __syncwarp();
            if (lane == 0) mbar_arrive(bars + 8 * (B_QDONE + wgi));
        }
        asm volatile("barrier.cluster.arrive.release.aligned;" ::: "memory");
        asm volatile("barrier.cluster.wait.acquire.aligned;" ::: "memory");
        uint32_t kp[4], sf = 0;
#define X_PASS(d)                                                                                          \
        wg_fence();                                                                                        \
        _Pragma("unroll") for (int ks = 0; ks < 32; ks++) { if (ks == 0) wg_rs32<0>(d, a[ks], xdesc(ks)); else wg_rs32<1>(d, a[ks], xdesc(ks)); } \
        wg_commit();                                                                                       \
        wg_wait<0>();
#define QK_LOOP(R)                                                                                         \
        _Pragma("unroll 1") for (int sg = 0; sg < RA; sg++) {                                              \
            float d[16]; uint32_t sn[4];                                                                   \
            if (sg > 0) { x_wait(R, sg - 1, sb); x_finish<R>(kp, sg - 1, h, nh * 4 + w, kh, tid, sb); }    \
            mbar_wait(bars + 8 * B_XFULL, sg & 1);                                                         \
            X_PASS(d);                                                                                     \
            x_split(d, sn, kp, kh);                                                                        \
            x_send(R, sn, sg, tid, sb, mate);                                                              \
            if (lane == 0) mbar_arrive(bars + 8 * B_XEMPTY);                                               \
        }                                                                                                  \
        _Pragma("unroll 1") for (int s = 0; s < 64; s++) {                                                 \
            TSI(s);                                                                                        \
            {                                                                                              \
                float d[16]; uint32_t sn[4], kc[4];                                                        \
                x_wait(R, s + RA - 1, sb);                                                                 \
                mbar_wait(bars + 8 * B_XFULL, (s + RA) & 1);                                               \
                mbar_wait(bars + 8 * B_OPDONE, s & 1);                                                     \
                if (R == 1) { x_finish<R>(kp, s + RA - 1, h, nh * 4 + w, kh, tid, sb); TS(5); }            \
                TS(6);                                                                                     \
                X_PASS(d);                                                                                 \
                TS(7);                                                                                     \
                x_split(d, sn, kc, kh);                                                                    \
                x_send(R, sn, s + RA, tid, sb, mate);                                                      \
                if (lane == 0) mbar_arrive(bars + 8 * B_XEMPTY);                                           \
                TS(4);                                                                                     \
                if (R == 0) { x_finish<R>(kp, s + RA - 1, h, nh * 4 + w, kh, tid, sb); TS(5); }            \
                _Pragma("unroll") for (int i = 0; i < 4; i++) kp[i] = kc[i];                               \
            }                                                                                              \
            uint2* ap = &g_alpha[((s & 1) * 32 + h) * (3 * 512) + R * 512 + ((nh * 4 + w) * 2 + kh) * 32 + lane]; \
            uint32_t mb0 = sb + O_MEM + (lane & 7) * 128 + (((lane >> 3) ^ (lane & 7)) << 4), mb1 = mb0 ^ 64; \
            asm volatile("mov.b32 %0, %0;\nmov.b32 %1, %1;" : "+r"(mb0), "+r"(mb1), "+l"(ap));            \
            float e[2][4];                                                                                 \
            _Pragma("unroll") for (int i = 0; i < 4; i++) e[0][i] = e[1][i] = 0.f;                         \
            mbar_wait(bars + 8 * B_MEM, s & 1);                                                            \
            TS(0);                                                                                         \
            _Pragma("unroll") for (int ks = 0; ks < 32; ks += 2) {                                         \
                uint32_t b[4];                                                                             \
                ldsm4(b, ((ks & 2) ? mb1 : mb0) + (ks >> 2) * 1024);                                       \
                mma16816(e[0], a[ks][0], a[ks][1], a[ks][2], a[ks][3], b[0], b[1]);                        \
                mma16816(e[1], a[ks + 1][0], a[ks + 1][1], a[ks + 1][2], a[ks + 1][3], b[2], b[3]);        \
            }                                                                                              \
            TS(2);                                                                                         \
            if (lane < 8) asm volatile("st.relaxed.gpu.global.u32 [%0], %1;" ::"l"((uint32_t*)g_qst + role * 8 + lane), "r"(gtime()) : "memory"); \
            uint32_t u0 = pack_bf16(e[0][0] + e[1][0], e[0][1] + e[1][1]), u1 = pack_bf16(e[0][2] + e[1][2], e[0][3] + e[1][3]); \
            u0 = movm(u0); u1 = movm(u1);                                                                  \
            if (QKW_EARLY) { SCHED_FENCE(); if (lane == 0) mbar_arrive(bars + 8 * B_QKW); }                \
            stg_rlx64(ap, (u0 & ~1u) | (((s >> 1) & 1) ^ 1), u1);                                          \
            if (!QKW_EARLY && lane == 0) mbar_arrive(bars + 8 * B_QKW);                                    \
            TS(3);                                                                                         \
        }                                                                                                  \
        x_wait(R, 63 + RA, sb);
        if (wgi == 0) { QK_LOOP(0); } else { QK_LOOP(1); }
        if (QKW_EARLY) sts32(bars + 252, sf);
        TSDUMP();
    } else if (wgi == 2) {
        asm volatile("setmaxnreg.dec.sync.aligned.u32 64;");
        asm volatile("barrier.cluster.arrive.release.aligned;" ::: "memory");
        if (w == 0) {
            mbar_wait(bars + 8 * B_KDONE, 0);
            if (lane == 0) {
                mbar_expect_tx(bars + 8 * B_XFULL, 32768);
                tma4d(sb + O_XB, &tm_x, kh * 8, 0, bars + 8 * B_XFULL);
            }
            mbar_wait(bars + 8 * B_QDONE, 0);
            if (lane == 0) {
                mbar_expect_tx(bars + 8 * B_WO, 65536);
#pragma unroll
                for (int i = 0; i < 4; i++) tma2d(sb + O_WO + i * 16384, &tm_wo, j * 256 + i * 64, h * 128, bars + 8 * B_WO);
            }
        }
        asm volatile("barrier.cluster.wait.acquire.aligned;" ::: "memory");
        mbar_wait(bars + 8 * B_WV, 0);
        sts128u(sb + O_VM + tid * 16, make_uint4(0, 0, 0, 0));
        uint32_t tref = gtime() - 4000;
#define V_PASS(d)                                                                                          \
        wg_fence();                                                                                        \
        _Pragma("unroll") for (int ks = 0; ks < 32; ks++) {                                                \
            constexpr uint64_t da0 = mkdesc(SM_BASE + O_WV, 16, 1024, 1);                                  \
            if (ks == 0) wg_ss40<0>(d, da0 + ks * 128, xdesc(ks)); else wg_ss40<1>(d, da0 + ks * 128, xdesc(ks)); \
        }                                                                                                  \
        wg_commit();                                                                                       \
        wg_wait<0>();
#define X_REFILL(sg)                                                                                       \
        if (lane == 0) {                                                                                   \
            mbar_expect_tx(bars + 8 * B_XFULL, 32768);                                                     \
            tma4d(sb + O_XB, &tm_x, kh * 8, (sg) * 4, bars + 8 * B_XFULL);       \
        }
#pragma unroll 1
        for (int sg = 0; sg < RA; sg++) {
            float d[20]; uint32_t sn[4], kp[4];
            mbar_wait(bars + 8 * B_XFULL, sg & 1);
            V_PASS(d);
            if (lane == 0) mbar_arrive(bars + 8 * B_XEMPTY);
            if (w == 0) { mbar_wait(bars + 8 * B_XEMPTY, sg & 1); X_REFILL(sg + 1); }
            x_split(d, sn, kp, kh);
            x_send(2, sn, sg, tid, sb, mate);
            x_wait(2, sg, sb);
            x_finish<2>(kp, sg, h, nh * 4 + w, kh, tid, sb);
        }
#pragma unroll 1
        for (int s = 0; s < 64; s++) {
            TSI(s);
            OPAQUE_IDS();
            uint2* ap = &g_alpha[((s & 1) * 32 + h) * (3 * 512) + 1024 + ((nh * 4 + w) * 2 + kh) * 32 + lane];
            asm volatile("" : "+l"(ap));
            float d[20];
            mbar_wait(bars + 8 * B_QKW, s & 1);
            TS(0);
            V_PASS(d);
            TS(1);
            stg_rlx64(ap, (pack_bf16(d[16], d[17]) & ~1u) | (((s >> 1) & 1) ^ 1), pack_bf16(d[18], d[19]));
            const uint32_t tv = gtime();
            if (tid == 0) asm volatile("st.relaxed.gpu.global.u32 [%0], %1;" ::"l"((uint32_t*)g_stamp + role), "r"(tv) : "memory");
            if (lane == 0) mbar_arrive(bars + 8 * B_XEMPTY);
            uint32_t sn[4], kp[4];
            x_split(d, sn, kp, kh);
            {
                const uint2* vp = &g_alpha[((s & 1) * 32 + h) * (3 * 512) + 1024 + w * 128 + lane];
                const uint32_t tag = ((s >> 1) & 1) ^ 1;
                mbar_wait(bars + 8 * B_AFULL, s & 1);
                int dt;
                asm volatile("ld.shared.u32 %0, [%1];" : "=r"(dt) : "r"(sb + O_QST + lane * 4) : "memory");
                dt = min(__reduce_max_sync(~0u, dt - (int)tv), 0);
                asm volatile("" : "+l"(vp));
                wait_gtime(tv + dt + tn.d_v);
                uint32_t n = 0, bad;
                do {
                    uint2 va[4];
#pragma unroll
                    for (int i = 0; i < 4; i++) va[i] = ldg_rlx64(vp + i * 32);
                    if (++n > SPIN_LIMIT) __trap();
                    bad = (orx2(va[0].x, va[1].x, tag) | orx2(va[2].x, va[3].x, tag)) & 1;
                    sts128u(sb + O_VM + tid * 16, make_uint4((add_bf16x2(va[0].x, va[1].x) & ~1u) | ((~s ^ bad) & 1), add_bf16x2(va[0].y, va[1].y),
                                                             add_bf16x2(va[2].x, va[3].x), add_bf16x2(va[2].y, va[3].y)));
                } while (__any_sync(~0u, bad));
                TS(2);
                TSV(16 + w, n - 1);
            }
            if (s == 63) break;
            if (w == 0) {
                mbar_wait(bars + 8 * B_XEMPTY, (s + RA) & 1);
                X_REFILL(s + RA + 1);
                if (lane == 0 && nh == 0 && ((h ^ s) & 7) == 0 && s < 61 - RA) tma4d_prefetch(&tm_x, kh * 8, (s + RA + 3) * 4);
                mbar_wait(bars + 8 * B_SRDY, s & 1);
                if (lane == 0) {
                    const uint4* hb = &g_kvq[(((s + 1) & 3) * 32 + h) * (3 * 512)];
                    mbar_expect_tx(bars + 8 * B_KVFULL, 18432);
                    bulk_g2s(sb + O_KVQ, hb + 512, 16384, bars + 8 * B_KVFULL);
                    bulk_g2s(sb + O_KVQ + 16384, hb + j * 128, 2048, bars + 8 * B_KVFULL);
                }
            }
            if (w == 3) {
                wait_clk(clk(), tn.d_st);
                uint32_t n = 0, mx, mn;
                do {
                    const uint4 st = ldg_rlx128(&g_stamp[lane]);
                    mx = __reduce_max_sync(~0u, max(max(st.x - tref, st.y - tref), max(st.z - tref, st.w - tref)));
                    mn = __reduce_min_sync(~0u, min(min(st.x - tref, st.y - tref), min(st.z - tref, st.w - tref)));
                } while (mx >= 200000u && ++n < 64);
                tref = mx < 200000u ? tref + mx + (mx - mn > tn.spread ? tn.extra : 1) : gtime();
                TSV(12, clk()); TSV(13, n); TSV(14, mx - mn);
            }
            mbar_wait(bars + 8 * B_OPDONE, (s + 1) & 1);
            x_send(2, sn, s + RA, tid, sb, mate);
            if (w == 3) {
                wait_gtime(tref + tn.d_r0);
                if (lane == 0) {
                    mbar_expect_tx(bars + 8 * B_RFULL, 16384);
                    bulk_g2s(sb + O_STG, redp + (s & 3) * 32768 + kh * 16384, 16384, bars + 8 * B_RFULL);
                }
                TSV(3, clk());
            }
            x_wait(2, s + RA, sb);
            x_finish<2>(kp, s + RA, h, nh * 4 + w, kh, tid, sb);
            TS(6);
            if (DBG_TIMING) { mbar_wait(bars + 8 * B_RFULL, s & 1); TS(4); }
            const uint32_t n = convert_mem(redp, s, kh, 0, w, lane, sb); (void)n;
            TS(5);
            TSV(8 + w, n);
        }
        TSDUMP();
    } else {
        asm volatile("setmaxnreg.dec.sync.aligned.u32 96;");
        GT(0);
        asm volatile("barrier.cluster.arrive.release.aligned;" ::: "memory");
#define RED_CLEAR(st)                                                                                           \
        if (lane < 16) {                                                                                        \
            const uint32_t cb = ((st) & 4) ? 0x42800000u : 0u;                                                  \
            stg128(redp + ((st) & 3) * 32768 + role * 256 + lane * 16, 0, (role & 2) ? cb : 0u, 0, cb);        \
        }
#define KQ_BAD(tg) __any_sync(~0u, or3(orx2(kf[0].x, kf[1].x, tg), orx2(kf[2].x, kf[3].x, tg), orx2(qf[0].x, qf[1].x, tg)) & 1)
#define KQ_POLL(st)                                                                                             \
        {                                                                                                       \
            const uint4* hb = &g_kvq[(((st) & 3) * 32 + h) * (3 * 512)];                                        \
            uint32_t n_ = 0;                                                                                    \
            do {                                                                                                \
                _Pragma("unroll") for (int i = 0; i < 4; i++) kf[i] = ldg_rlx128(hb + 512 + w * 128 + i * 32 + lane); \
                _Pragma("unroll") for (int u = 0; u < 2; u++) qf[u] = ldg_rlx64((const uint2*)hb + j * 256 + (2 * w + u) * 32 + lane); \
                if (++n_ > SPIN_LIMIT) __trap();                                                                \
            } while (KQ_BAD((((st) >> 2) & 1) ^ 1));                                                \
        }
        uint32_t start_target = 0;
        if (w == 0) {
            RED_CLEAR(0); RED_CLEAR(1); RED_CLEAR(2);
            fence_gpu();
            __syncwarp();
            if (lane == 0) start_target = (atomicAdd(&g_start, 1) & ~127u) + 128;
            start_target = __shfl_sync(~0u, start_target, 0);
        }
        mbar_wait(bars + 8 * B_KDONE, 0);
        {
            const int kb0 = (w & 1) * 4 + (w >> 1) * 2;
#pragma unroll
            for (int q = 0; q < 4; q++) {
                const int row = (lane >> 3) + (q & 1) * 4, ch = lane & 7, kb = kb0 + (q >> 1);
                const uint4 v = *(const uint4*)(mem0 + row * 1024 + kh * 512 + kb * 64 + ch * 8);
                sts128u(sb + O_MEM + kb * 1024 + row * 128 + ((ch ^ row) << 4), v);
            }
            fence_async_smem();
            __syncwarp();
            if (lane < 2) { mbar_arrive(bars + 8 * B_MEM); mbar_arrive(bars + 8 * B_QKW); }
            if (lane == 0) mbar_arrive(bars + 8 * B_OPDONE);
        }
        asm volatile("barrier.cluster.wait.acquire.aligned;" ::: "memory");
        if (w == 0) { uint32_t n = 0; while (__any_sync(~0u, (int)(ld_acquire(&g_start) - start_target) < 0)) { if (++n > SPIN_LIMIT) __trap(); } }
        mbar_wait(bars + 8 * B_WO, 0);
        GT(1);
        uint32_t sf = 0;
        uint4 kf[4]; uint2 qf[2];
        KQ_POLL(0);
#pragma unroll
        for (int i = 0; i < 4; i++) sts128u(sb + O_KVQ + 8192 + w * 2048 + i * 512 + lane * 16, make_uint4(0, 0, 0, 0));
#pragma unroll 1
        for (int s = 0; s < 64; s++) {
            TSI(s);
            OPAQUE_IDS();
            const uint32_t tg = ((s >> 2) & 1) ^ 1;
            const uint32_t tag = ((s >> 1) & 1) ^ 1;
            const uint2* ap = &g_alpha[((s & 1) * 32 + h) * (3 * 512) + w * 128 + lane];
            uint32_t sw = sb + O_S + w * 2560 + lane * 16, sr = sb + O_S + tid * 4;
            uint32_t pw = sb + O_P + ((lane >> 1) & 1) * 704 + (2 * w + (lane >> 4)) * 16 + ((lane >> 2) & 3) * 4 + (lane & 1) * 2;
            int lim = (lane & 2) ? 8 * j + 2 * w + (lane >> 4) - 2 * ((lane >> 2) & 3) - (lane & 1) : 64;
            uint32_t pr = sb + O_P + lane * 16, oa = sb + O_O + w * 512 + lane * 4;
            uint32_t aa = sb + O_STG + w * 1024 + lane * 8, vv = sb + O_KVQ + 8192 + w * 2048 + lane * 16;
            unsigned char* pa = redp + (s & 3) * 32768 + red_grp(j * 16 + (tid >> 3));
            unsigned char* pb = pa + 512 + ((lane >> 3) & 1) * 64 + (lane & 7) * 8;
            pa += (lane & 7) * 16;
            asm volatile("" : "+r"(sw), "+r"(sr), "+r"(pw), "+r"(lim), "+r"(pr), "+r"(oa), "+r"(aa), "+r"(vv), "+l"(ap), "+l"(pa), "+l"(pb));
            TS(0);
            mbar_wait(bars + 8 * B_QKW, s & 1);
            TS(1);
            if (w == 0) {
                wait_clk(clk(), tn.d_alpha);
                if (lane == 0) {
                    mbar_expect_tx(bars + 8 * B_AFULL, 8192 + 128);
                    bulk_g2s(sb + O_STG, ap, 8192, bars + 8 * B_AFULL);
                    bulk_g2s(sb + O_QST, &g_qst[h * 8], 128, bars + 8 * B_AFULL);
                }
            }
            mbar_wait(bars + 8 * B_AFULL, s & 1);
            TS(12);
            uint4 vf[4];
            {
                uint2 qa[4], ka[4];
#pragma unroll
                for (int i = 0; i < 4; i++) { qa[i] = lds64u(aa + i * 256); ka[i] = lds64u(aa + 4096 + i * 256); }
#define QK_BAD() __any_sync(~0u, or3(orx2(qa[0].x, ka[0].x, tag), orx2(qa[1].x, ka[1].x, tag), orx(orx(orx2(qa[2].x, ka[2].x, tag), qa[3].x, tag), ka[3].x, tag)) & 1)
#define SCORES()                                                                                                                  \
                {                                                                                                                 \
                    float sa[5][4];                                                                                               \
                    _Pragma("unroll") for (int n = 0; n < 5; n++) sa[n][0] = sa[n][1] = sa[n][2] = sa[n][3] = 0.f;                \
                    _Pragma("unroll") for (int u = 0; u < 2; u++) {                                                               \
                        const uint32_t q0 = add_bf16x2(qa[2 * u].x, qa[2 * u + 1].x), q1 = add_bf16x2(qa[2 * u].y, qa[2 * u + 1].y); \
                        const uint32_t k0 = add_bf16x2(ka[2 * u].x, ka[2 * u + 1].x), k1 = add_bf16x2(ka[2 * u].y, ka[2 * u + 1].y); \
                        mma16816(sa[1], q0, qf[u].x, q1, qf[u].y, kf[2 * u].x, kf[2 * u].y);                                      \
                        mma16816(sa[2], q0, qf[u].x, q1, qf[u].y, kf[2 * u].z, kf[2 * u].w);                                      \
                        mma16816(sa[3], q0, qf[u].x, q1, qf[u].y, kf[2 * u + 1].x, kf[2 * u + 1].y);                              \
                        mma16816(sa[4], q0, qf[u].x, q1, qf[u].y, kf[2 * u + 1].z, kf[2 * u + 1].w);                              \
                        mma16816(sa[0], q0, qf[u].x, q1, qf[u].y, k0, k1);                                                        \
                        if (u == 0) SCHED_FENCE();                                                                                \
                    }                                                                                                             \
                    _Pragma("unroll") for (int n = 1; n <= 5; n++) sts128(sw + (n % 5) * 512, sa[n % 5][0], sa[n % 5][1], sa[n % 5][2], sa[n % 5][3]); \
                }
                SCORES();
                uint32_t nr = 0;
                if (__builtin_expect(QK_BAD(), 0)) {
                    do {
#pragma unroll
                        for (int i = 0; i < 4; i++) { qa[i] = ldg_rlx64(ap + i * 32); ka[i] = ldg_rlx64(ap + 512 + i * 32); }
                        if (++nr > SPIN_LIMIT) __trap();
                    } while (QK_BAD());
                    SCORES();
                }
                if (w == 0) TSV(20, nr);
            }
            TS(2);
            bar_sync(1, 128);
            float sc[5];
            {
                float x[4][5];
#pragma unroll
                for (int q = 0; q < 4; q++)
#pragma unroll
                    for (int n = 0; n < 5; n++) asm volatile("ld.shared.f32 %0, [%1];" : "=f"(x[q][n]) : "r"(sr + q * 2560 + n * 512) : "memory");
#pragma unroll
                for (int n = 0; n < 5; n++) sc[n] = (x[0][n] + x[1][n]) + (x[2][n] + x[3][n]);
            }
            TS(15);
#pragma unroll
            for (int n = 1; n < 5; n++) if (8 * (n - 1) > lim) sc[n] = MASK_VAL;
            float m = fmaxf(fmaxf(fmaxf(sc[0], sc[1]), fmaxf(sc[2], sc[3])), sc[4]);
            m = fmaxf(m, __shfl_xor_sync(~0u, m, 1));
            m = fmaxf(m, __shfl_xor_sync(~0u, m, 4));
            m = fmaxf(m, __shfl_xor_sync(~0u, m, 8));
            m *= -SM_SCALE_LOG2;
            SCHED_FENCE();
#pragma unroll
            for (int i = 0; i < 4; i++) vf[i] = lds128u(vv + i * 512);
#pragma unroll
            for (int n = 0; n < 5; n++) {
                const uint32_t pv = pack_bf16(ex2(fmaf(sc[n], SM_SCALE_LOG2, m)), 0.f);
                asm volatile("st.shared.u16 [%0], %1;" ::"r"(pw + n * 128), "h"((uint16_t)pv) : "memory");
            }
            bar_sync(1, 128);
            TS(3);
            uint32_t pf[4], p0, px[4], px0;
            ldsm4(pf, pr + 128);
            asm volatile("ld.shared.u32 %0, [%1];" : "=r"(p0) : "r"(oa - w * 512 + (O_P - O_O)) : "memory");
            ldsm4(px, pr + 128 + 704);
            asm volatile("ld.shared.u32 %0, [%1];" : "=r"(px0) : "r"(oa - w * 512 + (O_P - O_O) + 704) : "memory");
            if (lane == 0) mbar_arrive(bars + 8 * B_SRDY);
            uint4 vm = lds128u(sb + O_VM + tid * 16);
            if (__builtin_expect(__any_sync(~0u, orx(orx(orx2(vf[0].x, vf[1].x, tg), vf[2].x, tg), vf[3].x, tg) & 1), 0)) {
                const uint4* vp = &g_kvq[((s & 3) * 32 + h) * (3 * 512) + 1024 + w * 128 + lane];
                uint32_t nr = 0;
                do {
#pragma unroll
                    for (int i = 0; i < 4; i++) vf[i] = ldg_rlx128(vp + i * 32);
                    if (++nr > SPIN_LIMIT) __trap();
                } while (__any_sync(~0u, orx(orx(orx2(vf[0].x, vf[1].x, tg), vf[2].x, tg), vf[3].x, tg) & 1));
            }
            float o[2][4], ox[2][4], sm[4], sx[4];
#pragma unroll
            for (int i = 0; i < 4; i++) o[0][i] = o[1][i] = ox[0][i] = ox[1][i] = sm[i] = sx[i] = 0.f;
            constexpr uint32_t ONE2 = 0x3f803f80u;
#pragma unroll
            for (int c = 0; c < 2; c++) {
#pragma unroll
                for (int u = 0; u < 2; u++) mma16816(o[u], vf[2 * u + c].x, vf[2 * u + c].y, vf[2 * u + c].z, vf[2 * u + c].w, pf[2 * c], pf[2 * c + 1]);
#pragma unroll
                for (int u = 0; u < 2; u++) mma16816(ox[u], vf[2 * u + c].x, vf[2 * u + c].y, vf[2 * u + c].z, vf[2 * u + c].w, px[2 * c], px[2 * c + 1]);
            }
            {
                uint32_t nr = 0;
                while (__any_sync(~0u, (vm.x ^ ~s) & 1)) { vm = lds128u(sb + O_VM + tid * 16); if (++nr > SPIN_LIMIT) __trap(); }
                if (w == 0) TSV(21, nr);
            }
            mma1688(o[0], vm.x, vm.y, p0);
            mma1688(o[1], vm.z, vm.w, p0);
            mma1688(sm, ONE2, ONE2, p0);
            mma1688(sx, ONE2, ONE2, px0);
            SCHED_FENCE();
            sts32(oa, pack_bf16(o[0][0], o[0][1]));
            sts32(oa + 128, pack_bf16(o[0][2], o[0][3]));
            sts32(oa + 256, pack_bf16(o[1][0], o[1][1]));
            sts32(oa + 384, pack_bf16(o[1][2], o[1][3]));
            mma1688(ox[0], vm.x, vm.y, px0);
            mma1688(ox[1], vm.z, vm.w, px0);
#pragma unroll
            for (int c = 0; c < 2; c++) {
                mma16816(sm, ONE2, ONE2, ONE2, ONE2, pf[2 * c], pf[2 * c + 1]);
                mma16816(sx, ONE2, ONE2, ONE2, ONE2, px[2 * c], px[2 * c + 1]);
            }
            SCHED_FENCE();
            TS(4);
            fence_async_smem();
            bar_sync(1, 128);
            if (s == 0) GT(2);
            TS(5);
            {
            float cc[4][4];
            wg_fence();
#pragma unroll
            for (int ks = 0; ks < 8; ks++)
#pragma unroll
                for (int t = 0; t < 4; t++) {
                    constexpr uint64_t da0 = mkdesc(SM_BASE + O_WO, 16, 1024, 1), db0 = mkdesc(SM_BASE + O_O, 128, 128, 0);
                    if (ks == 0) wg_ss8<0>(cc[t], da0 + t * 1024, db0); else wg_ss8<1>(cc[t], da0 + t * 1024 + ks * 128, db0 + ks * 16);
                }
            wg_commit();
            const float i0 = rcp(sm[0]), i1 = rcp(sm[1]);
            wg_wait<0>();
            TS(6);
#pragma unroll
            for (int hf = 0; hf < 2; hf++)
                asm volatile("red.relaxed.gpu.global.add.noftz.v4.bf16x2 [%0], {%1,%2,%3,%4};" ::"l"(pa + hf * 128),
                             "r"(pack_bf16(cc[2 * hf][0] * i0, cc[2 * hf][1] * i1)), "r"(pack_bf16(cc[2 * hf][2] * i0, cc[2 * hf][3] * i1)),
                             "r"(pack_bf16(cc[2 * hf + 1][0] * i0, cc[2 * hf + 1][1] * i1)), "r"(pack_bf16(cc[2 * hf + 1][2] * i0, 1.f)) : "memory");
            asm volatile("red.relaxed.gpu.global.add.noftz.v2.bf16x2 [%0], {%1,%2};" ::"l"(pb), "r"(pack_bf16(cc[1][3] * i1, cc[3][3] * i1)), "r"(0x3f800000u) : "memory");
            SCHED_FENCE();
            TS(7);
            if (lane == 0) mbar_arrive(bars + 8 * B_OPDONE);
            }
            if (!FLAG(3)) {
                const float ix0 = rcp(sx[0]), ix1 = rcp(sx[1]);
                const uint32_t xo = sb + O_XO + w * 512;
                stsm4t(xo + (lane & 7) * 64 + (((lane >> 3) ^ ((lane >> 1) & 3)) << 4), pack_bf16(ox[0][0] * ix0, ox[0][1] * ix1),
                       pack_bf16(ox[0][2] * ix0, ox[0][3] * ix1), pack_bf16(ox[1][0] * ix0, ox[1][1] * ix1), pack_bf16(ox[1][2] * ix0, ox[1][3] * ix1));
                __syncwarp();
                const uint4 ov = lds128u(xo + (lane >> 2) * 64 + (((lane & 3) ^ ((lane >> 3) & 3)) << 4));
                stg128(&g_ox[(size_t)(s * 32 + j * 8 + (lane >> 2)) * 4096 + h * 128 + w * 32 + (lane & 3) * 8], ov.x, ov.y, ov.z, ov.w);
            }
            TS(8);
            if (s == 63) { GT(3); break; }
            mbar_wait(bars + 8 * B_KVFULL, s & 1);
#pragma unroll
            for (int i = 0; i < 4; i++) kf[i] = lds128u(vv - 8192 + i * 512);
#pragma unroll
            for (int u = 0; u < 2; u++) qf[u] = lds64u(sb + O_KVQ + 16384 + (2 * w + u) * 256 + lane * 8);
            if (__builtin_expect(KQ_BAD((((s + 1) >> 2) & 1) ^ 1), 0)) { KQ_POLL(s + 1); if (w == 0) TSV(22, 1); }
            TS(9);
            {
                const uint32_t n = convert_mem(redp, s, kh, 1, w, lane, sb); (void)n;
                TS(11);
                TSV(16 + w, n);
            }
            if (w == 0 && s < 61) RED_CLEAR(s + 3);
        }
        sts32(bars + 252, sf);
        TSDUMP();
    }
}

constexpr int G_ST = 6;
constexpr uint32_t G_SMEM = G_ST * 32768 + 256;
#define F16(d, o) F4(d, o), F4(d, o + 4), F4(d, o + 8), F4(d, o + 12)
__device__ __forceinline__ void wg_ss128(float (&d)[64], uint64_t da, uint64_t db, int sc) {
    asm volatile("{\n.reg .pred p;\nsetp.ne.b32 p, %66, 0;\nwgmma.mma_async.sync.aligned.m64n128k16.f32.bf16.bf16 "
                 "{%0,%1,%2,%3,%4,%5,%6,%7,%8,%9,%10,%11,%12,%13,%14,%15,%16,%17,%18,%19,%20,%21,%22,%23,%24,%25,%26,%27,%28,%29,%30,%31,"
                 "%32,%33,%34,%35,%36,%37,%38,%39,%40,%41,%42,%43,%44,%45,%46,%47,%48,%49,%50,%51,%52,%53,%54,%55,%56,%57,%58,%59,%60,%61,%62,%63}, "
                 "%64, %65, p, 1, 1, 0, 1;\n}"
                 : F16(d, 0), F16(d, 16), F16(d, 32), F16(d, 48) : "l"(da), "l"(db), "r"(sc));
}

__global__ void __launch_bounds__(384, 1)
out_gemm(const __grid_constant__ CUtensorMap tm_o, const __grid_constant__ CUtensorMap tm_w, bf16* __restrict__ out) {
    extern __shared__ __align__(1024) unsigned char smem_raw[];
    const uint32_t sb = smem_u32(smem_raw), bars = sb + G_ST * 32768;
    const int m0 = (blockIdx.x >> 3) * 128, n0 = (blockIdx.x & 7) * 128;
    const int wgi = __shfl_sync(~0u, threadIdx.x >> 7, 0), tid = threadIdx.x & 127;
    if (threadIdx.x == 0) {
        for (int i = 0; i < G_ST; i++) { mbar_init(bars + 8 * i, 1); mbar_init(bars + 8 * (G_ST + i), 8); }
        fence_async_smem();
    }
    __syncthreads();
    if (wgi == 0) GT(4);
    if (wgi == 2) {
        if (tid == 0) {
            for (int kt = 0; kt < 64; kt++) {
                const int st = kt % G_ST;
                if (kt >= G_ST) mbar_wait(bars + 8 * (G_ST + st), (kt / G_ST - 1) & 1);
                mbar_expect_tx(bars + 8 * st, 32768);
                tma2d(sb + st * 32768, &tm_o, kt * 64, m0, bars + 8 * st);
                tma2d(sb + st * 32768 + 16384, &tm_w, n0, kt * 64, bars + 8 * st);
                tma2d(sb + st * 32768 + 24576, &tm_w, n0 + 64, kt * 64, bars + 8 * st);
            }
        }
    } else {
        float d[64];
        int st = 0, ph = 0;
#pragma unroll 1
        for (int kt = 0; kt < 64; kt++) {
            mbar_wait(bars + 8 * st, ph);
            const uint64_t da = mkdesc(sb + st * 32768 + wgi * 8192, 16, 1024, 1), db = mkdesc(sb + st * 32768 + 16384, 8192, 1024, 1);
            wg_fence();
#pragma unroll
            for (int k = 0; k < 4; k++) wg_ss128(d, da + k * 2, db + k * 128, kt | k);
            wg_commit();
            if (kt > 0) {
                wg_wait<1>();
                if ((tid & 31) == 0) mbar_arrive(bars + 8 * (G_ST + (st == 0 ? G_ST - 1 : st - 1)));
            }
            if (++st == G_ST) { st = 0; ph ^= 1; }
        }
        wg_wait<0>();
        const int row = m0 + wgi * 64 + (tid >> 5) * 16 + ((tid & 31) >> 2);
        bf16* op = out + (size_t)row * 2048 + 1024 + n0 + (tid & 3) * 2;
#pragma unroll
        for (int i = 0; i < 16; i++) {
            *(uint32_t*)(op + i * 8) = pack_bf16(d[4 * i], d[4 * i + 1]);
            *(uint32_t*)(op + 8 * 2048 + i * 8) = pack_bf16(d[4 * i + 2], d[4 * i + 3]);
        }
        if (wgi == 0) GT(5);
    }
}

typedef CUresult (*EncodeFn)(CUtensorMap*, CUtensorMapDataType, cuuint32_t, void*, const cuuint64_t*, const cuuint64_t*,
                             const cuuint32_t*, const cuuint32_t*, CUtensorMapInterleave, CUtensorMapSwizzle,
                             CUtensorMapL2promotion, CUtensorMapFloatOOBfill);

static void make_map(EncodeFn fn, CUtensorMap* m, const void* p, uint64_t cols, uint64_t rows, uint32_t bc, uint32_t br) {
    cuuint64_t dims[2] = {cols, rows}, strides[1] = {cols * 2};
    cuuint32_t box[2] = {bc, br}, es[2] = {1, 1};
    fn(m, CU_TENSOR_MAP_DATA_TYPE_BFLOAT16, 2, (void*)p, dims, strides, box, es, CU_TENSOR_MAP_INTERLEAVE_NONE,
       CU_TENSOR_MAP_SWIZZLE_128B, CU_TENSOR_MAP_L2_PROMOTION_L2_128B, CU_TENSOR_MAP_FLOAT_OOB_FILL_NONE);
}

static Tune h_tune = {300, 1120, 1, 0, 0, 672, 4000, 300};

extern "C" void kernel_launch(void* const* d_in, const int* in_sizes, int n_in, void* d_out, int out_size) {
    static bool init = false;
    static CUtensorMap tm_x, tm_wq, tm_wk, tm_wv, tm_wo, tm_o, tm_wo2;
    if (!init) {
        void* fp = nullptr; cudaDriverEntryPointQueryResult qr;
        cudaGetDriverEntryPoint("cuTensorMapEncodeTiled", &fp, cudaEnableDefault, &qr);
        EncodeFn fn = (EncodeFn)fp;
        void* ox = nullptr; cudaGetSymbolAddress(&ox, g_ox);
        {
            cuuint64_t dims[4] = {64, 8, 16, 256}, strides[3] = {2048, 128, 16384};
            cuuint32_t box[4] = {64, 8, 8, 4}, es[4] = {1, 1, 1, 1};
            fn(&tm_x, CU_TENSOR_MAP_DATA_TYPE_BFLOAT16, 4, d_in[3], dims, strides, box, es, CU_TENSOR_MAP_INTERLEAVE_NONE,
               CU_TENSOR_MAP_SWIZZLE_128B, CU_TENSOR_MAP_L2_PROMOTION_L2_128B, CU_TENSOR_MAP_FLOAT_OOB_FILL_NONE);
        }
        make_map(fn, &tm_wq, d_in[5], 4096, 1024, 64, 256);
        make_map(fn, &tm_wk, d_in[6], 4096, 1024, 64, 256);
        make_map(fn, &tm_wv, d_in[7], 4096, 1024, 64, 256);
        make_map(fn, &tm_wo, d_in[8], 1024, 4096, 64, 128);
        make_map(fn, &tm_o, ox, 4096, 2048, 64, 128);
        make_map(fn, &tm_wo2, d_in[8], 1024, 4096, 64, 64);
        cudaFuncSetAttribute(rmt_main, cudaFuncAttributeMaxDynamicSharedMemorySize, MAIN_SMEM);
        cudaFuncSetAttribute(out_gemm, cudaFuncAttributeMaxDynamicSharedMemorySize, G_SMEM);
        cudaFuncSetAttribute(fft_pass<0>, cudaFuncAttributeMaxDynamicSharedMemorySize, FT_SIZE + FG_SIZE);
        cudaFuncSetAttribute(fft_pass<1>, cudaFuncAttributeMaxDynamicSharedMemorySize, FT_SIZE + FG_SIZE);
        cudaFuncSetAttribute(fft_pass<2>, cudaFuncAttributeMaxDynamicSharedMemorySize, FT_SIZE + FG_SIZE);
        init = true;
    }
    const uint4* ax = (const uint4*)d_in[0];
    const unsigned char *wr = (const unsigned char*)d_in[1], *wi = (const unsigned char*)d_in[2];
    fft_pass<0><<<128, 256, FT_SIZE + FG_SIZE>>>(ax, wr, wi, (uint4*)d_out);
    fft_pass<1><<<129, 256, FT_SIZE + FG_SIZE>>>(ax, wr, wi, (uint4*)d_out);
    fft_pass<2><<<128, 256, FT_SIZE + FG_SIZE>>>(ax, wr, wi, (uint4*)d_out);
    rmt_main<<<132, 512, MAIN_SMEM>>>(tm_x, tm_wq, tm_wk, tm_wv, tm_wo, (const bf16*)d_in[4], h_tune);
    out_gemm<<<128, 384, G_SMEM>>>(tm_o, tm_wo2, (bf16*)d_out);
}
```

```cpp
#include <cuda_runtime.h>
#include <cuda_bf16.h>
#include <cuda.h>
#include <stdint.h>

typedef __nv_bfloat16 bf16;

#define DBG_TIMING 0

#define SPIN_LIMIT (1u << 22)

__device__ __forceinline__ uint32_t smem_u32(const void* p) { return (uint32_t)__cvta_generic_to_shared(p); }
__device__ __forceinline__ uint32_t clk() { uint32_t c; asm volatile("mov.u32 %0, %%clock;" : "=r"(c)::"memory"); return c; }
#define SCHED_FENCE() sf ^= (uint32_t)clock64()
__device__ __forceinline__ uint32_t gtime() { uint32_t c; asm volatile("mov.u32 %0, %%globaltimer_lo;" : "=r"(c)::"memory"); return c; }
__device__ __forceinline__ void wait_clk(uint32_t t0, uint32_t d) {
    asm volatile("{\n.reg .pred p;\n.reg .s32 t;\n.reg .b64 c;\nWL:\nmov.u64 c, %%clock64;\ncvt.u32.u64 t, c;\nsub.s32 t, t, %0;\nsetp.lt.s32 p, t, 0;\n@p bra.uni WL;\n}" ::"r"(t0 + d) : "memory");
}
__device__ __forceinline__ void wait_gtime(uint32_t t1) {
    asm volatile("{\n.reg .pred p;\n.reg .s32 t;\n.reg .b64 c;\nWL:\nmov.u64 c, %%globaltimer;\ncvt.u32.u64 t, c;\nsub.s32 t, t, %0;\nsetp.lt.s32 p, t, 0;\n@p bra.uni WL;\n}" ::"r"(t1) : "memory");
}

__device__ __forceinline__ void mbar_init(uint32_t bar, uint32_t cnt) {
    asm volatile("mbarrier.init.shared::cta.b64 [%0], %1;" ::"r"(bar), "r"(cnt) : "memory");
}
__device__ __forceinline__ void mbar_arrive(uint32_t bar) {
    asm volatile("mbarrier.arrive.shared::cta.b64 _, [%0];" ::"r"(bar) : "memory");
}
__device__ __forceinline__ void mbar_expect_tx(uint32_t bar, uint32_t bytes) {
    asm volatile("mbarrier.arrive.expect_tx.shared::cta.b64 _, [%0], %1;" ::"r"(bar), "r"(bytes) : "memory");
}
__device__ __forceinline__ void mbar_wait(uint32_t bar, uint32_t parity) {
    asm volatile(
        "{\n.reg .pred p, q;\n.reg .u32 n;\nmov.u32 n, 0;\n"
        "WL:\nmbarrier.try_wait.parity.shared::cta.b64 p, [%0], %1;\n"
        "add.u32 n, n, 1;\nsetp.gt.u32 q, n, %2;\n@q trap;\n@!p bra.uni WL;\n}" ::"r"(bar), "r"(parity), "n"(SPIN_LIMIT) : "memory");
}
__device__ __forceinline__ void mbar_wait_cluster(uint32_t bar, uint32_t parity) {
    asm volatile(
        "{\n.reg .pred p, q;\n.reg .u32 n;\nmov.u32 n, 0;\n"
        "WL:\nmbarrier.try_wait.parity.acquire.cluster.shared::cta.b64 p, [%0], %1;\n"
        "add.u32 n, n, 1;\nsetp.gt.u32 q, n, %2;\n@q trap;\n@!p bra.uni WL;\n}" ::"r"(bar), "r"(parity), "n"(SPIN_LIMIT) : "memory");
}
__device__ __forceinline__ void tma2d(uint32_t dst, const CUtensorMap* m, int c0, int c1, uint32_t bar) {
    asm volatile("cp.async.bulk.tensor.2d.shared::cluster.global.mbarrier::complete_tx::bytes [%0], [%1, {%3, %4}], [%2];"
                 ::"r"(dst), "l"(m), "r"(bar), "r"(c0), "r"(c1) : "memory");
}
__device__ __forceinline__ void tma4d(uint32_t dst, const CUtensorMap* m, int c2, int c3, uint32_t bar) {
    asm volatile("cp.async.bulk.tensor.4d.shared::cluster.global.mbarrier::complete_tx::bytes [%0], [%1, {%5, %5, %3, %4}], [%2];"
                 ::"r"(dst), "l"(m), "r"(bar), "r"(c2), "r"(c3), "r"(0) : "memory");
}
__device__ __forceinline__ void bulk_g2s(uint32_t dst, const void* src, uint32_t bytes, uint32_t bar) {
    asm volatile("cp.async.bulk.shared::cluster.global.mbarrier::complete_tx::bytes [%0], [%1], %2, [%3];"
                 ::"r"(dst), "l"(src), "r"(bytes), "r"(bar) : "memory");
}
__device__ __forceinline__ void tma4d_prefetch(const CUtensorMap* m, int c2, int c3) {
    asm volatile("cp.async.bulk.prefetch.tensor.4d.L2.global [%0, {%3, %3, %1, %2}];" ::"l"(m), "r"(c2), "r"(c3), "r"(0) : "memory");
}
__device__ __forceinline__ void tma2d_prefetch(const CUtensorMap* m, int c0, int c1) {
    asm volatile("cp.async.bulk.prefetch.tensor.2d.L2.global [%0, {%1, %2}];" ::"l"(m), "r"(c0), "r"(c1) : "memory");
}
__device__ __forceinline__ void fence_async_smem() { asm volatile("fence.proxy.async.shared::cta;" ::: "memory"); }
__device__ __forceinline__ void fence_gpu() { asm volatile("fence.acq_rel.gpu;" ::: "memory"); }
__device__ __forceinline__ float rcp(float x) { float r; asm("rcp.approx.ftz.f32 %0, %1;" : "=f"(r) : "f"(x)); return r; }
__device__ __forceinline__ void bar_sync(int id, int n) { asm volatile("bar.sync %0, %1;" ::"r"(id), "r"(n) : "memory"); }

__device__ __forceinline__ bool bar_or(int id, int n, uint32_t x) {
    uint32_t r;
    asm volatile("{\n.reg .pred p, q;\n.reg .b32 t;\nand.b32 t, %3, 1;\nsetp.ne.u32 p, t, 0;\nbar.red.or.pred q, %1, %2, p;\nselp.u32 %0, 1, 0, q;\n}"
                 : "=r"(r) : "r"(id), "r"(n), "r"(x) : "memory");
    return __any_sync(~0u, r);
}
__device__ __forceinline__ uint32_t or3(uint32_t a, uint32_t b, uint32_t c) {
    uint32_t r; asm("lop3.b32 %0, %1, %2, %3, 0xFE;" : "=r"(r) : "r"(a), "r"(b), "r"(c)); return r;
}
__device__ __forceinline__ uint32_t pack_bf16(float lo, float hi) {
    uint32_t r; asm("cvt.rn.bf16x2.f32 %0, %1, %2;" : "=r"(r) : "f"(hi), "f"(lo)); return r;
}
__device__ __forceinline__ uint32_t add_bf16x2(uint32_t a, uint32_t b) {
    uint32_t r; asm volatile("add.rn.bf16x2 %0, %1, %2;" : "=r"(r) : "r"(a), "r"(b)); return r;
}
__device__ __forceinline__ uint32_t movm(uint32_t a) {
    uint32_t r; asm volatile("movmatrix.sync.aligned.m8n8.trans.b16 %0, %1;" : "=r"(r) : "r"(a)); return r;
}
__device__ __forceinline__ uint32_t orx(uint32_t acc, uint32_t a, uint32_t t) {
    uint32_t r; asm("lop3.b32 %0, %1, %2, %3, 0xF6;" : "=r"(r) : "r"(acc), "r"(a), "r"(t)); return r;
}
__device__ __forceinline__ uint32_t orx2(uint32_t a, uint32_t b, uint32_t t) {
    uint32_t r; asm("lop3.b32 %0, %1, %2, %3, 0x7E;" : "=r"(r) : "r"(a), "r"(b), "r"(t)); return r;
}
__device__ __forceinline__ float ex2(float x) { float r; asm("ex2.approx.ftz.f32 %0, %1;" : "=f"(r) : "f"(x)); return r; }
__device__ __forceinline__ void ldsm4t(uint32_t (&r)[4], uint32_t a) {
    asm volatile("ldmatrix.sync.aligned.m8n8.x4.trans.shared.b16 {%0,%1,%2,%3}, [%4];"
                 : "=r"(r[0]), "=r"(r[1]), "=r"(r[2]), "=r"(r[3]) : "r"(a) : "memory");
}
__device__ __forceinline__ void ldsm4(uint32_t (&r)[4], uint32_t a) {
    asm volatile("ldmatrix.sync.aligned.m8n8.x4.shared.b16 {%0,%1,%2,%3}, [%4];"
                 : "=r"(r[0]), "=r"(r[1]), "=r"(r[2]), "=r"(r[3]) : "r"(a) : "memory");
}
__device__ __forceinline__ void stsm4t(uint32_t a, uint32_t r0, uint32_t r1, uint32_t r2, uint32_t r3) {
    asm volatile("stmatrix.sync.aligned.m8n8.x4.trans.shared.b16 [%0], {%1,%2,%3,%4};"
                 ::"r"(a), "r"(r0), "r"(r1), "r"(r2), "r"(r3) : "memory");
}
__device__ __forceinline__ void stsm4(uint32_t a, uint32_t r0, uint32_t r1, uint32_t r2, uint32_t r3) {
    asm volatile("stmatrix.sync.aligned.m8n8.x4.shared.b16 [%0], {%1,%2,%3,%4};"
                 ::"r"(a), "r"(r0), "r"(r1), "r"(r2), "r"(r3) : "memory");
}
__device__ __forceinline__ void mma16816(float* c, uint32_t a0, uint32_t a1, uint32_t a2, uint32_t a3, uint32_t b0, uint32_t b1) {
    asm volatile("mma.sync.aligned.m16n8k16.row.col.f32.bf16.bf16.f32 {%0,%1,%2,%3}, {%4,%5,%6,%7}, {%8,%9}, {%0,%1,%2,%3};"
                 : "+f"(c[0]), "+f"(c[1]), "+f"(c[2]), "+f"(c[3]) : "r"(a0), "r"(a1), "r"(a2), "r"(a3), "r"(b0), "r"(b1));
}
__device__ __forceinline__ void mma1688(float* c, uint32_t a0, uint32_t a1, uint32_t b0) {
    asm volatile("mma.sync.aligned.m16n8k8.row.col.f32.bf16.bf16.f32 {%0,%1,%2,%3}, {%4,%5}, {%6}, {%0,%1,%2,%3};"
                 : "+f"(c[0]), "+f"(c[1]), "+f"(c[2]), "+f"(c[3]) : "r"(a0), "r"(a1), "r"(b0));
}
__device__ __forceinline__ void sts128(uint32_t a, float x, float y, float z, float w) {
    asm volatile("st.shared.v4.f32 [%0], {%1,%2,%3,%4};" ::"r"(a), "f"(x), "f"(y), "f"(z), "f"(w) : "memory");
}
__device__ __forceinline__ void sts64(uint32_t a, float x, float y) {
    asm volatile("st.shared.v2.f32 [%0], {%1,%2};" ::"r"(a), "f"(x), "f"(y) : "memory");
}
__device__ __forceinline__ void sts32(uint32_t a, uint32_t x) { asm volatile("st.shared.b32 [%0], %1;" ::"r"(a), "r"(x) : "memory"); }
__device__ __forceinline__ void sts128u(uint32_t a, uint4 v) {
    asm volatile("st.shared.v4.b32 [%0], {%1,%2,%3,%4};" ::"r"(a), "r"(v.x), "r"(v.y), "r"(v.z), "r"(v.w) : "memory");
}
__device__ __forceinline__ float4 lds128(uint32_t a) {
    float4 v; asm volatile("ld.shared.v4.f32 {%0,%1,%2,%3}, [%4];" : "=f"(v.x), "=f"(v.y), "=f"(v.z), "=f"(v.w) : "r"(a) : "memory"); return v;
}
__device__ __forceinline__ uint4 lds128u(uint32_t a) {
    uint4 v; asm volatile("ld.shared.v4.b32 {%0,%1,%2,%3}, [%4];" : "=r"(v.x), "=r"(v.y), "=r"(v.z), "=r"(v.w) : "r"(a) : "memory"); return v;
}
__device__ __forceinline__ uint2 lds64u(uint32_t a) {
    uint2 v; asm volatile("ld.shared.v2.b32 {%0,%1}, [%2];" : "=r"(v.x), "=r"(v.y) : "r"(a) : "memory"); return v;
}
__device__ __forceinline__ float2 lds64(uint32_t a) {
    float2 v; asm volatile("ld.shared.v2.f32 {%0,%1}, [%2];" : "=f"(v.x), "=f"(v.y) : "r"(a) : "memory"); return v;
}
__device__ __forceinline__ uint2 ldg_rlx64(const void* p) {
    uint2 v; asm volatile("ld.relaxed.gpu.global.v2.b32 {%0,%1}, [%2];" : "=r"(v.x), "=r"(v.y) : "l"(p) : "memory"); return v;
}
__device__ __forceinline__ uint4 ldg_rlx128(const void* p) {
    uint4 v; asm volatile("ld.relaxed.gpu.global.v4.b32 {%0,%1,%2,%3}, [%4];" : "=r"(v.x), "=r"(v.y), "=r"(v.z), "=r"(v.w) : "l"(p) : "memory"); return v;
}
__device__ __forceinline__ void stg_rlx64(void* p, uint32_t x, uint32_t y) {
    asm volatile("st.relaxed.gpu.global.v2.b32 [%0], {%1,%2};" ::"l"(p), "r"(x), "r"(y) : "memory");
}
__device__ __forceinline__ void stg_rlx128(void* p, uint32_t x, uint32_t y, uint32_t z, uint32_t w) {
    asm volatile("st.relaxed.gpu.global.v4.b32 [%0], {%1,%2,%3,%4};" ::"l"(p), "r"(x), "r"(y), "r"(z), "r"(w) : "memory");
}
__device__ __forceinline__ uint32_t ldg_rlx32(const void* p) {
    uint32_t v; asm volatile("ld.relaxed.gpu.global.b32 %0, [%1];" : "=r"(v) : "l"(p) : "memory"); return v;
}
__device__ __forceinline__ void stg128(void* p, uint32_t x, uint32_t y, uint32_t z, uint32_t w) {
    asm volatile("st.global.v4.b32 [%0], {%1,%2,%3,%4};" ::"l"(p), "r"(x), "r"(y), "r"(z), "r"(w) : "memory");
}
__device__ __forceinline__ uint32_t ld_acquire(const unsigned* p) {
    uint32_t v; asm volatile("ld.acquire.gpu.global.u32 %0, [%1];" : "=r"(v) : "l"(p) : "memory"); return v;
}
__device__ __forceinline__ void red_add_u32(unsigned* p, uint32_t v) {
    asm volatile("red.relaxed.gpu.global.add.u32 [%0], %1;" ::"l"(p), "r"(v) : "memory");
}
__device__ __forceinline__ void wait_counter(const unsigned* p, uint32_t target) {
    uint32_t n = 0;
    while (ld_acquire(p) < target) { if (++n > SPIN_LIMIT) __trap(); }
}

__device__ __forceinline__ void wg_fence() { asm volatile("wgmma.fence.sync.aligned;" ::: "memory"); }
__device__ __forceinline__ void wg_commit() { asm volatile("wgmma.commit_group.sync.aligned;" ::: "memory"); }
template <int N> __device__ __forceinline__ void wg_wait() { asm volatile("wgmma.wait_group.sync.aligned %0;" ::"n"(N) : "memory"); }
__host__ __device__ constexpr uint64_t mkdesc(uint32_t addr, uint32_t lbo, uint32_t sbo, uint32_t swz) {
    return (uint64_t)((addr & 0x3FFFF) >> 4) | ((uint64_t)(lbo >> 4) << 16) | ((uint64_t)(sbo >> 4) << 32) | ((uint64_t)swz << 62);
}
#define F4(d, o) "+f"(d[o]), "+f"(d[o + 1]), "+f"(d[o + 2]), "+f"(d[o + 3])
template <int SC> __device__ __forceinline__ void wg_rs32(float (&d)[16], const uint32_t (&a)[4], uint64_t db) {
    asm volatile("wgmma.mma_async.sync.aligned.m64n32k16.f32.bf16.bf16 "
                 "{%0,%1,%2,%3,%4,%5,%6,%7,%8,%9,%10,%11,%12,%13,%14,%15}, {%16,%17,%18,%19}, %20, %21, 1, 1, 0;"
                 : F4(d, 0), F4(d, 4), F4(d, 8), F4(d, 12)
                 : "r"(a[0]), "r"(a[1]), "r"(a[2]), "r"(a[3]), "l"(db), "n"(SC));
}
template <int SC> __device__ __forceinline__ void wg_rs40(float (&d)[20], const uint32_t (&a)[4], uint64_t db) {
    asm volatile("wgmma.mma_async.sync.aligned.m64n40k16.f32.bf16.bf16 "
                 "{%0,%1,%2,%3,%4,%5,%6,%7,%8,%9,%10,%11,%12,%13,%14,%15,%16,%17,%18,%19}, {%20,%21,%22,%23}, %24, %25, 1, 1, 0;"
                 : F4(d, 0), F4(d, 4), F4(d, 8), F4(d, 12), F4(d, 16)
                 : "r"(a[0]), "r"(a[1]), "r"(a[2]), "r"(a[3]), "l"(db), "n"(SC));
}
template <int SC> __device__ __forceinline__ void wg_ss40(float (&d)[20], uint64_t da, uint64_t db) {
    asm volatile("wgmma.mma_async.sync.aligned.m64n40k16.f32.bf16.bf16 "
                 "{%0,%1,%2,%3,%4,%5,%6,%7,%8,%9,%10,%11,%12,%13,%14,%15,%16,%17,%18,%19}, %20, %21, %22, 1, 1, 1, 0;"
                 : F4(d, 0), F4(d, 4), F4(d, 8), F4(d, 12), F4(d, 16)
                 : "l"(da), "l"(db), "n"(SC));
}
template <int SC> __device__ __forceinline__ void wg_ss8(float (&d)[4], uint64_t da, uint64_t db) {
    asm volatile("wgmma.mma_async.sync.aligned.m64n8k16.f32.bf16.bf16 {%0,%1,%2,%3}, %4, %5, %6, 1, 1, 1, 1;"
                 : F4(d, 0) : "l"(da), "l"(db), "n"(SC));
}

constexpr int DBG_N = 12;
#define TSI(st) do {} while (0)
#define TS(k) do {} while (0)
#define TSV(k, v) do {} while (0)
#define TSDUMP() do {} while (0)
#define GT(k) do {} while (0)
#define FLAG(b) false

__device__ uint4 g_fy[2048 * 128];

constexpr uint32_t FG_SIZE = 2 * 32768 + 36864;
constexpr uint32_t FT_F16 = 2 * FG_SIZE, FT_B1F = FT_F16 + 2048, FT_B1I = FT_B1F + 2048, FT_C = FT_B1I + 2048, FT_A8 = FT_C + 2048,
                   FT_TWC = FT_A8 + 512, FT_TWB = FT_TWC + 8192, FT_BAR = FT_TWB + 8192, FFT_SMEM = FT_BAR + 256;
struct FftMaps { CUtensorMap x, y, o, y2, wr, wi; };

__device__ __forceinline__ float2 wroot(int e) {
    float s, c; sincospif((float)(e & 2047) * (-1.f / 1024.f), &s, &c); return make_float2(c, s);
}
__device__ __forceinline__ uint4 afrag(float2 a, float2 b) {
    return make_uint4(pack_bf16(a.x, -a.y), pack_bf16(a.y, a.x), pack_bf16(b.x, -b.y), pack_bf16(b.y, b.x));
}
__device__ __forceinline__ uint4 conjfrag(uint4 v) { return make_uint4(v.x ^ 0x80000000u, v.y ^ 0x8000u, v.z ^ 0x80000000u, v.w ^ 0x8000u); }
__device__ __forceinline__ uint4 negfrag(uint4 v) { return make_uint4(v.x ^ 0x80008000u, v.y ^ 0x80008000u, v.z ^ 0x80008000u, v.w ^ 0x80008000u); }
__device__ __forceinline__ uint32_t comp(const uint4& v, int i) { return i == 0 ? v.x : i == 1 ? v.y : i == 2 ? v.z : v.w; }
__device__ __forceinline__ void setcomp(uint4& v, int i, uint32_t x) { if (i == 0) v.x = x; else if (i == 1) v.y = x; else if (i == 2) v.z = x; else v.w = x; }
__device__ __forceinline__ float2 cmul(float2 a, float2 b) { return make_float2(a.x * b.x - a.y * b.y, a.x * b.y + a.y * b.x); }
__device__ __forceinline__ float2 cmulc(float2 a, float2 b) { return make_float2(a.x * b.x + a.y * b.y, a.y * b.x - a.x * b.y); }

__device__ __forceinline__ uint32_t pack_h2(float2 a) { uint32_t r; asm("cvt.rn.f16x2.f32 %0, %1, %2;" : "=r"(r) : "f"(a.y), "f"(a.x)); return r; }
__device__ __forceinline__ float2 unpack_h2(uint32_t v) {
    float2 r; asm("{\n.reg .b16 l, h;\nmov.b32 {l, h}, %2;\ncvt.f32.f16 %0, l;\ncvt.f32.f16 %1, h;\n}" : "=f"(r.x), "=f"(r.y) : "r"(v)); return r;
}
__device__ __forceinline__ void fft_tables(uint32_t tb, int tid, int nthr) {
    for (int i = tid; i < 128; i += nthr) {
        const int lane = i & 31, q = i >> 5, g = lane >> 2, t = lane & 3, o = 8 * (q >> 1) + g, in = 8 * (q & 1) + 2 * t;
        sts128u(tb + FT_F16 + i * 16, afrag(wroot(128 * o * in), wroot(128 * o * (in + 1))));
        sts128u(tb + FT_B1F + i * 16, afrag(wroot(64 * (1 + 2 * o) * in), wroot(64 * (1 + 2 * o) * (in + 1))));
        sts128u(tb + FT_B1I + i * 16, afrag(wroot(-64 * o * (1 + 2 * in)), wroot(-64 * o * (3 + 2 * in))));
        uint4 v;
        for (int r = 0; r < 4; r++) {
            const float2 a = wroot(128 * (4 * r + t) * (4 * q + (g >> 1)));
            setcomp(v, r, (g & 1) ? pack_bf16(a.y, a.x) : pack_bf16(a.x, -a.y));
        }
        sts128u(tb + FT_C + i * 16, v);
        if (q == 0) sts128u(tb + FT_A8 + lane * 16, afrag(wroot(256 * g * 2 * t), wroot(256 * g * (2 * t + 1))));
    }
    for (int i = tid; i < 512; i += nthr) {
        const int lane = i & 31, r = (i >> 5) & 3, phi = 8 * (i >> 7) + (lane >> 2), c = 4 * r + (lane & 3);
        const float2 a = wroot(4 * c * phi), b = wroot(2 * (phi + 32 * c));
        constexpr float SC = 1.f / (2.f * 2048.f * 512.f);
        sts128(tb + FT_TWC + i * 16, a.x * SC, a.y * SC, b.x, b.y);
    }
    for (int i = tid; i < 512; i += nthr) {
        const int lane = i & 31, r = (i >> 5) & 3, fa = (i >> 7) & 1, hf = i >> 8, c = 8 * (lane & 1) + r;
        const int p0 = fa + 2 * (lane >> 2), p1 = p0 + 16, s0 = (hf && p0) ? 32 - p0 : p0, s1 = hf ? 32 - p1 : p1;
        sts128u(tb + FT_TWB + i * 16, make_uint4(pack_h2(wroot(4 * c * s0)), pack_h2(wroot(4 * (c + 4) * s0)),
                                                 pack_h2(wroot(4 * c * s1)), pack_h2(wroot(4 * (c + 4) * s1))));
    }
}

template <bool TW>
__device__ __forceinline__ void dft16(uint4 (&out)[4], const uint4 (&in)[4], const uint4 (&m)[4], const uint4 (&tw)[4]) {
#pragma unroll
    for (int i = 0; i < 4; i++)
#pragma unroll
        for (int mt = 0; mt < 2; mt++) {
            float c[4] = {0.f, 0.f, 0.f, 0.f};
            mma16816(c, m[2 * mt].x, m[2 * mt].y, m[2 * mt].z, m[2 * mt].w, comp(in[0], i), comp(in[1], i));
            mma16816(c, m[2 * mt + 1].x, m[2 * mt + 1].y, m[2 * mt + 1].z, m[2 * mt + 1].w, comp(in[2], i), comp(in[3], i));
            if (TW) {
                const float2 a = cmul(make_float2(c[0], c[2]), unpack_h2(comp(tw[i], 2 * mt))), b = cmul(make_float2(c[1], c[3]), unpack_h2(comp(tw[i], 2 * mt + 1)));
                setcomp(out[2 * mt], i, pack_bf16(a.x, a.y));
                setcomp(out[2 * mt + 1], i, pack_bf16(b.x, b.y));
            } else {
                setcomp(out[2 * mt], i, pack_bf16(c[0], c[2]));
                setcomp(out[2 * mt + 1], i, pack_bf16(c[1], c[3]));
            }
        }
}
__device__ __forceinline__ void tma_ld4(uint32_t dst, const CUtensorMap* m, int c0, int c1, uint32_t bar) {
    asm volatile("cp.async.bulk.tensor.4d.shared::cluster.global.mbarrier::complete_tx::bytes [%0], [%1, {%3, %4, %5, %5}], [%2];"
                 ::"r"(dst), "l"(m), "r"(bar), "r"(c0), "r"(c1), "r"(0) : "memory");
}
__device__ __forceinline__ void tma_st4(uint32_t src, const CUtensorMap* m, int c0, int c1) {
    asm volatile("cp.async.bulk.tensor.4d.global.shared::cta.bulk_group [%1, {%2, %3, %4, %4}], [%0];" ::"r"(src), "l"(m), "r"(c0), "r"(c1), "r"(0) : "memory");
}
__device__ __forceinline__ void tma_ld3(uint32_t dst, const CUtensorMap* m, int c0, int c1, uint32_t bar) {
    asm volatile("cp.async.bulk.tensor.3d.shared::cluster.global.mbarrier::complete_tx::bytes [%0], [%1, {%3, %4, %5}], [%2];"
                 ::"r"(dst), "l"(m), "r"(bar), "r"(c0), "r"(c1), "r"(0) : "memory");
}
__device__ __forceinline__ void tma_st3(uint32_t src, const CUtensorMap* m, int c0, int c1) {
    asm volatile("cp.async.bulk.tensor.3d.global.shared::cta.bulk_group [%1, {%2, %3, %4}], [%0];" ::"r"(src), "l"(m), "r"(c0), "r"(c1), "r"(0) : "memory");
}
__device__ __forceinline__ void bulk_commit() { asm volatile("cp.async.bulk.commit_group;" ::: "memory"); }
__device__ __forceinline__ void bulk_wait_read() { asm volatile("cp.async.bulk.wait_group.read 0;" ::: "memory"); }
__device__ __forceinline__ void bulk_wait_all() { asm volatile("cp.async.bulk.wait_group 0;" ::: "memory"); }

template <bool INV>
__device__ __forceinline__ void fft_col(int s2, const CUtensorMap* src, const CUtensorMap* dst, uint32_t tb, uint32_t gb, uint32_t mb,
                                        int w, int lane, int bar) {
    const int g = lane >> 2, t = lane & 3;
    const bool lead = w == 0 && lane == 0;
    if (lead)
        for (int i = 0; i < 2; i++) { mbar_expect_tx(mb + 8 * i, 32768); tma_ld4(gb + i * 32768, src, i * 64, s2, mb + 8 * i); }
    uint4 f[4], m[2][4];
#pragma unroll
    for (int i = 0; i < 4; i++) {
        f[i] = lds128u(tb + FT_F16 + i * 512 + lane * 16);
        if (INV) f[i] = conjfrag(f[i]);
#pragma unroll
        for (int q = 0; q < 2; q++) {
            const int o = 8 * (i >> 1) + g, in = 8 * (i & 1) + 2 * t, z = 2 * w + q;
            m[q][i] = INV ? afrag(wroot(-(8 * o + s2) * (z + 16 * in)), wroot(-(8 * o + s2) * (z + 16 * in + 16)))
                          : afrag(wroot((z + 16 * o) * (8 * in + s2)), wroot((z + 16 * o) * (8 * in + 8 + s2)));
        }
    }
    const uint32_t r1 = (32 * w + 2 * t) * 128 + ((g ^ (2 * t)) << 4);
    const uint32_t w1 = (32 * w + g) * 128 + (((2 * t) ^ (((w & 3) << 1) | (g & 1))) << 4);
    const uint32_t r2 = (32 * t + 2 * w) * 128 + ((g ^ (2 * t)) << 4);
    const uint32_t w2 = (32 * w + g) * 128 + (((2 * t) ^ g) << 4);
    int bi = 0, ph = 0;
#pragma unroll 1
    for (int it = 0; it < 16; it++) {
        const uint32_t buf = gb + bi * 32768;
        mbar_wait(mb + 8 * bi, ph);
        uint4 in[2][4], out[4];
#pragma unroll
        for (int q = 0; q < 2; q++)
#pragma unroll
            for (int i = 0; i < 4; i++) in[q][i] = lds128u(buf + (r1 ^ ((i & 1) * 0x90)) + (i >> 1) * 1024 + q * 2048);
        __syncwarp();
#pragma unroll
        for (int q = 0; q < 2; q++) {
            if (INV) dft16<false>(out, in[q], m[q], f); else dft16<false>(out, in[q], f, f);
#pragma unroll
            for (int i = 0; i < 4; i++) sts128u(buf + (w1 ^ ((i & 1) << 4)) + (i >> 1) * 1024 + q * 2048, out[i]);
        }
        bar_sync(bar, 256);
#pragma unroll
        for (int q = 0; q < 2; q++)
#pragma unroll
            for (int i = 0; i < 4; i++) in[q][i] = lds128u(buf + (r2 ^ (q * 0x90)) + (i & 1) * 2048 + (i >> 1) * 16384);
        const int bn = bi == 0 ? 2 : bi - 1;
        if (lead && it < 14) { bulk_wait_read(); mbar_expect_tx(mb + 8 * bn, 32768); tma_ld4(gb + bn * 32768, src, (it + 2) * 64, s2, mb + 8 * bn); }
        bar_sync(bar, 256);
#pragma unroll
        for (int q = 0; q < 2; q++) {
            if (INV) dft16<false>(out, in[q], f, f); else dft16<false>(out, in[q], m[q], f);
#pragma unroll
            for (int i = 0; i < 4; i++) sts128u(buf + (w2 ^ ((i & 1) << 4)) + (i >> 1) * 1024 + q * 2048, out[i]);
        }
        fence_async_smem();
        bar_sync(bar, 256);
        if (lead) { tma_st4(buf, dst, it * 64, s2); bulk_commit(); }
        if (++bi == 3) { bi = 0; ph ^= 1; }
    }
    if (lead) bulk_wait_all();
}

__device__ __forceinline__ float ldw(uint32_t a) {
    uint16_t v; asm volatile("ld.shared.u16 %0, [%1];" : "=h"(v) : "r"(a) : "memory");
    return __uint_as_float((uint32_t)v << 16);
}
__device__ __forceinline__ void fft_mid(int grp, const FftMaps& fm, uint32_t tb,
                                        uint32_t gb, uint32_t mb, uint32_t& cnt, int w, int lane, int bar) {
    const int g = lane >> 2, t = lane & 3;
    const bool lead = w == 0 && lane == 0;
    const uint32_t wb = gb + 65536;
#define MID_LOAD(k, c)                                                                                                  \
    { mbar_expect_tx(mb + 8 * ((c) & 1), 32768);                                                                        \
      tma_ld3(gb + ((c) & 1) * 32768, &fm.y2, 0, (k) * 8, mb + 8 * ((c) & 1));                                          \
      tma_ld3(gb + ((c) & 1) * 32768 + 16384, &fm.y2, 0, ((256 - (k)) & 255) * 8, mb + 8 * ((c) & 1)); }
#define MID_LOADW(k)                                                                                                    \
    { mbar_expect_tx(mb + 16, 36864);                                                                                   \
      tma_ld3(wb, &fm.wr, (k) * 513 & ~7, 0, mb + 16); tma_ld3(wb + 9216, &fm.wi, (k) * 513 & ~7, 0, mb + 16);          \
      tma_ld3(wb + 18432, &fm.wr, ((256 - (k)) & 255) * 513 & ~7, 0, mb + 16); tma_ld3(wb + 27648, &fm.wi, ((256 - (k)) & 255) * 513 & ~7, 0, mb + 16); }
    if (lead) { MID_LOAD(grp, cnt); MID_LOADW(grp); }
    const int hB = w >> 2, faB = (w >> 1) & 1, xB = faB;
    const int phi = 8 * (w & 3) + g;
    const uint32_t rA = (8 * w + 2 * t) * 128 + ((g ^ (2 * t)) << 4);
    const uint32_t wA = (8 * w + g) * 128 + (((2 * t) ^ ((g & 1) | ((w & 3) << 1))) << 4);
    const uint32_t oB = (w >> 1) * 8192 + (w & 1) * 512;
    const uint32_t rB = oB + (8 * t + (g >> 2)) * 128 + (((g & 3) ^ ((g >> 2) | (t << 1)) ^ xB) << 4);
    const uint32_t wB = oB + (8 * (g >> 1) + (t >> 1)) * 128 + (((((g & 1) << 2) | (2 * (t & 1))) ^ ((t >> 1) | ((g >> 1) << 1)) ^ xB) << 4);
    const uint32_t wBi = oB + (8 * (g >> 1) + (t >> 1)) * 128 + (((((g & 1) << 2) | (2 * (t & 1))) ^ ((t >> 1) | ((w & 1) << 2))) << 4);
    const int hC = (lane >> 3) & 1, pr = 8 * (w & 3) + (lane & 7), pc = hC ? (32 - pr) & 31 : pr;
    const uint32_t aC = hC * 16384 + (pc & 1) * 8192 + (pc >> 2) * 1024 + (((((pc & 2) << 1) | (lane >> 4)) ^ (((pc >> 2) & 3) << 1) ^ (pc & 1)) << 4);
    const uint32_t g0 = wb + (t >> 1) * 144 + (32 * (t & 1) + phi) * 2, g1 = wb + 18432 + (7 - (t >> 1)) * 144 + (64 - 32 * (t & 1) - phi) * 2;
    const uint32_t wAo = (8 * w + g) * 128 + (((2 * t) ^ g) << 4);
    uint32_t wph = 0;
#pragma unroll 1
    for (int k1 = grp; k1 < 129; k1 += 8, cnt++, wph ^= 1) {
        const uint32_t buf = gb + (cnt & 1) * 32768;
        uint4 in[2][4], m[4], out[4];
        m[0] = m[1] = m[2] = lds128u(tb + FT_A8 + lane * 16);
        m[3] = negfrag(m[0]);
        mbar_wait(mb + 8 * (cnt & 1), (cnt >> 1) & 1);
#pragma unroll
        for (int q = 0; q < 2; q++)
#pragma unroll
            for (int i = 0; i < 4; i++) in[q][i] = lds128u(buf + (rA ^ ((i & 1) * 0x90)) + (i >> 1) * 8192 + q * 16384);
        __syncwarp();
#pragma unroll
        for (int q = 0; q < 2; q++) {
            dft16<false>(out, in[q], m, m);
#pragma unroll
            for (int i = 0; i < 4; i++) sts128u(buf + (wA ^ (((i ^ (i >> 1)) & 1) << 4)) + (i >> 1) * 8192 + q * 16384, out[i]);
        }
        {
            uint4 tw[4];
#pragma unroll
            for (int i = 0; i < 4; i++) {
                m[i] = lds128u(tb + (faB ? FT_B1F : FT_F16) + i * 512 + lane * 16);
                if (hB) { m[i].y ^= 0x80008000u; m[i].w ^= 0x80008000u; }
                tw[i] = lds128u(tb + FT_TWB + (w >> 1) * 2048 + i * 512 + lane * 16);
            }
            bar_sync(bar, 256);
#pragma unroll
            for (int q = 0; q < 2; q++)
#pragma unroll
                for (int i = 0; i < 4; i++) in[q][i] = lds128u(buf + (rB ^ ((i & 1) << 6)) + (i >> 1) * 4096 + q * 256);
            __syncwarp();
#pragma unroll
            for (int q = 0; q < 2; q++) {
                dft16<true>(out, in[q], m, tw);
#pragma unroll
                for (int i = 0; i < 4; i++) sts128u(buf + (wB ^ ((i & 1) << 4)) + (i >> 1) * 4096 + q * 256, out[i]);
            }
        }
        {
            const uint32_t cjm = (g & 1) ? 0x8000u : 0x80000000u;
            float4 tw[4];
#pragma unroll
            for (int i = 0; i < 4; i++) { m[i] = lds128u(tb + FT_C + i * 512 + lane * 16); tw[i] = lds128(tb + FT_TWC + ((w & 3) * 4 + i) * 512 + lane * 16); }
            if (lead && k1 + 8 < 129) { bulk_wait_read(); MID_LOAD(k1 + 8, cnt + 1); }
            __syncwarp();
            mbar_wait(mb + 16, wph);
            const uint32_t o0 = (k1 & 7) * 2, o1 = (-k1 & 7) * 2;
            if (w == 1 && lane < 16) {
                const int k2 = lane & 7, k2p = k1 ? 7 - k2 : (8 - k2) & 7;
                const uint32_t p0 = wb + (lane >> 3) * 9216 + k2 * 1152 + o0, p1 = wb + 18432 + (lane >> 3) * 9216 + k2p * 1152 + o1;
                const float sg = lane < 8 ? 0.5f : -0.5f;
                const uint32_t v = pack_bf16(0.5f * ldw(p0) + sg * ldw(p1), 0.5f * ldw(p1 + 1136) + sg * ldw(p0 + 1136));
                asm volatile("st.shared.u16 [%0], %1;" ::"r"(p0), "h"((uint16_t)v) : "memory");
                asm volatile("st.shared.u16 [%0], %1;" ::"r"(p1 + 1136), "h"((uint16_t)(v >> 16)) : "memory");
                fence_async_smem();
            }
            bar_sync(bar, 256);
#define FFT_CU 2
            constexpr int CU = FFT_CU;
#pragma unroll CU
            for (int q = 0; q < 4; q++) {
                const int k2 = 4 * (w >> 2) + q, k2p = k1 ? 7 - k2 : (8 - k2) & 7, kr = hC ? k2p : k2;
                const uint32_t a0 = buf + (aC ^ ((kr & 1) << 4)) + kr * 128;
                const uint32_t r0 = g0 + k2 * 1152 + o0, r1 = g1 + k2p * 1152 + o1;
                uint32_t x[4], y[4];
                ldsm4(x, a0); ldsm4(y, a0 ^ 32);
                float c[4][4];
#pragma unroll
                for (int i = 0; i < 4; i++) { c[i][0] = c[i][1] = c[i][2] = c[i][3] = 0.f; mma16816(c[i], x[0], x[1], x[2], x[3], m[i].x, m[i].y); }
#pragma unroll
                for (int i = 0; i < 4; i++) mma16816(c[i], y[0], y[1], y[2], y[3], m[i].z, m[i].w);
#pragma unroll
                for (int i = 0; i < 4; i++) {
                    const float2 ga = make_float2(ldw(r0 + i * 288), ldw(r0 + 9216 + i * 288));
                    const float2 gc = make_float2(ldw(r1 - i * 288), ldw(r1 + 9216 - i * 288));
                    const float tc = tw[i].z, ts = tw[i].w;
                    const float* z = c[i];
                    const float2 S = make_float2(ga.x + gc.x, ga.y - gc.y), D = make_float2(ga.x - gc.x, ga.y + gc.y);
                    const float2 u = make_float2(ts * z[0] - tc * z[3], ts * z[1] + tc * z[2]), v = make_float2(ts * z[2] - tc * z[1], ts * z[3] + tc * z[0]);
                    uint32_t* o = (i < 2 ? x : y) + 2 * (i & 1);
                    o[0] = pack_bf16(fmaf(S.x, z[0], fmaf(-S.y, z[1], fmaf(D.x, u.x, -D.y * u.y))), fmaf(S.x, z[1], fmaf(S.y, z[0], fmaf(D.x, u.y, D.y * u.x))));
                    o[1] = pack_bf16(fmaf(S.x, z[2], fmaf(-S.y, z[3], fmaf(-D.x, v.x, D.y * v.y))), fmaf(S.x, z[3], fmaf(S.y, z[2], fmaf(-D.x, v.y, -D.y * v.x))));
                }
#pragma unroll
                for (int i = 0; i < 4; i++) { c[i][0] = c[i][1] = c[i][2] = c[i][3] = 0.f; mma16816(c[i], x[0], x[1], x[2], x[3], m[i].x ^ cjm, m[i].y ^ cjm); }
#pragma unroll
                for (int i = 0; i < 4; i++) mma16816(c[i], y[0], y[1], y[2], y[3], m[i].z ^ cjm, m[i].w ^ cjm);
#pragma unroll
                for (int i = 0; i < 4; i++) {
                    uint32_t* o = (i < 2 ? x : y) + 2 * (i & 1);
                    o[0] = pack_bf16(c[i][0] * tw[i].x + c[i][1] * tw[i].y, c[i][1] * tw[i].x - c[i][0] * tw[i].y);
                    o[1] = pack_bf16(c[i][2] * tw[i].x + c[i][3] * tw[i].y, c[i][2] * tw[i].y - c[i][3] * tw[i].x);
                }
                stsm4(a0, x[0], x[1], x[2], x[3]);
                stsm4(a0 ^ 32, y[0], y[1], y[2], y[3]);
            }
        }
#pragma unroll
        for (int i = 0; i < 4; i++) { m[i] = lds128u(tb + (faB ? FT_B1I : FT_F16) + i * 512 + lane * 16); if (!faB) m[i] = conjfrag(m[i]); }
        bar_sync(bar, 256);
        if (lead && k1 + 8 < 129) MID_LOADW(k1 + 8);
        __syncwarp();
#pragma unroll
        for (int q = 0; q < 2; q++)
#pragma unroll
            for (int i = 0; i < 4; i++) in[q][i] = lds128u(buf + (rB ^ ((i & 1) << 6)) + (i >> 1) * 4096 + q * 256);
        __syncwarp();
#pragma unroll
        for (int q = 0; q < 2; q++) {
            dft16<false>(out, in[q], m, m);
#pragma unroll
            for (int i = 0; i < 4; i++) sts128u(buf + (wBi ^ ((i & 1) << 4) ^ (q << 5)) + (i >> 1) * 4096 + q * 256, out[i]);
        }
        m[0] = m[1] = m[2] = conjfrag(lds128u(tb + FT_A8 + lane * 16));
        m[3] = negfrag(m[0]);
        bar_sync(bar, 256);
#pragma unroll
        for (int q = 0; q < 2; q++)
#pragma unroll
            for (int i = 0; i < 4; i++) in[q][i] = lds128u(buf + (rA ^ ((i & 1) * 0x90)) + (i >> 1) * 8192 + q * 16384);
        __syncwarp();
#pragma unroll
        for (int q = 0; q < 2; q++) {
            dft16<false>(out, in[q], m, m);
#pragma unroll
            for (int i = 0; i < 4; i++) sts128u(buf + (wAo ^ ((i & 1) << 4)) + (i >> 1) * 8192 + q * 16384, out[i]);
        }
        fence_async_smem();
        bar_sync(bar, 256);
        if (lead) {
            tma_st3(buf, &fm.y2, 0, k1 * 8);
            if (k1 & 127) tma_st3(buf + 16384, &fm.y2, 0, (256 - k1) * 8);
            bulk_commit();
        }
    }
    if (lead) bulk_wait_all();
}

__device__ unsigned g_fbar;
__device__ __forceinline__ void fft_group_barrier(unsigned& base, int first, int w, int lane) {
    if (w == 0) {
        unsigned v = 0;
        if (lane == 0) { asm volatile("fence.proxy.async;" ::: "memory"); fence_gpu(); v = atomicAdd(&g_fbar, 1); }
        v = __shfl_sync(~0u, v, 0);
        if (first) base = v & ~15u;
        const unsigned target = base + (first ? 8 : 16);
        uint32_t n = 0;
        while (__any_sync(~0u, (int)(ld_acquire(&g_fbar) - target) < 0)) { __nanosleep(200); if (++n > SPIN_LIMIT) __trap(); }
        asm volatile("fence.proxy.async;" ::: "memory");
    }
}
__device__ __forceinline__ void fft_all(int cta, const FftMaps& fm, uint32_t sb) {
    if (threadIdx.x < 32) mbar_init(sb + FT_BAR + 8 * threadIdx.x, 1);
    fft_tables(sb, threadIdx.x, 512);
    fence_async_smem();
    __syncthreads();
    const int hi = __shfl_sync(~0u, threadIdx.x >> 8, 0), w = __shfl_sync(~0u, (threadIdx.x >> 5) & 7, 0), lane = threadIdx.x & 31;
    const int grp = cta * 2 + hi, bar = 1 + hi;
    const uint32_t gb = sb + hi * FG_SIZE, mb = sb + FT_BAR + hi * 128;
    unsigned base = 0;
    uint32_t cnt = 0;
    fft_col<false>(grp, &fm.x, &fm.y, sb, gb, mb + 32, w, lane, bar);
    fft_group_barrier(base, 1, w, lane);
    GT(1);
    fft_mid(grp, fm, sb, gb, mb, cnt, w, lane, bar);
    fft_group_barrier(base, 0, w, lane);
    GT(2);
    fft_col<true>(grp, &fm.y, &fm.o, sb, gb, mb + 64, w, lane, bar);
}

__device__ uint4 g_kvq[4 * 32 * 3 * 8 * 2 * 32];
__device__ uint2 g_alpha[2 * 32 * 3 * 8 * 2 * 32];
__device__ uint4 g_red[5 * 32768 / 16];
__device__ uint4 g_stamp[32];
__device__ uint4 g_qst[128 * 2];
__device__ unsigned g_start;
__device__ bf16 g_ox[2048 * 4096];
struct Tune { uint32_t d_alpha, d_r0, d_r1, flags, d_st, d_v, spread, extra; };
#define QKW_EARLY 1
constexpr int RA = 2;
#define AV_POS 2

constexpr uint32_t SM_BASE = 1024;
constexpr uint32_t O_WO = 0;
constexpr uint32_t O_WV = 65536;
constexpr uint32_t O_XB = 131072;
constexpr uint32_t O_MEM = O_XB + 32768;
constexpr uint32_t O_RECV = O_MEM + 8192;
constexpr uint32_t O_KVQ = O_RECV + 12288;
constexpr uint32_t O_STG = O_KVQ + 18432;
constexpr uint32_t O_S = O_STG + 8192;
constexpr uint32_t O_XO = O_STG + 16384;
constexpr uint32_t O_P = O_S + 10240;
constexpr uint32_t O_O = O_P + 1536;
constexpr uint32_t O_VM = O_O + 2048;
constexpr uint32_t O_QST = O_VM + 2048;
constexpr uint32_t O_BAR = O_QST + 128;
constexpr uint32_t O_DBG = O_BAR + 256;
constexpr uint32_t RMT_SMEM = O_DBG + (DBG_TIMING ? 4 * DBG_N * 24 * 4 : 0);
constexpr uint32_t MAIN_SMEM = RMT_SMEM > FFT_SMEM ? RMT_SMEM : FFT_SMEM;
static_assert(MAIN_SMEM <= 232448, "smem");
enum { B_WQ0 = 0, B_WQ1, B_WK0, B_WK1, B_WV, B_WO, B_QDONE, B_KDONE, B_XFULL, B_XEMPTY, B_MEM, B_RFULL, B_AFULL, B_KVFULL,
       B_RECV, B_QKW = B_RECV + 6, B_SDONE, B_SRDY, B_OPDONE, B_COUNT };

constexpr float SM_SCALE_LOG2 = 0.08838834764831845f * 1.4426950408889634f;
constexpr float MASK_VAL = -1.0e9f / 0.08838834764831845f;

__device__ __forceinline__ uint32_t red_grp(int grp) { return (uint32_t)((grp >> 1) * 1024 + (grp & 1) * 256); }
__host__ __device__ constexpr uint64_t xdesc(int ks) { return mkdesc(SM_BASE + O_XB + (ks >> 2) * 1024 + (ks & 3) * 32, 16, 8192, 1); }

__device__ __forceinline__ void x_split(const float* d, uint32_t (&sn)[4], uint32_t (&kp)[4], int kh) {
#pragma unroll
    for (int i = 0; i < 4; i++) {
        const uint32_t lo = pack_bf16(d[2 * i], d[2 * i + 1]), hi = pack_bf16(d[8 + 2 * i], d[8 + 2 * i + 1]);
        sn[i] = kh ? lo : hi; kp[i] = kh ? hi : lo;
    }
}
__device__ __forceinline__ void x_send(int R, const uint32_t (&sn)[4], int sg, int tid, uint32_t sb, uint32_t mate) {
    const uint32_t par = sg & 1;
    const uint32_t bar = O_BAR + 8 * (B_RECV + R * 2) + 8 * par;
    if (tid == 0) mbar_expect_tx(sb + bar, 2048);
    asm volatile("st.async.shared::cluster.mbarrier::complete_tx::bytes.v4.b32 [%0], {%1,%2,%3,%4}, [%5];"
                 ::"r"(mate + O_RECV + (par * 3 + R) * 2048 + tid * 16), "r"(sn[0]), "r"(sn[1]), "r"(sn[2]), "r"(sn[3]), "r"(mate + bar) : "memory");
}
__device__ __forceinline__ void x_wait(int R, int sg, uint32_t sb) {
    mbar_wait_cluster(sb + O_BAR + 8 * (B_RECV + R * 2) + 8 * (sg & 1), (sg >> 1) & 1);
}
template <int R>
__device__ __forceinline__ void x_finish(const uint32_t (&kp)[4], int sg, int h, int mt, int kh, int tid, uint32_t sb) {
    const uint4 r = lds128u(sb + O_RECV + ((sg & 1) * 3 + R) * 2048 + tid * 16);
    uint32_t u0 = add_bf16x2(kp[0], r.x), u1 = add_bf16x2(kp[1], r.y), u2 = add_bf16x2(kp[2], r.z), u3 = add_bf16x2(kp[3], r.w);
    if (R < 2) { u0 = movm(u0); u1 = movm(u1); u2 = movm(u2); u3 = movm(u3); }
    const uint32_t tag = ((sg >> 2) & 1) ^ 1;
    u0 = (u0 & ~1u) | tag;
    uint4* const hb = &g_kvq[((sg & 3) * 32 + h) * (3 * 512)];
    if (R == 0) {
        uint2* p = (uint2*)hb + (kh * 16 + mt) * 32 + (tid & 31);
        asm volatile("{\n.reg .pred p;\nsetp.lt.s32 p, %5, 64;\n@p st.relaxed.gpu.global.v2.b32 [%0], {%1,%2};\n@p st.relaxed.gpu.global.v2.b32 [%0+2048], {%3,%4};\n}"
                     ::"l"(p), "r"(u0), "r"(u1), "r"((u2 & ~1u) | tag), "r"(u3), "r"(sg) : "memory");
    } else {
        asm volatile("{\n.reg .pred p;\nsetp.lt.s32 p, %5, 64;\n@p st.relaxed.gpu.global.v4.b32 [%0], {%1,%2,%3,%4};\n}"
                     ::"l"(hb + R * 512 + (mt * 2 + kh) * 32 + (tid & 31)), "r"(u0), "r"(u1), "r"(u2), "r"(u3), "r"(sg) : "memory");
    }
}

__device__ __forceinline__ uint32_t convert_mem(const unsigned char* redp, int s, int kh, int jj, int w, int lane, uint32_t sb) {
    const uint32_t off = red_grp(jj * 16 + w * 4 + (lane >> 3)), o16 = off + (lane & 7) * 16, o8 = off + 512 + ((lane >> 3) & 1) * 64 + (lane & 7) * 8;
    uint32_t ma = sb + O_MEM + (jj * 4 + (lane >> 4)) * 1024 + (lane & 7) * 128 + (((2 * w + ((lane >> 3) & 1)) ^ (lane & 7)) << 4);
    uint32_t a16 = sb + O_STG + o16, a8 = sb + O_STG + o8;
    const uint32_t target = (s & 4) ? 0x42C00000u : 0x42000000u;
    asm volatile("" : "+r"(ma), "+r"(a16), "+r"(a8));
    mbar_wait(sb + O_BAR + 8 * B_RFULL, s & 1);
    uint4 ra = lds128u(a16), rb = lds128u(a16 + 128);
    uint2 rc = lds64u(a8);
    uint32_t n = 0;
    while (true) {
        stsm4t(ma, ra.x, ra.y, ra.z, __byte_perm(ra.w, rc.x, 0x5410));
        stsm4t(ma + 2048, rb.x, rb.y, rb.z, __byte_perm(rb.w, rc.x, 0x7610));
        if (__builtin_expect(!__any_sync(~0u, orx(orx2(ra.w, rb.w, target), rc.y, target) > 0xffffu), 1)) break;
        const unsigned char* pg = redp + (s & 3) * 32768 + kh * 16384;
        ra = ldg_rlx128(pg + o16); rb = ldg_rlx128(pg + o16 + 128); rc = ldg_rlx64(pg + o8);
        if (++n > SPIN_LIMIT) __trap();
    }
    __syncwarp();
    if (lane == 0) mbar_arrive(sb + O_BAR + 8 * B_MEM);
    fence_async_smem();
    __syncwarp();
    if (lane == 0) mbar_arrive(sb + O_BAR + 8 * B_QKW);
    return n;
}

__global__ void __cluster_dims__(2, 1, 1) __launch_bounds__(512, 1)
rmt_main(const __grid_constant__ CUtensorMap tm_x, const __grid_constant__ CUtensorMap tm_wq, const __grid_constant__ CUtensorMap tm_wk,
         const __grid_constant__ CUtensorMap tm_wv, const __grid_constant__ CUtensorMap tm_wo, const bf16* __restrict__ mem0, const Tune tn,
         const __grid_constant__ FftMaps fm) {
    extern __shared__ __align__(1024) unsigned char smem_raw[];
    const uint32_t sb = smem_u32(smem_raw);
    if ((sb & 0x3FFFF) != SM_BASE) __trap();
    const int cid = blockIdx.x >> 1, kh = blockIdx.x & 1;
    const int tpc = cid < 4 ? 62 + cid : cid - 4;
    int h, nh;
    if (tpc < 32) { h = (tpc >> 4) * 8 + (tpc & 7); nh = (tpc >> 3) & 1; }
    else if (tpc < 60) { int u = tpc - 32, r = u % 14; h = 16 + (u / 14) * 7 + r % 7; nh = r / 7; }
    else if (tpc < 62) { GT(0); fft_all((tpc - 60) * 2 + kh, fm, sb); GT(3); return; }
    else { h = 30 + ((tpc - 62) >> 1); nh = tpc & 1; }
    const int j = nh * 2 + kh, role = h * 4 + j;
    const int wgi = __shfl_sync(~0u, threadIdx.x >> 7, 0);
    const int w = __shfl_sync(~0u, (threadIdx.x >> 5) & 3, 0);
    const int tid = threadIdx.x & 127, lane = tid & 31;
#define OPAQUE_IDS() int tid_ = tid; asm volatile("" : "+r"(tid_)); const int tid = tid_, lane = tid_ & 31; (void)lane
    unsigned char* const redp = (unsigned char*)(((uintptr_t)g_red + 32767) & ~(uintptr_t)32767);
    const uint32_t bars = sb + O_BAR;

    if (threadIdx.x == 0) {
        const uint8_t cnts[B_COUNT] = {1, 1, 1, 1, 1, 1, 4, 4, 1, 12, 8, 1, 1, 1, 1, 1, 1, 1, 1, 1, 16, 4, 4, 4};
#pragma unroll
        for (int i = 0; i < B_COUNT; i++) mbar_init(bars + 8 * i, cnts[i]);
        asm volatile("fence.mbarrier_init.release.cluster;" ::: "memory");
        fence_async_smem();
        const int c0 = h * 128 + nh * 64, r0 = kh * 512;
        for (int i = 0; i < 2; i++) {
            mbar_expect_tx(bars + 8 * (B_WK0 + i), 32768);
            tma2d(sb + O_XB + i * 32768, &tm_wk, c0, r0 + i * 256, bars + 8 * (B_WK0 + i));
            mbar_expect_tx(bars + 8 * (B_WQ0 + i), 32768);
            tma2d(sb + O_WO + i * 32768, &tm_wq, c0, r0 + i * 256, bars + 8 * (B_WQ0 + i));
        }
        mbar_expect_tx(bars + 8 * B_WV, 65536);
        for (int i = 0; i < 2; i++) tma2d(sb + O_WV + i * 32768, &tm_wv, c0, r0 + i * 256, bars + 8 * B_WV);
        for (int i = 0; i < 4; i++) tma2d_prefetch(&tm_wo, j * 256 + i * 64, h * 128);
        tma4d_prefetch(&tm_x, kh * 8, (role >> 1) * 4);
    }
    __syncthreads();
    uint32_t mate;
    asm volatile("mapa.shared::cluster.u32 %0, %1, %2;" : "=r"(mate) : "r"(sb), "r"(kh ^ 1));

    if (wgi < 2) {
        asm volatile("setmaxnreg.inc.sync.aligned.u32 176;");
        uint32_t a[32][4];
        {
            const uint32_t stage = sb + (wgi == 0 ? O_WO : O_XB);
            const uint32_t ad = stage + (((lane >> 4) & 1) * 8 + (lane & 7)) * 128 + (((2 * w + ((lane >> 3) & 1)) ^ (lane & 7)) << 4);
#pragma unroll
            for (int i = 0; i < 2; i++) {
                mbar_wait(bars + 8 * (B_WQ0 + 2 * wgi + i), 0);
#pragma unroll
                for (int ks = 0; ks < 16; ks++) ldsm4t(a[i * 16 + ks], ad + (i * 16 + ks) * 2048);
            }
            __syncwarp();
            if (lane == 0) mbar_arrive(bars + 8 * (B_QDONE + wgi));
        }
        asm volatile("barrier.cluster.arrive.release.aligned;" ::: "memory");
        asm volatile("barrier.cluster.wait.acquire.aligned;" ::: "memory");
        uint32_t kp[4], sf = 0;
#define X_PASS(d)                                                                                          \
        wg_fence();                                                                                        \
        _Pragma("unroll") for (int ks = 0; ks < 32; ks++) { if (ks == 0) wg_rs32<0>(d, a[ks], xdesc(ks)); else wg_rs32<1>(d, a[ks], xdesc(ks)); } \
        wg_commit();                                                                                       \
        wg_wait<0>();
#define QK_LOOP(R)                                                                                         \
        _Pragma("unroll 1") for (int sg = 0; sg < RA; sg++) {                                              \
            float d[16]; uint32_t sn[4];                                                                   \
            if (sg > 0) { x_wait(R, sg - 1, sb); x_finish<R>(kp, sg - 1, h, nh * 4 + w, kh, tid, sb); }    \
            mbar_wait(bars + 8 * B_XFULL, sg & 1);                                                         \
            X_PASS(d);                                                                                     \
            x_split(d, sn, kp, kh);                                                                        \
            x_send(R, sn, sg, tid, sb, mate);                                                              \
            if (lane == 0) mbar_arrive(bars + 8 * B_XEMPTY);                                               \
        }                                                                                                  \
        _Pragma("unroll 1") for (int s = 0; s < 64; s++) {                                                 \
            TSI(s);                                                                                        \
            {                                                                                              \
                float d[16]; uint32_t sn[4], kc[4];                                                        \
                x_wait(R, s + RA - 1, sb);                                                                 \
                mbar_wait(bars + 8 * B_XFULL, (s + RA) & 1);                                               \
                mbar_wait(bars + 8 * B_OPDONE, s & 1);                                                     \
                if (R == 1) { x_finish<R>(kp, s + RA - 1, h, nh * 4 + w, kh, tid, sb); TS(5); }            \
                TS(6);                                                                                     \
                X_PASS(d);                                                                                 \
                TS(7);                                                                                     \
                x_split(d, sn, kc, kh);                                                                    \
                x_send(R, sn, s + RA, tid, sb, mate);                                                      \
                if (lane == 0) mbar_arrive(bars + 8 * B_XEMPTY);                                           \
                TS(4);                                                                                     \
                if (R == 0) { x_finish<R>(kp, s + RA - 1, h, nh * 4 + w, kh, tid, sb); TS(5); }            \
                _Pragma("unroll") for (int i = 0; i < 4; i++) kp[i] = kc[i];                               \
            }                                                                                              \
            uint2* ap = &g_alpha[((s & 1) * 32 + h) * (3 * 512) + R * 512 + ((nh * 4 + w) * 2 + kh) * 32 + lane]; \
            uint32_t mb0 = sb + O_MEM + (lane & 7) * 128 + (((lane >> 3) ^ (lane & 7)) << 4), mb1 = mb0 ^ 64; \
            asm volatile("mov.b32 %0, %0;\nmov.b32 %1, %1;" : "+r"(mb0), "+r"(mb1), "+l"(ap));            \
            float e[2][4];                                                                                 \
            _Pragma("unroll") for (int i = 0; i < 4; i++) e[0][i] = e[1][i] = 0.f;                         \
            mbar_wait(bars + 8 * B_MEM, s & 1);                                                            \
            TS(0);                                                                                         \
            _Pragma("unroll") for (int ks = 0; ks < 32; ks += 2) {                                         \
                uint32_t b[4];                                                                             \
                ldsm4(b, ((ks & 2) ? mb1 : mb0) + (ks >> 2) * 1024);                                       \
                mma16816(e[0], a[ks][0], a[ks][1], a[ks][2], a[ks][3], b[0], b[1]);                        \
                mma16816(e[1], a[ks + 1][0], a[ks + 1][1], a[ks + 1][2], a[ks + 1][3], b[2], b[3]);        \
            }                                                                                              \
            TS(2);                                                                                         \
            if (lane < 8) asm volatile("st.relaxed.gpu.global.u32 [%0], %1;" ::"l"((uint32_t*)g_qst + role * 8 + lane), "r"(gtime()) : "memory"); \
            uint32_t u0 = pack_bf16(e[0][0] + e[1][0], e[0][1] + e[1][1]), u1 = pack_bf16(e[0][2] + e[1][2], e[0][3] + e[1][3]); \
            u0 = movm(u0); u1 = movm(u1);                                                                  \
            if (QKW_EARLY) { SCHED_FENCE(); if (lane == 0) mbar_arrive(bars + 8 * B_QKW); }                \
            stg_rlx64(ap, (u0 & ~1u) | (((s >> 1) & 1) ^ 1), u1);                                          \
            if (!QKW_EARLY && lane == 0) mbar_arrive(bars + 8 * B_QKW);                                    \
            TS(3);                                                                                         \
        }                                                                                                  \
        x_wait(R, 63 + RA, sb);
        if (wgi == 0) { QK_LOOP(0); } else { QK_LOOP(1); }
        if (QKW_EARLY) sts32(bars + 252, sf);
        TSDUMP();
    } else if (wgi == 2) {
        asm volatile("setmaxnreg.dec.sync.aligned.u32 64;");
        asm volatile("barrier.cluster.arrive.release.aligned;" ::: "memory");
        if (w == 0) {
            mbar_wait(bars + 8 * B_KDONE, 0);
            if (lane == 0) {
                mbar_expect_tx(bars + 8 * B_XFULL, 32768);
                tma4d(sb + O_XB, &tm_x, kh * 8, 0, bars + 8 * B_XFULL);
            }
            mbar_wait(bars + 8 * B_QDONE, 0);
            if (lane == 0) {
                mbar_expect_tx(bars + 8 * B_WO, 65536);
#pragma unroll
                for (int i = 0; i < 4; i++) tma2d(sb + O_WO + i * 16384, &tm_wo, j * 256 + i * 64, h * 128, bars + 8 * B_WO);
            }
        }
        asm volatile("barrier.cluster.wait.acquire.aligned;" ::: "memory");
        mbar_wait(bars + 8 * B_WV, 0);
        sts128u(sb + O_VM + tid * 16, make_uint4(0, 0, 0, 0));
        uint32_t tref = gtime() - 4000;
#define V_PASS(d)                                                                                          \
        wg_fence();                                                                                        \
        _Pragma("unroll") for (int ks = 0; ks < 32; ks++) {                                                \
            constexpr uint64_t da0 = mkdesc(SM_BASE + O_WV, 16, 1024, 1);                                  \
            if (ks == 0) wg_ss40<0>(d, da0 + ks * 128, xdesc(ks)); else wg_ss40<1>(d, da0 + ks * 128, xdesc(ks)); \
        }                                                                                                  \
        wg_commit();                                                                                       \
        wg_wait<0>();
#define X_REFILL(sg)                                                                                       \
        if (lane == 0) {                                                                                   \
            mbar_expect_tx(bars + 8 * B_XFULL, 32768);                                                     \
            tma4d(sb + O_XB, &tm_x, kh * 8, (sg) * 4, bars + 8 * B_XFULL);       \
        }
#pragma unroll 1
        for (int sg = 0; sg < RA; sg++) {
            float d[20]; uint32_t sn[4], kp[4];
            mbar_wait(bars + 8 * B_XFULL, sg & 1);
            V_PASS(d);
            if (lane == 0) mbar_arrive(bars + 8 * B_XEMPTY);
            if (w == 0) { mbar_wait(bars + 8 * B_XEMPTY, sg & 1); X_REFILL(sg + 1); }
            x_split(d, sn, kp, kh);
            x_send(2, sn, sg, tid, sb, mate);
            x_wait(2, sg, sb);
            x_finish<2>(kp, sg, h, nh * 4 + w, kh, tid, sb);
        }
#pragma unroll 1
        for (int s = 0; s < 64; s++) {
            TSI(s);
            OPAQUE_IDS();
            uint2* ap = &g_alpha[((s & 1) * 32 + h) * (3 * 512) + 1024 + ((nh * 4 + w) * 2 + kh) * 32 + lane];
            asm volatile("" : "+l"(ap));
            float d[20];
            mbar_wait(bars + 8 * B_QKW, s & 1);
            TS(0);
            V_PASS(d);
            TS(1);
            stg_rlx64(ap, (pack_bf16(d[16], d[17]) & ~1u) | (((s >> 1) & 1) ^ 1), pack_bf16(d[18], d[19]));
            const uint32_t tv = gtime();
            if (tid == 0) asm volatile("st.relaxed.gpu.global.u32 [%0], %1;" ::"l"((uint32_t*)g_stamp + role), "r"(tv) : "memory");
            if (lane == 0) mbar_arrive(bars + 8 * B_XEMPTY);
            uint32_t sn[4], kp[4];
            x_split(d, sn, kp, kh);
            {
                const uint2* vp = &g_alpha[((s & 1) * 32 + h) * (3 * 512) + 1024 + w * 128 + lane];
                const uint32_t tag = ((s >> 1) & 1) ^ 1;
                mbar_wait(bars + 8 * B_AFULL, s & 1);
                int dt;
                asm volatile("ld.shared.u32 %0, [%1];" : "=r"(dt) : "r"(sb + O_QST + lane * 4) : "memory");
                dt = min(__reduce_max_sync(~0u, dt - (int)tv), 0);
                asm volatile("" : "+l"(vp));
                wait_gtime(tv + dt + tn.d_v);
                uint32_t n = 0, bad;
                do {
                    uint2 va[4];
#pragma unroll
                    for (int i = 0; i < 4; i++) va[i] = ldg_rlx64(vp + i * 32);
                    if (++n > SPIN_LIMIT) __trap();
                    bad = (orx2(va[0].x, va[1].x, tag) | orx2(va[2].x, va[3].x, tag)) & 1;
                    sts128u(sb + O_VM + tid * 16, make_uint4((add_bf16x2(va[0].x, va[1].x) & ~1u) | ((~s ^ bad) & 1), add_bf16x2(va[0].y, va[1].y),
                                                             add_bf16x2(va[2].x, va[3].x), add_bf16x2(va[2].y, va[3].y)));
                } while (__any_sync(~0u, bad));
                TS(2);
                TSV(16 + w, n - 1);
            }
            if (s == 63) break;
            if (w == 0) {
                mbar_wait(bars + 8 * B_XEMPTY, (s + RA) & 1);
                X_REFILL(s + RA + 1);
                if (lane == 0 && nh == 0 && ((h ^ s) & 7) == 0 && s < 61 - RA) tma4d_prefetch(&tm_x, kh * 8, (s + RA + 3) * 4);
                mbar_wait(bars + 8 * B_SRDY, s & 1);
                if (lane == 0) {
                    const uint4* hb = &g_kvq[(((s + 1) & 3) * 32 + h) * (3 * 512)];
                    mbar_expect_tx(bars + 8 * B_KVFULL, 18432);
                    bulk_g2s(sb + O_KVQ, hb + 512, 16384, bars + 8 * B_KVFULL);
                    bulk_g2s(sb + O_KVQ + 16384, hb + j * 128, 2048, bars + 8 * B_KVFULL);
                }
            }
            if (w == 3) {
                wait_clk(clk(), tn.d_st);
                uint32_t n = 0, mx, mn;
                do {
                    const uint4 st = ldg_rlx128(&g_stamp[lane]);
                    mx = __reduce_max_sync(~0u, max(max(st.x - tref, st.y - tref), max(st.z - tref, st.w - tref)));
                    mn = __reduce_min_sync(~0u, min(min(st.x - tref, st.y - tref), min(st.z - tref, st.w - tref)));
                } while (mx >= 200000u && ++n < 64);
                tref = mx < 200000u ? tref + mx + (mx - mn > tn.spread ? tn.extra : 1) : gtime();
                TSV(12, clk()); TSV(13, n); TSV(14, mx - mn);
            }
            mbar_wait(bars + 8 * B_OPDONE, (s + 1) & 1);
            x_send(2, sn, s + RA, tid, sb, mate);
            if (w == 3) {
                wait_gtime(tref + tn.d_r0);
                if (lane == 0) {
                    mbar_expect_tx(bars + 8 * B_RFULL, 16384);
                    bulk_g2s(sb + O_STG, redp + (s & 3) * 32768 + kh * 16384, 16384, bars + 8 * B_RFULL);
                }
                TSV(3, clk());
            }
            x_wait(2, s + RA, sb);
            x_finish<2>(kp, s + RA, h, nh * 4 + w, kh, tid, sb);
            TS(6);
            if (DBG_TIMING) { mbar_wait(bars + 8 * B_RFULL, s & 1); TS(4); }
            const uint32_t n = convert_mem(redp, s, kh, 0, w, lane, sb); (void)n;
            TS(5);
            TSV(8 + w, n);
        }
        TSDUMP();
    } else {
        asm volatile("setmaxnreg.dec.sync.aligned.u32 96;");
        GT(0);
        asm volatile("barrier.cluster.arrive.release.aligned;" ::: "memory");
#define RED_CLEAR(st)                                                                                           \
        if (lane < 16) {                                                                                        \
            const uint32_t cb = ((st) & 4) ? 0x42800000u : 0u;                                                  \
            stg128(redp + ((st) & 3) * 32768 + role * 256 + lane * 16, 0, (role & 2) ? cb : 0u, 0, cb);        \
        }
#define KQ_BAD(tg) __any_sync(~0u, or3(orx2(kf[0].x, kf[1].x, tg), orx2(kf[2].x, kf[3].x, tg), orx2(qf[0].x, qf[1].x, tg)) & 1)
#define KQ_POLL(st)                                                                                             \
        {                                                                                                       \
            const uint4* hb = &g_kvq[(((st) & 3) * 32 + h) * (3 * 512)];                                        \
            uint32_t n_ = 0;                                                                                    \
            do {                                                                                                \
                _Pragma("unroll") for (int i = 0; i < 4; i++) kf[i] = ldg_rlx128(hb + 512 + w * 128 + i * 32 + lane); \
                _Pragma("unroll") for (int u = 0; u < 2; u++) qf[u] = ldg_rlx64((const uint2*)hb + j * 256 + (2 * w + u) * 32 + lane); \
                if (++n_ > SPIN_LIMIT) __trap();                                                                \
            } while (KQ_BAD((((st) >> 2) & 1) ^ 1));                                                \
        }
        uint32_t start_target = 0;
        if (w == 0) {
            RED_CLEAR(0); RED_CLEAR(1); RED_CLEAR(2);
            fence_gpu();
            __syncwarp();
            if (lane == 0) start_target = (atomicAdd(&g_start, 1) & ~127u) + 128;
            start_target = __shfl_sync(~0u, start_target, 0);
        }
        mbar_wait(bars + 8 * B_KDONE, 0);
        {
            const int kb0 = (w & 1) * 4 + (w >> 1) * 2;
#pragma unroll
            for (int q = 0; q < 4; q++) {
                const int row = (lane >> 3) + (q & 1) * 4, ch = lane & 7, kb = kb0 + (q >> 1);
                const uint4 v = *(const uint4*)(mem0 + row * 1024 + kh * 512 + kb * 64 + ch * 8);
                sts128u(sb + O_MEM + kb * 1024 + row * 128 + ((ch ^ row) << 4), v);
            }
            fence_async_smem();
            __syncwarp();
            if (lane < 2) { mbar_arrive(bars + 8 * B_MEM); mbar_arrive(bars + 8 * B_QKW); }
            if (lane == 0) mbar_arrive(bars + 8 * B_OPDONE);
        }
        asm volatile("barrier.cluster.wait.acquire.aligned;" ::: "memory");
        if (w == 0) { uint32_t n = 0; while (__any_sync(~0u, (int)(ld_acquire(&g_start) - start_target) < 0)) { if (++n > SPIN_LIMIT) __trap(); } }
        mbar_wait(bars + 8 * B_WO, 0);
        GT(1);
        uint32_t sf = 0;
        uint4 kf[4]; uint2 qf[2];
        KQ_POLL(0);
#pragma unroll
        for (int i = 0; i < 4; i++) sts128u(sb + O_KVQ + 8192 + w * 2048 + i * 512 + lane * 16, make_uint4(0, 0, 0, 0));
#pragma unroll 1
        for (int s = 0; s < 64; s++) {
            TSI(s);
            OPAQUE_IDS();
            const uint32_t tg = ((s >> 2) & 1) ^ 1;
            const uint32_t tag = ((s >> 1) & 1) ^ 1;
            const uint2* ap = &g_alpha[((s & 1) * 32 + h) * (3 * 512) + w * 128 + lane];
            uint32_t sw = sb + O_S + w * 2560 + lane * 16, sr = sb + O_S + tid * 4;
            uint32_t pw = sb + O_P + ((lane >> 1) & 1) * 704 + (2 * w + (lane >> 4)) * 16 + ((lane >> 2) & 3) * 4 + (lane & 1) * 2;
            int lim = (lane & 2) ? 8 * j + 2 * w + (lane >> 4) - 2 * ((lane >> 2) & 3) - (lane & 1) : 64;
            uint32_t pr = sb + O_P + lane * 16, oa = sb + O_O + w * 512 + lane * 4;
            uint32_t aa = sb + O_STG + w * 1024 + lane * 8, vv = sb + O_KVQ + 8192 + w * 2048 + lane * 16;
            unsigned char* pa = redp + (s & 3) * 32768 + red_grp(j * 16 + (tid >> 3));
            unsigned char* pb = pa + 512 + ((lane >> 3) & 1) * 64 + (lane & 7) * 8;
            pa += (lane & 7) * 16;
            asm volatile("" : "+r"(sw), "+r"(sr), "+r"(pw), "+r"(lim), "+r"(pr), "+r"(oa), "+r"(aa), "+r"(vv), "+l"(ap), "+l"(pa), "+l"(pb));
            TS(0);
            mbar_wait(bars + 8 * B_QKW, s & 1);
            TS(1);
            if (w == 0) {
                wait_clk(clk(), tn.d_alpha);
                if (lane == 0) {
                    mbar_expect_tx(bars + 8 * B_AFULL, 8192 + 128);
                    bulk_g2s(sb + O_STG, ap, 8192, bars + 8 * B_AFULL);
                    bulk_g2s(sb + O_QST, &g_qst[h * 8], 128, bars + 8 * B_AFULL);
                }
            }
            mbar_wait(bars + 8 * B_AFULL, s & 1);
            TS(12);
            uint4 vf[4];
            {
                uint2 qa[4], ka[4];
#pragma unroll
                for (int i = 0; i < 4; i++) { qa[i] = lds64u(aa + i * 256); ka[i] = lds64u(aa + 4096 + i * 256); }
#define QK_BAD() __any_sync(~0u, or3(orx2(qa[0].x, ka[0].x, tag), orx2(qa[1].x, ka[1].x, tag), orx(orx(orx2(qa[2].x, ka[2].x, tag), qa[3].x, tag), ka[3].x, tag)) & 1)
#define SCORES()                                                                                                                  \
                {                                                                                                                 \
                    float sa[5][4];                                                                                               \
                    _Pragma("unroll") for (int n = 0; n < 5; n++) sa[n][0] = sa[n][1] = sa[n][2] = sa[n][3] = 0.f;                \
                    _Pragma("unroll") for (int u = 0; u < 2; u++) {                                                               \
                        const uint32_t q0 = add_bf16x2(qa[2 * u].x, qa[2 * u + 1].x), q1 = add_bf16x2(qa[2 * u].y, qa[2 * u + 1].y); \
                        const uint32_t k0 = add_bf16x2(ka[2 * u].x, ka[2 * u + 1].x), k1 = add_bf16x2(ka[2 * u].y, ka[2 * u + 1].y); \
                        mma16816(sa[1], q0, qf[u].x, q1, qf[u].y, kf[2 * u].x, kf[2 * u].y);                                      \
                        mma16816(sa[2], q0, qf[u].x, q1, qf[u].y, kf[2 * u].z, kf[2 * u].w);                                      \
                        mma16816(sa[3], q0, qf[u].x, q1, qf[u].y, kf[2 * u + 1].x, kf[2 * u + 1].y);                              \
                        mma16816(sa[4], q0, qf[u].x, q1, qf[u].y, kf[2 * u + 1].z, kf[2 * u + 1].w);                              \
                        mma16816(sa[0], q0, qf[u].x, q1, qf[u].y, k0, k1);                                                        \
                        if (u == 0) SCHED_FENCE();                                                                                \
                    }                                                                                                             \
                    _Pragma("unroll") for (int n = 1; n <= 5; n++) sts128(sw + (n % 5) * 512, sa[n % 5][0], sa[n % 5][1], sa[n % 5][2], sa[n % 5][3]); \
                }
                SCORES();
                uint32_t nr = 0;
                if (__builtin_expect(QK_BAD(), 0)) {
                    do {
#pragma unroll
                        for (int i = 0; i < 4; i++) { qa[i] = ldg_rlx64(ap + i * 32); ka[i] = ldg_rlx64(ap + 512 + i * 32); }
                        if (++nr > SPIN_LIMIT) __trap();
                    } while (QK_BAD());
                    SCORES();
                }
                if (w == 0) TSV(20, nr);
            }
            TS(2);
            bar_sync(1, 128);
            float sc[5];
            {
                float x[4][5];
#pragma unroll
                for (int q = 0; q < 4; q++)
#pragma unroll
                    for (int n = 0; n < 5; n++) asm volatile("ld.shared.f32 %0, [%1];" : "=f"(x[q][n]) : "r"(sr + q * 2560 + n * 512) : "memory");
#pragma unroll
                for (int n = 0; n < 5; n++) sc[n] = (x[0][n] + x[1][n]) + (x[2][n] + x[3][n]);
            }
            TS(15);
#pragma unroll
            for (int n = 1; n < 5; n++) if (8 * (n - 1) > lim) sc[n] = MASK_VAL;
            float m = fmaxf(fmaxf(fmaxf(sc[0], sc[1]), fmaxf(sc[2], sc[3])), sc[4]);
            m = fmaxf(m, __shfl_xor_sync(~0u, m, 1));
            m = fmaxf(m, __shfl_xor_sync(~0u, m, 4));
            m = fmaxf(m, __shfl_xor_sync(~0u, m, 8));
            m *= -SM_SCALE_LOG2;
            SCHED_FENCE();
#pragma unroll
            for (int i = 0; i < 4; i++) vf[i] = lds128u(vv + i * 512);
#pragma unroll
            for (int n = 0; n < 5; n++) {
                const uint32_t pv = pack_bf16(ex2(fmaf(sc[n], SM_SCALE_LOG2, m)), 0.f);
                asm volatile("st.shared.u16 [%0], %1;" ::"r"(pw + n * 128), "h"((uint16_t)pv) : "memory");
            }
            bar_sync(1, 128);
            TS(3);
            uint32_t pf[4], p0, px[4], px0;
            ldsm4(pf, pr + 128);
            asm volatile("ld.shared.u32 %0, [%1];" : "=r"(p0) : "r"(oa - w * 512 + (O_P - O_O)) : "memory");
            ldsm4(px, pr + 128 + 704);
            asm volatile("ld.shared.u32 %0, [%1];" : "=r"(px0) : "r"(oa - w * 512 + (O_P - O_O) + 704) : "memory");
            if (lane == 0) mbar_arrive(bars + 8 * B_SRDY);
            uint4 vm = lds128u(sb + O_VM + tid * 16);
            if (__builtin_expect(__any_sync(~0u, orx(orx(orx2(vf[0].x, vf[1].x, tg), vf[2].x, tg), vf[3].x, tg) & 1), 0)) {
                const uint4* vp = &g_kvq[((s & 3) * 32 + h) * (3 * 512) + 1024 + w * 128 + lane];
                uint32_t nr = 0;
                do {
#pragma unroll
                    for (int i = 0; i < 4; i++) vf[i] = ldg_rlx128(vp + i * 32);
                    if (++nr > SPIN_LIMIT) __trap();
                } while (__any_sync(~0u, orx(orx(orx2(vf[0].x, vf[1].x, tg), vf[2].x, tg), vf[3].x, tg) & 1));
            }
            float o[2][4], ox[2][4], sm[4], sx[4];
#pragma unroll
            for (int i = 0; i < 4; i++) o[0][i] = o[1][i] = ox[0][i] = ox[1][i] = sm[i] = sx[i] = 0.f;
            constexpr uint32_t ONE2 = 0x3f803f80u;
#pragma unroll
            for (int c = 0; c < 2; c++) {
#pragma unroll
                for (int u = 0; u < 2; u++) mma16816(o[u], vf[2 * u + c].x, vf[2 * u + c].y, vf[2 * u + c].z, vf[2 * u + c].w, pf[2 * c], pf[2 * c + 1]);
#pragma unroll
                for (int u = 0; u < 2; u++) mma16816(ox[u], vf[2 * u + c].x, vf[2 * u + c].y, vf[2 * u + c].z, vf[2 * u + c].w, px[2 * c], px[2 * c + 1]);
            }
            {
                uint32_t nr = 0;
                while (__any_sync(~0u, (vm.x ^ ~s) & 1)) { vm = lds128u(sb + O_VM + tid * 16); if (++nr > SPIN_LIMIT) __trap(); }
                if (w == 0) TSV(21, nr);
            }
            mma1688(o[0], vm.x, vm.y, p0);
            mma1688(o[1], vm.z, vm.w, p0);
            mma1688(sm, ONE2, ONE2, p0);
            mma1688(sx, ONE2, ONE2, px0);
            SCHED_FENCE();
            sts32(oa, pack_bf16(o[0][0], o[0][1]));
            sts32(oa + 128, pack_bf16(o[0][2], o[0][3]));
            sts32(oa + 256, pack_bf16(o[1][0], o[1][1]));
            sts32(oa + 384, pack_bf16(o[1][2], o[1][3]));
            mma1688(ox[0], vm.x, vm.y, px0);
            mma1688(ox[1], vm.z, vm.w, px0);
#pragma unroll
            for (int c = 0; c < 2; c++) {
                mma16816(sm, ONE2, ONE2, ONE2, ONE2, pf[2 * c], pf[2 * c + 1]);
                mma16816(sx, ONE2, ONE2, ONE2, ONE2, px[2 * c], px[2 * c + 1]);
            }
            SCHED_FENCE();
            TS(4);
            fence_async_smem();
            bar_sync(1, 128);
            if (s == 0) GT(2);
            TS(5);
            {
            float cc[4][4];
            wg_fence();
#pragma unroll
            for (int ks = 0; ks < 8; ks++)
#pragma unroll
                for (int t = 0; t < 4; t++) {
                    constexpr uint64_t da0 = mkdesc(SM_BASE + O_WO, 16, 1024, 1), db0 = mkdesc(SM_BASE + O_O, 128, 128, 0);
                    if (ks == 0) wg_ss8<0>(cc[t], da0 + t * 1024, db0); else wg_ss8<1>(cc[t], da0 + t * 1024 + ks * 128, db0 + ks * 16);
                }
            wg_commit();
            const float i0 = rcp(sm[0]), i1 = rcp(sm[1]);
            wg_wait<0>();
            TS(6);
#pragma unroll
            for (int hf = 0; hf < 2; hf++)
                asm volatile("red.relaxed.gpu.global.add.noftz.v4.bf16x2 [%0], {%1,%2,%3,%4};" ::"l"(pa + hf * 128),
                             "r"(pack_bf16(cc[2 * hf][0] * i0, cc[2 * hf][1] * i1)), "r"(pack_bf16(cc[2 * hf][2] * i0, cc[2 * hf][3] * i1)),
                             "r"(pack_bf16(cc[2 * hf + 1][0] * i0, cc[2 * hf + 1][1] * i1)), "r"(pack_bf16(cc[2 * hf + 1][2] * i0, 1.f)) : "memory");
            asm volatile("red.relaxed.gpu.global.add.noftz.v2.bf16x2 [%0], {%1,%2};" ::"l"(pb), "r"(pack_bf16(cc[1][3] * i1, cc[3][3] * i1)), "r"(0x3f800000u) : "memory");
            SCHED_FENCE();
            TS(7);
            if (lane == 0) mbar_arrive(bars + 8 * B_OPDONE);
            }
            if (!FLAG(3)) {
                const float ix0 = rcp(sx[0]), ix1 = rcp(sx[1]);
                const uint32_t xo = sb + O_XO + w * 512;
                stsm4t(xo + (lane & 7) * 64 + (((lane >> 3) ^ ((lane >> 1) & 3)) << 4), pack_bf16(ox[0][0] * ix0, ox[0][1] * ix1),
                       pack_bf16(ox[0][2] * ix0, ox[0][3] * ix1), pack_bf16(ox[1][0] * ix0, ox[1][1] * ix1), pack_bf16(ox[1][2] * ix0, ox[1][3] * ix1));
                __syncwarp();
                const uint4 ov = lds128u(xo + (lane >> 2) * 64 + (((lane & 3) ^ ((lane >> 3) & 3)) << 4));
                stg128(&g_ox[(size_t)(s * 32 + j * 8 + (lane >> 2)) * 4096 + h * 128 + w * 32 + (lane & 3) * 8], ov.x, ov.y, ov.z, ov.w);
            }
            TS(8);
            if (s == 63) { GT(3); break; }
            mbar_wait(bars + 8 * B_KVFULL, s & 1);
#pragma unroll
            for (int i = 0; i < 4; i++) kf[i] = lds128u(vv - 8192 + i * 512);
#pragma unroll
            for (int u = 0; u < 2; u++) qf[u] = lds64u(sb + O_KVQ + 16384 + (2 * w + u) * 256 + lane * 8);
            if (__builtin_expect(KQ_BAD((((s + 1) >> 2) & 1) ^ 1), 0)) { KQ_POLL(s + 1); if (w == 0) TSV(22, 1); }
            TS(9);
            {
                const uint32_t n = convert_mem(redp, s, kh, 1, w, lane, sb); (void)n;
                TS(11);
                TSV(16 + w, n);
            }
            if (w == 0 && s < 61) RED_CLEAR(s + 3);
        }
        sts32(bars + 252, sf);
        TSDUMP();
    }
}

constexpr int G_ST = 6;
constexpr uint32_t G_SMEM = G_ST * 32768 + 256;
#define F16(d, o) F4(d, o), F4(d, o + 4), F4(d, o + 8), F4(d, o + 12)
__device__ __forceinline__ void wg_ss128(float (&d)[64], uint64_t da, uint64_t db, int sc) {
    asm volatile("{\n.reg .pred p;\nsetp.ne.b32 p, %66, 0;\nwgmma.mma_async.sync.aligned.m64n128k16.f32.bf16.bf16 "
                 "{%0,%1,%2,%3,%4,%5,%6,%7,%8,%9,%10,%11,%12,%13,%14,%15,%16,%17,%18,%19,%20,%21,%22,%23,%24,%25,%26,%27,%28,%29,%30,%31,"
                 "%32,%33,%34,%35,%36,%37,%38,%39,%40,%41,%42,%43,%44,%45,%46,%47,%48,%49,%50,%51,%52,%53,%54,%55,%56,%57,%58,%59,%60,%61,%62,%63}, "
                 "%64, %65, p, 1, 1, 0, 1;\n}"
                 : F16(d, 0), F16(d, 16), F16(d, 32), F16(d, 48) : "l"(da), "l"(db), "r"(sc));
}

__global__ void __launch_bounds__(384, 1)
out_gemm(const __grid_constant__ CUtensorMap tm_o, const __grid_constant__ CUtensorMap tm_w, bf16* __restrict__ out) {
    extern __shared__ __align__(1024) unsigned char smem_raw[];
    const uint32_t sb = smem_u32(smem_raw), bars = sb + G_ST * 32768;
    const int m0 = (blockIdx.x >> 3) * 128, n0 = (blockIdx.x & 7) * 128;
    const int wgi = __shfl_sync(~0u, threadIdx.x >> 7, 0), tid = threadIdx.x & 127;
    if (threadIdx.x == 0) {
        for (int i = 0; i < G_ST; i++) { mbar_init(bars + 8 * i, 1); mbar_init(bars + 8 * (G_ST + i), 8); }
        fence_async_smem();
    }
    __syncthreads();
    if (wgi == 0) GT(4);
    if (wgi == 2) {
        if (tid == 0) {
            for (int kt = 0; kt < 64; kt++) {
                const int st = kt % G_ST;
                if (kt >= G_ST) mbar_wait(bars + 8 * (G_ST + st), (kt / G_ST - 1) & 1);
                mbar_expect_tx(bars + 8 * st, 32768);
                tma2d(sb + st * 32768, &tm_o, kt * 64, m0, bars + 8 * st);
                tma2d(sb + st * 32768 + 16384, &tm_w, n0, kt * 64, bars + 8 * st);
                tma2d(sb + st * 32768 + 24576, &tm_w, n0 + 64, kt * 64, bars + 8 * st);
            }
        }
    } else {
        float d[64];
        int st = 0, ph = 0;
#pragma unroll 1
        for (int kt = 0; kt < 64; kt++) {
            mbar_wait(bars + 8 * st, ph);
            const uint64_t da = mkdesc(sb + st * 32768 + wgi * 8192, 16, 1024, 1), db = mkdesc(sb + st * 32768 + 16384, 8192, 1024, 1);
            wg_fence();
#pragma unroll
            for (int k = 0; k < 4; k++) wg_ss128(d, da + k * 2, db + k * 128, kt | k);
            wg_commit();
            if (kt > 0) {
                wg_wait<1>();
                if ((tid & 31) == 0) mbar_arrive(bars + 8 * (G_ST + (st == 0 ? G_ST - 1 : st - 1)));
            }
            if (++st == G_ST) { st = 0; ph ^= 1; }
        }
        wg_wait<0>();
        const int row = m0 + wgi * 64 + (tid >> 5) * 16 + ((tid & 31) >> 2);
        bf16* op = out + (size_t)row * 2048 + 1024 + n0 + (tid & 3) * 2;
#pragma unroll
        for (int i = 0; i < 16; i++) {
            *(uint32_t*)(op + i * 8) = pack_bf16(d[4 * i], d[4 * i + 1]);
            *(uint32_t*)(op + 8 * 2048 + i * 8) = pack_bf16(d[4 * i + 2], d[4 * i + 3]);
        }
        if (wgi == 0) GT(5);
    }
}

typedef CUresult (*EncodeFn)(CUtensorMap*, CUtensorMapDataType, cuuint32_t, void*, const cuuint64_t*, const cuuint64_t*,
                             const cuuint32_t*, const cuuint32_t*, CUtensorMapInterleave, CUtensorMapSwizzle,
                             CUtensorMapL2promotion, CUtensorMapFloatOOBfill);

static void make_map(EncodeFn fn, CUtensorMap* m, const void* p, uint64_t cols, uint64_t rows, uint32_t bc, uint32_t br) {
    cuuint64_t dims[2] = {cols, rows}, strides[1] = {cols * 2};
    cuuint32_t box[2] = {bc, br}, es[2] = {1, 1};
    fn(m, CU_TENSOR_MAP_DATA_TYPE_BFLOAT16, 2, (void*)p, dims, strides, box, es, CU_TENSOR_MAP_INTERLEAVE_NONE,
       CU_TENSOR_MAP_SWIZZLE_128B, CU_TENSOR_MAP_L2_PROMOTION_L2_128B, CU_TENSOR_MAP_FLOAT_OOB_FILL_NONE);
}

static Tune h_tune = {300, 1120, 1, 0, 0, 672, 4000, 300};

extern "C" void kernel_launch(void* const* d_in, const int* in_sizes, int n_in, void* d_out, int out_size) {
    static bool init = false;
    static FftMaps fm;
    static CUtensorMap tm_x, tm_wq, tm_wk, tm_wv, tm_wo, tm_o, tm_wo2;
    if (!init) {
        void* fp = nullptr; cudaDriverEntryPointQueryResult qr;
        cudaGetDriverEntryPoint("cuTensorMapEncodeTiled", &fp, cudaEnableDefault, &qr);
        EncodeFn fn = (EncodeFn)fp;
        void* ox = nullptr; cudaGetSymbolAddress(&ox, g_ox);
        {
            cuuint64_t dims[4] = {64, 8, 16, 256}, strides[3] = {2048, 128, 16384};
            cuuint32_t box[4] = {64, 8, 8, 4}, es[4] = {1, 1, 1, 1};
            fn(&tm_x, CU_TENSOR_MAP_DATA_TYPE_BFLOAT16, 4, d_in[3], dims, strides, box, es, CU_TENSOR_MAP_INTERLEAVE_NONE,
               CU_TENSOR_MAP_SWIZZLE_128B, CU_TENSOR_MAP_L2_PROMOTION_L2_128B, CU_TENSOR_MAP_FLOAT_OOB_FILL_NONE);
        }
        void* fy = nullptr; cudaGetSymbolAddress(&fy, g_fy);
        for (int i = 0; i < 3; i++) {
            const cuuint64_t pitch = i == 2 ? 4096 : 2048;
            cuuint64_t dims[4] = {1024, 8, 16, 16}, strides[3] = {pitch, 128 * pitch, 8 * pitch};
            cuuint32_t box[4] = {64, 1, 16, 16}, es[4] = {1, 1, 1, 1};
            fn(i == 0 ? &fm.x : i == 1 ? &fm.y : &fm.o, CU_TENSOR_MAP_DATA_TYPE_BFLOAT16, 4, i == 0 ? d_in[0] : i == 1 ? fy : d_out, dims, strides, box, es,
               CU_TENSOR_MAP_INTERLEAVE_NONE, CU_TENSOR_MAP_SWIZZLE_128B, CU_TENSOR_MAP_L2_PROMOTION_L2_256B, CU_TENSOR_MAP_FLOAT_OOB_FILL_NONE);
        }
        {
            cuuint64_t dims[3] = {64, 2048, 16}, strides[2] = {2048, 128};
            cuuint32_t box[3] = {64, 8, 16}, es[3] = {1, 1, 1};
            fn(&fm.y2, CU_TENSOR_MAP_DATA_TYPE_BFLOAT16, 3, fy, dims, strides, box, es, CU_TENSOR_MAP_INTERLEAVE_NONE,
               CU_TENSOR_MAP_SWIZZLE_128B, CU_TENSOR_MAP_L2_PROMOTION_L2_128B, CU_TENSOR_MAP_FLOAT_OOB_FILL_NONE);
        }
        for (int i = 0; i < 2; i++) {
            cuuint64_t dims[3] = {256 * 513 - 448, 8, 8}, strides[2] = {128, 256 * 1026};
            cuuint32_t box[3] = {72, 8, 8}, es[3] = {1, 1, 1};
            fn(i ? &fm.wi : &fm.wr, CU_TENSOR_MAP_DATA_TYPE_BFLOAT16, 3, d_in[1 + i], dims, strides, box, es, CU_TENSOR_MAP_INTERLEAVE_NONE,
               CU_TENSOR_MAP_SWIZZLE_NONE, CU_TENSOR_MAP_L2_PROMOTION_L2_128B, CU_TENSOR_MAP_FLOAT_OOB_FILL_NONE);
        }
        make_map(fn, &tm_wq, d_in[5], 4096, 1024, 64, 256);
        make_map(fn, &tm_wk, d_in[6], 4096, 1024, 64, 256);
        make_map(fn, &tm_wv, d_in[7], 4096, 1024, 64, 256);
        make_map(fn, &tm_wo, d_in[8], 1024, 4096, 64, 128);
        make_map(fn, &tm_o, ox, 4096, 2048, 64, 128);
        make_map(fn, &tm_wo2, d_in[8], 1024, 4096, 64, 64);
        cudaFuncSetAttribute(rmt_main, cudaFuncAttributeMaxDynamicSharedMemorySize, MAIN_SMEM);
        cudaFuncSetAttribute(out_gemm, cudaFuncAttributeMaxDynamicSharedMemorySize, G_SMEM);
        init = true;
    }
    rmt_main<<<132, 512, MAIN_SMEM>>>(tm_x, tm_wq, tm_wk, tm_wv, tm_wo, (const bf16*)d_in[4], h_tune, fm);
    out_gemm<<<128, 384, G_SMEM>>>(tm_o, tm_wo2, (bf16*)d_out);
}
```

```cpp
#include <cuda_runtime.h>
#include <cuda_bf16.h>
#include <cuda.h>
#include <stdint.h>

typedef __nv_bfloat16 bf16;

#define DBG_TIMING 0

#define SPIN_LIMIT (1u << 22)

__device__ __forceinline__ uint32_t smem_u32(const void* p) { return (uint32_t)__cvta_generic_to_shared(p); }
__device__ __forceinline__ uint32_t clk() { uint32_t c; asm volatile("mov.u32 %0, %%clock;" : "=r"(c)::"memory"); return c; }
#define SCHED_FENCE() sf ^= (uint32_t)clock64()
__device__ __forceinline__ uint32_t gtime() { uint32_t c; asm volatile("mov.u32 %0, %%globaltimer_lo;" : "=r"(c)::"memory"); return c; }
__device__ __forceinline__ void wait_clk(uint32_t t0, uint32_t d) {
    asm volatile("{\n.reg .pred p;\n.reg .s32 t;\n.reg .b64 c;\nWL:\nmov.u64 c, %%clock64;\ncvt.u32.u64 t, c;\nsub.s32 t, t, %0;\nsetp.lt.s32 p, t, 0;\n@p bra.uni WL;\n}" ::"r"(t0 + d) : "memory");
}
__device__ __forceinline__ void wait_gtime(uint32_t t1) {
    asm volatile("{\n.reg .pred p;\n.reg .s32 t;\n.reg .b64 c;\nWL:\nmov.u64 c, %%globaltimer;\ncvt.u32.u64 t, c;\nsub.s32 t, t, %0;\nsetp.lt.s32 p, t, 0;\n@p bra.uni WL;\n}" ::"r"(t1) : "memory");
}

__device__ __forceinline__ void mbar_init(uint32_t bar, uint32_t cnt) {
    asm volatile("mbarrier.init.shared::cta.b64 [%0], %1;" ::"r"(bar), "r"(cnt) : "memory");
}
__device__ __forceinline__ void mbar_arrive(uint32_t bar) {
    asm volatile("mbarrier.arrive.shared::cta.b64 _, [%0];" ::"r"(bar) : "memory");
}
__device__ __forceinline__ void mbar_expect_tx(uint32_t bar, uint32_t bytes) {
    asm volatile("mbarrier.arrive.expect_tx.shared::cta.b64 _, [%0], %1;" ::"r"(bar), "r"(bytes) : "memory");
}
__device__ __forceinline__ void mbar_wait(uint32_t bar, uint32_t parity) {
    asm volatile(
        "{\n.reg .pred p, q;\n.reg .u32 n;\nmov.u32 n, 0;\n"
        "WL:\nmbarrier.try_wait.parity.shared::cta.b64 p, [%0], %1;\n"
        "add.u32 n, n, 1;\nsetp.gt.u32 q, n, %2;\n@q trap;\n@!p bra.uni WL;\n}" ::"r"(bar), "r"(parity), "n"(SPIN_LIMIT) : "memory");
}
__device__ __forceinline__ void mbar_wait_cluster(uint32_t bar, uint32_t parity) {
    asm volatile(
        "{\n.reg .pred p, q;\n.reg .u32 n;\nmov.u32 n, 0;\n"
        "WL:\nmbarrier.try_wait.parity.acquire.cluster.shared::cta.b64 p, [%0], %1;\n"
        "add.u32 n, n, 1;\nsetp.gt.u32 q, n, %2;\n@q trap;\n@!p bra.uni WL;\n}" ::"r"(bar), "r"(parity), "n"(SPIN_LIMIT) : "memory");
}
__device__ __forceinline__ void tma2d(uint32_t dst, const CUtensorMap* m, int c0, int c1, uint32_t bar) {
    asm volatile("cp.async.bulk.tensor.2d.shared::cluster.global.mbarrier::complete_tx::bytes [%0], [%1, {%3, %4}], [%2];"
                 ::"r"(dst), "l"(m), "r"(bar), "r"(c0), "r"(c1) : "memory");
}
__device__ __forceinline__ void tma4d(uint32_t dst, const CUtensorMap* m, int c2, int c3, uint32_t bar) {
    asm volatile("cp.async.bulk.tensor.4d.shared::cluster.global.mbarrier::complete_tx::bytes [%0], [%1, {%5, %5, %3, %4}], [%2];"
                 ::"r"(dst), "l"(m), "r"(bar), "r"(c2), "r"(c3), "r"(0) : "memory");
}
__device__ __forceinline__ void bulk_g2s(uint32_t dst, const void* src, uint32_t bytes, uint32_t bar) {
    asm volatile("cp.async.bulk.shared::cluster.global.mbarrier::complete_tx::bytes [%0], [%1], %2, [%3];"
                 ::"r"(dst), "l"(src), "r"(bytes), "r"(bar) : "memory");
}
__device__ __forceinline__ void tma4d_prefetch(const CUtensorMap* m, int c2, int c3) {
    asm volatile("cp.async.bulk.prefetch.tensor.4d.L2.global [%0, {%3, %3, %1, %2}];" ::"l"(m), "r"(c2), "r"(c3), "r"(0) : "memory");
}
__device__ __forceinline__ void tma2d_prefetch(const CUtensorMap* m, int c0, int c1) {
    asm volatile("cp.async.bulk.prefetch.tensor.2d.L2.global [%0, {%1, %2}];" ::"l"(m), "r"(c0), "r"(c1) : "memory");
}
__device__ __forceinline__ void fence_async_smem() { asm volatile("fence.proxy.async.shared::cta;" ::: "memory"); }
__device__ __forceinline__ void fence_gpu() { asm volatile("fence.acq_rel.gpu;" ::: "memory"); }
__device__ __forceinline__ float rcp(float x) { float r; asm("rcp.approx.ftz.f32 %0, %1;" : "=f"(r) : "f"(x)); return r; }
__device__ __forceinline__ void bar_sync(int id, int n) { asm volatile("bar.sync %0, %1;" ::"r"(id), "r"(n) : "memory"); }

__device__ __forceinline__ bool bar_or(int id, int n, uint32_t x) {
    uint32_t r;
    asm volatile("{\n.reg .pred p, q;\n.reg .b32 t;\nand.b32 t, %3, 1;\nsetp.ne.u32 p, t, 0;\nbar.red.or.pred q, %1, %2, p;\nselp.u32 %0, 1, 0, q;\n}"
                 : "=r"(r) : "r"(id), "r"(n), "r"(x) : "memory");
    return __any_sync(~0u, r);
}
__device__ __forceinline__ uint32_t or3(uint32_t a, uint32_t b, uint32_t c) {
    uint32_t r; asm("lop3.b32 %0, %1, %2, %3, 0xFE;" : "=r"(r) : "r"(a), "r"(b), "r"(c)); return r;
}
__device__ __forceinline__ uint32_t pack_bf16(float lo, float hi) {
    uint32_t r; asm("cvt.rn.bf16x2.f32 %0, %1, %2;" : "=r"(r) : "f"(hi), "f"(lo)); return r;
}
__device__ __forceinline__ uint32_t add_bf16x2(uint32_t a, uint32_t b) {
    uint32_t r; asm volatile("add.rn.bf16x2 %0, %1, %2;" : "=r"(r) : "r"(a), "r"(b)); return r;
}
__device__ __forceinline__ uint32_t movm(uint32_t a) {
    uint32_t r; asm volatile("movmatrix.sync.aligned.m8n8.trans.b16 %0, %1;" : "=r"(r) : "r"(a)); return r;
}
__device__ __forceinline__ uint32_t orx(uint32_t acc, uint32_t a, uint32_t t) {
    uint32_t r; asm("lop3.b32 %0, %1, %2, %3, 0xF6;" : "=r"(r) : "r"(acc), "r"(a), "r"(t)); return r;
}
__device__ __forceinline__ uint32_t orx2(uint32_t a, uint32_t b, uint32_t t) {
    uint32_t r; asm("lop3.b32 %0, %1, %2, %3, 0x7E;" : "=r"(r) : "r"(a), "r"(b), "r"(t)); return r;
}
__device__ __forceinline__ float ex2(float x) { float r; asm("ex2.approx.ftz.f32 %0, %1;" : "=f"(r) : "f"(x)); return r; }
__device__ __forceinline__ void ldsm4t(uint32_t (&r)[4], uint32_t a) {
    asm volatile("ldmatrix.sync.aligned.m8n8.x4.trans.shared.b16 {%0,%1,%2,%3}, [%4];"
                 : "=r"(r[0]), "=r"(r[1]), "=r"(r[2]), "=r"(r[3]) : "r"(a) : "memory");
}
__device__ __forceinline__ void ldsm4(uint32_t (&r)[4], uint32_t a) {
    asm volatile("ldmatrix.sync.aligned.m8n8.x4.shared.b16 {%0,%1,%2,%3}, [%4];"
                 : "=r"(r[0]), "=r"(r[1]), "=r"(r[2]), "=r"(r[3]) : "r"(a) : "memory");
}
__device__ __forceinline__ void stsm4t(uint32_t a, uint32_t r0, uint32_t r1, uint32_t r2, uint32_t r3) {
    asm volatile("stmatrix.sync.aligned.m8n8.x4.trans.shared.b16 [%0], {%1,%2,%3,%4};"
                 ::"r"(a), "r"(r0), "r"(r1), "r"(r2), "r"(r3) : "memory");
}
__device__ __forceinline__ void stsm4(uint32_t a, uint32_t r0, uint32_t r1, uint32_t r2, uint32_t r3) {
    asm volatile("stmatrix.sync.aligned.m8n8.x4.shared.b16 [%0], {%1,%2,%3,%4};"
                 ::"r"(a), "r"(r0), "r"(r1), "r"(r2), "r"(r3) : "memory");
}
__device__ __forceinline__ void mma16816(float* c, uint32_t a0, uint32_t a1, uint32_t a2, uint32_t a3, uint32_t b0, uint32_t b1) {
    asm volatile("mma.sync.aligned.m16n8k16.row.col.f32.bf16.bf16.f32 {%0,%1,%2,%3}, {%4,%5,%6,%7}, {%8,%9}, {%0,%1,%2,%3};"
                 : "+f"(c[0]), "+f"(c[1]), "+f"(c[2]), "+f"(c[3]) : "r"(a0), "r"(a1), "r"(a2), "r"(a3), "r"(b0), "r"(b1));
}
__device__ __forceinline__ void mma1688(float* c, uint32_t a0, uint32_t a1, uint32_t b0) {
    asm volatile("mma.sync.aligned.m16n8k8.row.col.f32.bf16.bf16.f32 {%0,%1,%2,%3}, {%4,%5}, {%6}, {%0,%1,%2,%3};"
                 : "+f"(c[0]), "+f"(c[1]), "+f"(c[2]), "+f"(c[3]) : "r"(a0), "r"(a1), "r"(b0));
}
__device__ __forceinline__ void sts128(uint32_t a, float x, float y, float z, float w) {
    asm volatile("st.shared.v4.f32 [%0], {%1,%2,%3,%4};" ::"r"(a), "f"(x), "f"(y), "f"(z), "f"(w) : "memory");
}
__device__ __forceinline__ void sts64(uint32_t a, float x, float y) {
    asm volatile("st.shared.v2.f32 [%0], {%1,%2};" ::"r"(a), "f"(x), "f"(y) : "memory");
}
__device__ __forceinline__ void sts32(uint32_t a, uint32_t x) { asm volatile("st.shared.b32 [%0], %1;" ::"r"(a), "r"(x) : "memory"); }
__device__ __forceinline__ void sts128u(uint32_t a, uint4 v) {
    asm volatile("st.shared.v4.b32 [%0], {%1,%2,%3,%4};" ::"r"(a), "r"(v.x), "r"(v.y), "r"(v.z), "r"(v.w) : "memory");
}
__device__ __forceinline__ float4 lds128(uint32_t a) {
    float4 v; asm volatile("ld.shared.v4.f32 {%0,%1,%2,%3}, [%4];" : "=f"(v.x), "=f"(v.y), "=f"(v.z), "=f"(v.w) : "r"(a) : "memory"); return v;
}
__device__ __forceinline__ uint4 lds128u(uint32_t a) {
    uint4 v; asm volatile("ld.shared.v4.b32 {%0,%1,%2,%3}, [%4];" : "=r"(v.x), "=r"(v.y), "=r"(v.z), "=r"(v.w) : "r"(a) : "memory"); return v;
}
__device__ __forceinline__ uint2 lds64u(uint32_t a) {
    uint2 v; asm volatile("ld.shared.v2.b32 {%0,%1}, [%2];" : "=r"(v.x), "=r"(v.y) : "r"(a) : "memory"); return v;
}
__device__ __forceinline__ float2 lds64(uint32_t a) {
    float2 v; asm volatile("ld.shared.v2.f32 {%0,%1}, [%2];" : "=f"(v.x), "=f"(v.y) : "r"(a) : "memory"); return v;
}
__device__ __forceinline__ uint2 ldg_rlx64(const void* p) {
    uint2 v; asm volatile("ld.relaxed.gpu.global.v2.b32 {%0,%1}, [%2];" : "=r"(v.x), "=r"(v.y) : "l"(p) : "memory"); return v;
}
__device__ __forceinline__ uint4 ldg_rlx128(const void* p) {
    uint4 v; asm volatile("ld.relaxed.gpu.global.v4.b32 {%0,%1,%2,%3}, [%4];" : "=r"(v.x), "=r"(v.y), "=r"(v.z), "=r"(v.w) : "l"(p) : "memory"); return v;
}
__device__ __forceinline__ void stg_rlx64(void* p, uint32_t x, uint32_t y) {
    asm volatile("st.relaxed.gpu.global.v2.b32 [%0], {%1,%2};" ::"l"(p), "r"(x), "r"(y) : "memory");
}
__device__ __forceinline__ void stg_rlx128(void* p, uint32_t x, uint32_t y, uint32_t z, uint32_t w) {
    asm volatile("st.relaxed.gpu.global.v4.b32 [%0], {%1,%2,%3,%4};" ::"l"(p), "r"(x), "r"(y), "r"(z), "r"(w) : "memory");
}
__device__ __forceinline__ uint32_t ldg_rlx32(const void* p) {
    uint32_t v; asm volatile("ld.relaxed.gpu.global.b32 %0, [%1];" : "=r"(v) : "l"(p) : "memory"); return v;
}
__device__ __forceinline__ void stg128(void* p, uint32_t x, uint32_t y, uint32_t z, uint32_t w) {
    asm volatile("st.global.v4.b32 [%0], {%1,%2,%3,%4};" ::"l"(p), "r"(x), "r"(y), "r"(z), "r"(w) : "memory");
}
__device__ __forceinline__ uint32_t ld_acquire(const unsigned* p) {
    uint32_t v; asm volatile("ld.acquire.gpu.global.u32 %0, [%1];" : "=r"(v) : "l"(p) : "memory"); return v;
}
__device__ __forceinline__ void red_add_u32(unsigned* p, uint32_t v) {
    asm volatile("red.relaxed.gpu.global.add.u32 [%0], %1;" ::"l"(p), "r"(v) : "memory");
}
__device__ __forceinline__ void wait_counter(const unsigned* p, uint32_t target) {
    uint32_t n = 0;
    while (ld_acquire(p) < target) { if (++n > SPIN_LIMIT) __trap(); }
}

__device__ __forceinline__ void wg_fence() { asm volatile("wgmma.fence.sync.aligned;" ::: "memory"); }
__device__ __forceinline__ void wg_commit() { asm volatile("wgmma.commit_group.sync.aligned;" ::: "memory"); }
template <int N> __device__ __forceinline__ void wg_wait() { asm volatile("wgmma.wait_group.sync.aligned %0;" ::"n"(N) : "memory"); }
__host__ __device__ constexpr uint64_t mkdesc(uint32_t addr, uint32_t lbo, uint32_t sbo, uint32_t swz) {
    return (uint64_t)((addr & 0x3FFFF) >> 4) | ((uint64_t)(lbo >> 4) << 16) | ((uint64_t)(sbo >> 4) << 32) | ((uint64_t)swz << 62);
}
#define F4(d, o) "+f"(d[o]), "+f"(d[o + 1]), "+f"(d[o + 2]), "+f"(d[o + 3])
template <int SC> __device__ __forceinline__ void wg_rs32(float (&d)[16], const uint32_t (&a)[4], uint64_t db) {
    asm volatile("wgmma.mma_async.sync.aligned.m64n32k16.f32.bf16.bf16 "
                 "{%0,%1,%2,%3,%4,%5,%6,%7,%8,%9,%10,%11,%12,%13,%14,%15}, {%16,%17,%18,%19}, %20, %21, 1, 1, 0;"
                 : F4(d, 0), F4(d, 4), F4(d, 8), F4(d, 12)
                 : "r"(a[0]), "r"(a[1]), "r"(a[2]), "r"(a[3]), "l"(db), "n"(SC));
}
template <int SC> __device__ __forceinline__ void wg_rs40(float (&d)[20], const uint32_t (&a)[4], uint64_t db) {
    asm volatile("wgmma.mma_async.sync.aligned.m64n40k16.f32.bf16.bf16 "
                 "{%0,%1,%2,%3,%4,%5,%6,%7,%8,%9,%10,%11,%12,%13,%14,%15,%16,%17,%18,%19}, {%20,%21,%22,%23}, %24, %25, 1, 1, 0;"
                 : F4(d, 0), F4(d, 4), F4(d, 8), F4(d, 12), F4(d, 16)
                 : "r"(a[0]), "r"(a[1]), "r"(a[2]), "r"(a[3]), "l"(db), "n"(SC));
}
template <int SC> __device__ __forceinline__ void wg_ss40(float (&d)[20], uint64_t da, uint64_t db) {
    asm volatile("wgmma.mma_async.sync.aligned.m64n40k16.f32.bf16.bf16 "
                 "{%0,%1,%2,%3,%4,%5,%6,%7,%8,%9,%10,%11,%12,%13,%14,%15,%16,%17,%18,%19}, %20, %21, %22, 1, 1, 1, 0;"
                 : F4(d, 0), F4(d, 4), F4(d, 8), F4(d, 12), F4(d, 16)
                 : "l"(da), "l"(db), "n"(SC));
}
template <int SC> __device__ __forceinline__ void wg_ss8(float (&d)[4], uint64_t da, uint64_t db) {
    asm volatile("wgmma.mma_async.sync.aligned.m64n8k16.f32.bf16.bf16 {%0,%1,%2,%3}, %4, %5, %6, 1, 1, 1, 1;"
                 : F4(d, 0) : "l"(da), "l"(db), "n"(SC));
}

constexpr int DBG_N = 12;
#define TSI(st) do {} while (0)
#define TS(k) do {} while (0)
#define TSV(k, v) do {} while (0)
#define TSDUMP() do {} while (0)
#define GT(k) do {} while (0)
#define FLAG(b) false

__device__ uint4 g_fy[2048 * 128];

constexpr uint32_t FG_SIZE = 2 * 32768 + 36864;
constexpr uint32_t FT_F16 = 2 * FG_SIZE, FT_B1F = FT_F16 + 2048, FT_B1I = FT_B1F + 2048, FT_C = FT_B1I + 2048, FT_A8 = FT_C + 2048,
                   FT_TWC = FT_A8 + 512, FT_TWB = FT_TWC + 8192, FT_BAR = FT_TWB + 8192, FFT_SMEM = FT_BAR + 256;
struct FftMaps { CUtensorMap x, y, o, y2, wr, wi; };

__device__ __forceinline__ float2 wroot(int e) {
    float s, c; sincospif((float)(e & 2047) * (-1.f / 1024.f), &s, &c); return make_float2(c, s);
}
__device__ __forceinline__ uint4 afrag(float2 a, float2 b) {
    return make_uint4(pack_bf16(a.x, -a.y), pack_bf16(a.y, a.x), pack_bf16(b.x, -b.y), pack_bf16(b.y, b.x));
}
__device__ __forceinline__ uint4 conjfrag(uint4 v) { return make_uint4(v.x ^ 0x80000000u, v.y ^ 0x8000u, v.z ^ 0x80000000u, v.w ^ 0x8000u); }
__device__ __forceinline__ uint4 negfrag(uint4 v) { return make_uint4(v.x ^ 0x80008000u, v.y ^ 0x80008000u, v.z ^ 0x80008000u, v.w ^ 0x80008000u); }
__device__ __forceinline__ uint32_t comp(const uint4& v, int i) { return i == 0 ? v.x : i == 1 ? v.y : i == 2 ? v.z : v.w; }
__device__ __forceinline__ void setcomp(uint4& v, int i, uint32_t x) { if (i == 0) v.x = x; else if (i == 1) v.y = x; else if (i == 2) v.z = x; else v.w = x; }
__device__ __forceinline__ float2 cmul(float2 a, float2 b) { return make_float2(a.x * b.x - a.y * b.y, a.x * b.y + a.y * b.x); }
__device__ __forceinline__ float2 cmulc(float2 a, float2 b) { return make_float2(a.x * b.x + a.y * b.y, a.y * b.x - a.x * b.y); }

__device__ __forceinline__ uint32_t pack_h2(float2 a) { uint32_t r; asm("cvt.rn.f16x2.f32 %0, %1, %2;" : "=r"(r) : "f"(a.y), "f"(a.x)); return r; }
__device__ __forceinline__ float2 unpack_h2(uint32_t v) {
    float2 r; asm("{\n.reg .b16 l, h;\nmov.b32 {l, h}, %2;\ncvt.f32.f16 %0, l;\ncvt.f32.f16 %1, h;\n}" : "=f"(r.x), "=f"(r.y) : "r"(v)); return r;
}
__device__ __forceinline__ void fft_tables(uint32_t tb, int tid, int nthr) {
    for (int i = tid; i < 128; i += nthr) {
        const int lane = i & 31, q = i >> 5, g = lane >> 2, t = lane & 3, o = 8 * (q >> 1) + g, in = 8 * (q & 1) + 2 * t;
        sts128u(tb + FT_F16 + i * 16, afrag(wroot(128 * o * in), wroot(128 * o * (in + 1))));
        sts128u(tb + FT_B1F + i * 16, afrag(wroot(64 * (1 + 2 * o) * in), wroot(64 * (1 + 2 * o) * (in + 1))));
        sts128u(tb + FT_B1I + i * 16, afrag(wroot(-64 * o * (1 + 2 * in)), wroot(-64 * o * (3 + 2 * in))));
        uint4 v;
        for (int r = 0; r < 4; r++) {
            const float2 a = wroot(128 * (4 * r + t) * (4 * q + (g >> 1)));
            setcomp(v, r, (g & 1) ? pack_bf16(a.y, a.x) : pack_bf16(a.x, -a.y));
        }
        sts128u(tb + FT_C + i * 16, v);
        if (q == 0) sts128u(tb + FT_A8 + lane * 16, afrag(wroot(256 * g * 2 * t), wroot(256 * g * (2 * t + 1))));
    }
    for (int i = tid; i < 512; i += nthr) {
        const int lane = i & 31, r = (i >> 5) & 3, phi = 8 * (i >> 7) + (lane >> 2), c = 4 * r + (lane & 3);
        const float2 a = wroot(4 * c * phi), b = wroot(2 * (phi + 32 * c));
        constexpr float SC = 1.f / (2.f * 2048.f * 512.f);
        sts128(tb + FT_TWC + i * 16, a.x * SC, a.y * SC, b.x, b.y);
    }
    for (int i = tid; i < 512; i += nthr) {
        const int lane = i & 31, r = (i >> 5) & 3, fa = (i >> 7) & 1, hf = i >> 8, c = 8 * (lane & 1) + r;
        const int p0 = fa + 2 * (lane >> 2), p1 = p0 + 16, s0 = (hf && p0) ? 32 - p0 : p0, s1 = hf ? 32 - p1 : p1;
        sts128u(tb + FT_TWB + i * 16, make_uint4(pack_h2(wroot(4 * c * s0)), pack_h2(wroot(4 * (c + 4) * s0)),
                                                 pack_h2(wroot(4 * c * s1)), pack_h2(wroot(4 * (c + 4) * s1))));
    }
}

template <bool TW>
__device__ __forceinline__ void dft16(uint4 (&out)[4], const uint4 (&in)[4], const uint4 (&m)[4], const uint4 (&tw)[4]) {
#pragma unroll
    for (int i = 0; i < 4; i++)
#pragma unroll
        for (int mt = 0; mt < 2; mt++) {
            float c[4] = {0.f, 0.f, 0.f, 0.f};
            mma16816(c, m[2 * mt].x, m[2 * mt].y, m[2 * mt].z, m[2 * mt].w, comp(in[0], i), comp(in[1], i));
            mma16816(c, m[2 * mt + 1].x, m[2 * mt + 1].y, m[2 * mt + 1].z, m[2 * mt + 1].w, comp(in[2], i), comp(in[3], i));
            if (TW) {
                const float2 a = cmul(make_float2(c[0], c[2]), unpack_h2(comp(tw[i], 2 * mt))), b = cmul(make_float2(c[1], c[3]), unpack_h2(comp(tw[i], 2 * mt + 1)));
                setcomp(out[2 * mt], i, pack_bf16(a.x, a.y));
                setcomp(out[2 * mt + 1], i, pack_bf16(b.x, b.y));
            } else {
                setcomp(out[2 * mt], i, pack_bf16(c[0], c[2]));
                setcomp(out[2 * mt + 1], i, pack_bf16(c[1], c[3]));
            }
        }
}
__device__ __forceinline__ void tma_ld4(uint32_t dst, const CUtensorMap* m, int c0, int c1, uint32_t bar) {
    asm volatile("cp.async.bulk.tensor.4d.shared::cluster.global.mbarrier::complete_tx::bytes [%0], [%1, {%3, %4, %5, %5}], [%2];"
                 ::"r"(dst), "l"(m), "r"(bar), "r"(c0), "r"(c1), "r"(0) : "memory");
}
__device__ __forceinline__ void tma_st4(uint32_t src, const CUtensorMap* m, int c0, int c1) {
    asm volatile("cp.async.bulk.tensor.4d.global.shared::cta.bulk_group [%1, {%2, %3, %4, %4}], [%0];" ::"r"(src), "l"(m), "r"(c0), "r"(c1), "r"(0) : "memory");
}
__device__ __forceinline__ void tma_ld3(uint32_t dst, const CUtensorMap* m, int c0, int c1, uint32_t bar) {
    asm volatile("cp.async.bulk.tensor.3d.shared::cluster.global.mbarrier::complete_tx::bytes [%0], [%1, {%3, %4, %5}], [%2];"
                 ::"r"(dst), "l"(m), "r"(bar), "r"(c0), "r"(c1), "r"(0) : "memory");
}
__device__ __forceinline__ void tma_st3(uint32_t src, const CUtensorMap* m, int c0, int c1) {
    asm volatile("cp.async.bulk.tensor.3d.global.shared::cta.bulk_group [%1, {%2, %3, %4}], [%0];" ::"r"(src), "l"(m), "r"(c0), "r"(c1), "r"(0) : "memory");
}
__device__ __forceinline__ void bulk_commit() { asm volatile("cp.async.bulk.commit_group;" ::: "memory"); }
__device__ __forceinline__ void bulk_wait_read() { asm volatile("cp.async.bulk.wait_group.read 0;" ::: "memory"); }
__device__ __forceinline__ void bulk_wait_all() { asm volatile("cp.async.bulk.wait_group 0;" ::: "memory"); }

__device__ __forceinline__ float2 wroot_fast(int e) {
    float s, c; __sincosf((float)(((e + 1024) & 2047) - 1024) * (-3.14159265358979f / 1024.f), &s, &c); return make_float2(c, s);
}
template <bool INV, int NT>
__device__ __forceinline__ void fft_col(int s2, int t0, const CUtensorMap* src, const CUtensorMap* dst, uint32_t gb, uint32_t mb,
                                        int w, int lane, int bar) {
    const int g = lane >> 2, t = lane & 3;
    const bool lead = w == 4 && lane == 0;
    if (NT > 1 && lead)
        for (int i = 0; i < 2; i++) { mbar_expect_tx(mb + 8 * i, 32768); tma_ld4(gb + i * 32768, src, (t0 + i) * 64, s2, mb + 8 * i); }
    uint4 f[4], m[2][4];
#pragma unroll
    for (int i = 0; i < 4; i++) {
        const int o = 8 * (i >> 1) + g, in = 8 * (i & 1) + 2 * t, sg = INV ? -128 : 128;
        f[i] = afrag(wroot_fast(sg * o * in), wroot_fast(sg * o * (in + 1)));
#pragma unroll
        for (int q = 0; q < 2; q++) {
            const int z = 2 * w + q;
            m[q][i] = INV ? afrag(wroot_fast(-(8 * o + s2) * (z + 16 * in)), wroot_fast(-(8 * o + s2) * (z + 16 * in + 16)))
                          : afrag(wroot_fast((z + 16 * o) * (8 * in + s2)), wroot_fast((z + 16 * o) * (8 * in + 8 + s2)));
        }
    }
    const uint32_t r1 = (32 * w + 2 * t) * 128 + ((g ^ (2 * t)) << 4);
    const uint32_t w1 = (32 * w + g) * 128 + (((2 * t) ^ (((w & 3) << 1) | (g & 1))) << 4);
    const uint32_t r2 = (32 * t + 2 * w) * 128 + ((g ^ (2 * t)) << 4);
    const uint32_t w2 = (32 * w + g) * 128 + (((2 * t) ^ g) << 4);
    int bi = 0, ph = 0;
#pragma unroll 1
    for (int it = 0; it < NT; it++) {
        const uint32_t buf = gb + bi * 32768;
        mbar_wait(mb + 8 * bi, ph);
        uint4 in[2][4], out[4];
#pragma unroll
        for (int q = 0; q < 2; q++)
#pragma unroll
            for (int i = 0; i < 4; i++) in[q][i] = lds128u(buf + (r1 ^ ((i & 1) * 0x90)) + (i >> 1) * 1024 + q * 2048);
        __syncwarp();
#pragma unroll
        for (int q = 0; q < 2; q++) {
            if (INV) dft16<false>(out, in[q], m[q], f); else dft16<false>(out, in[q], f, f);
#pragma unroll
            for (int i = 0; i < 4; i++) sts128u(buf + (w1 ^ ((i & 1) << 4)) + (i >> 1) * 1024 + q * 2048, out[i]);
        }
        bar_sync(bar, 256);
#pragma unroll
        for (int q = 0; q < 2; q++)
#pragma unroll
            for (int i = 0; i < 4; i++) in[q][i] = lds128u(buf + (r2 ^ (q * 0x90)) + (i & 1) * 2048 + (i >> 1) * 16384);
        const int bn = bi == 0 ? 2 : bi - 1;
        if (lead && it < NT - 2) { bulk_wait_read(); mbar_expect_tx(mb + 8 * bn, 32768); tma_ld4(gb + bn * 32768, src, (t0 + it + 2) * 64, s2, mb + 8 * bn); }
        bar_sync(bar, 256);
#pragma unroll
        for (int q = 0; q < 2; q++) {
            if (INV) dft16<false>(out, in[q], f, f); else dft16<false>(out, in[q], m[q], f);
#pragma unroll
            for (int i = 0; i < 4; i++) sts128u(buf + (w2 ^ ((i & 1) << 4)) + (i >> 1) * 1024 + q * 2048, out[i]);
        }
        fence_async_smem();
        bar_sync(bar, 256);
        if (lead) { tma_st4(buf, dst, (t0 + it) * 64, s2); bulk_commit(); }
        if (++bi == 3) { bi = 0; ph ^= 1; }
    }
    if (lead) bulk_wait_read();
}

__device__ __forceinline__ float ldw(uint32_t a) {
    uint16_t v; asm volatile("ld.shared.u16 %0, [%1];" : "=h"(v) : "r"(a) : "memory");
    return __uint_as_float((uint32_t)v << 16);
}
__device__ __forceinline__ void fft_mid(int grp, const FftMaps& fm, uint32_t tb,
                                        uint32_t gb, uint32_t mb, uint32_t& cnt, int w, int lane, int bar) {
    const int g = lane >> 2, t = lane & 3;
    const bool lead = w == 4 && lane == 0;
    const uint32_t wb = gb + 65536;
#define MID_LOAD(k, c)                                                                                                  \
    { mbar_expect_tx(mb + 8 * ((c) & 1), 32768);                                                                        \
      tma_ld3(gb + ((c) & 1) * 32768, &fm.y2, 0, (k) * 8, mb + 8 * ((c) & 1));                                          \
      tma_ld3(gb + ((c) & 1) * 32768 + 16384, &fm.y2, 0, ((256 - (k)) & 255) * 8, mb + 8 * ((c) & 1)); }
#define MID_LOADW(k)                                                                                                    \
    { mbar_expect_tx(mb + 16, 36864);                                                                                   \
      tma_ld3(wb, &fm.wr, (k) * 513 & ~7, 0, mb + 16); tma_ld3(wb + 9216, &fm.wi, (k) * 513 & ~7, 0, mb + 16);          \
      tma_ld3(wb + 18432, &fm.wr, ((256 - (k)) & 255) * 513 & ~7, 0, mb + 16); tma_ld3(wb + 27648, &fm.wi, ((256 - (k)) & 255) * 513 & ~7, 0, mb + 16); }
    if (lead) { MID_LOAD(grp, cnt); MID_LOADW(grp); }
    const int hB = w >> 2, faB = (w >> 1) & 1, xB = faB;
    const int phi = 8 * (w & 3) + g;
    const uint32_t rA = (8 * w + 2 * t) * 128 + ((g ^ (2 * t)) << 4);
    const uint32_t wA = (8 * w + g) * 128 + (((2 * t) ^ ((g & 1) | ((w & 3) << 1))) << 4);
    const uint32_t oB = (w >> 1) * 8192 + (w & 1) * 512;
    const uint32_t rB = oB + (8 * t + (g >> 2)) * 128 + (((g & 3) ^ ((g >> 2) | (t << 1)) ^ xB) << 4);
    const uint32_t wB = oB + (8 * (g >> 1) + (t >> 1)) * 128 + (((((g & 1) << 2) | (2 * (t & 1))) ^ ((t >> 1) | ((g >> 1) << 1)) ^ xB) << 4);
    const uint32_t wBi = oB + (8 * (g >> 1) + (t >> 1)) * 128 + (((((g & 1) << 2) | (2 * (t & 1))) ^ ((t >> 1) | ((w & 1) << 2))) << 4);
    const int hC = (lane >> 3) & 1, pr = 8 * (w & 3) + (lane & 7), pc = hC ? (32 - pr) & 31 : pr;
    const uint32_t aC = hC * 16384 + (pc & 1) * 8192 + (pc >> 2) * 1024 + (((((pc & 2) << 1) | (lane >> 4)) ^ (((pc >> 2) & 3) << 1) ^ (pc & 1)) << 4);
    const uint32_t g0 = wb + (t >> 1) * 144 + (32 * (t & 1) + phi) * 2, g1 = wb + 18432 + (7 - (t >> 1)) * 144 + (64 - 32 * (t & 1) - phi) * 2;
    const uint32_t wAo = (8 * w + g) * 128 + (((2 * t) ^ g) << 4);
    uint32_t wph = 0;
#pragma unroll 1
    for (int k1 = grp; k1 < 129; k1 += 8, cnt++, wph ^= 1) {
        const uint32_t buf = gb + (cnt & 1) * 32768;
        uint4 in[2][4], m[4], out[4];
        m[0] = m[1] = m[2] = lds128u(tb + FT_A8 + lane * 16);
        m[3] = negfrag(m[0]);
        mbar_wait(mb + 8 * (cnt & 1), (cnt >> 1) & 1);
#pragma unroll
        for (int q = 0; q < 2; q++)
#pragma unroll
            for (int i = 0; i < 4; i++) in[q][i] = lds128u(buf + (rA ^ ((i & 1) * 0x90)) + (i >> 1) * 8192 + q * 16384);
        __syncwarp();
#pragma unroll
        for (int q = 0; q < 2; q++) {
            dft16<false>(out, in[q], m, m);
#pragma unroll
            for (int i = 0; i < 4; i++) sts128u(buf + (wA ^ (((i ^ (i >> 1)) & 1) << 4)) + (i >> 1) * 8192 + q * 16384, out[i]);
        }
        {
            uint4 tw[4];
#pragma unroll
            for (int i = 0; i < 4; i++) {
                m[i] = lds128u(tb + (faB ? FT_B1F : FT_F16) + i * 512 + lane * 16);
                if (hB) { m[i].y ^= 0x80008000u; m[i].w ^= 0x80008000u; }
                tw[i] = lds128u(tb + FT_TWB + (w >> 1) * 2048 + i * 512 + lane * 16);
            }
            bar_sync(bar, 256);
#pragma unroll
            for (int q = 0; q < 2; q++)
#pragma unroll
                for (int i = 0; i < 4; i++) in[q][i] = lds128u(buf + (rB ^ ((i & 1) << 6)) + (i >> 1) * 4096 + q * 256);
            __syncwarp();
#pragma unroll
            for (int q = 0; q < 2; q++) {
                dft16<true>(out, in[q], m, tw);
#pragma unroll
                for (int i = 0; i < 4; i++) sts128u(buf + (wB ^ ((i & 1) << 4)) + (i >> 1) * 4096 + q * 256, out[i]);
            }
        }
        {
            const uint32_t cjm = (g & 1) ? 0x8000u : 0x80000000u;
            float4 tw[4];
#pragma unroll
            for (int i = 0; i < 4; i++) { m[i] = lds128u(tb + FT_C + i * 512 + lane * 16); tw[i] = lds128(tb + FT_TWC + ((w & 3) * 4 + i) * 512 + lane * 16); }
            if (lead && k1 + 8 < 129) { bulk_wait_read(); MID_LOAD(k1 + 8, cnt + 1); }
            __syncwarp();
            mbar_wait(mb + 16, wph);
            const uint32_t o0 = (k1 & 7) * 2, o1 = (-k1 & 7) * 2;
            if (w == 1 && lane < 16) {
                const int k2 = lane & 7, k2p = k1 ? 7 - k2 : (8 - k2) & 7;
                const uint32_t p0 = wb + (lane >> 3) * 9216 + k2 * 1152 + o0, p1 = wb + 18432 + (lane >> 3) * 9216 + k2p * 1152 + o1;
                const float sg = lane < 8 ? 0.5f : -0.5f;
                const uint32_t v = pack_bf16(0.5f * ldw(p0) + sg * ldw(p1), 0.5f * ldw(p1 + 1136) + sg * ldw(p0 + 1136));
                asm volatile("st.shared.u16 [%0], %1;" ::"r"(p0), "h"((uint16_t)v) : "memory");
                asm volatile("st.shared.u16 [%0], %1;" ::"r"(p1 + 1136), "h"((uint16_t)(v >> 16)) : "memory");
                fence_async_smem();
            }
            bar_sync(bar, 256);
#define FFT_CU 1
            constexpr int CU = FFT_CU;
#pragma unroll CU
            for (int q = 0; q < 4; q++) {
                const int k2 = 4 * (w >> 2) + q, k2p = k1 ? 7 - k2 : (8 - k2) & 7, kr = hC ? k2p : k2;
                const uint32_t a0 = buf + (aC ^ ((kr & 1) << 4)) + kr * 128;
                const uint32_t r0 = g0 + k2 * 1152 + o0, r1 = g1 + k2p * 1152 + o1;
                uint32_t x[4], y[4];
                ldsm4(x, a0); ldsm4(y, a0 ^ 32);
                float c[4][4];
#pragma unroll
                for (int i = 0; i < 4; i++) { c[i][0] = c[i][1] = c[i][2] = c[i][3] = 0.f; mma16816(c[i], x[0], x[1], x[2], x[3], m[i].x, m[i].y); }
#pragma unroll
                for (int i = 0; i < 4; i++) mma16816(c[i], y[0], y[1], y[2], y[3], m[i].z, m[i].w);
#pragma unroll
                for (int i = 0; i < 4; i++) {
                    const float2 ga = make_float2(ldw(r0 + i * 288), ldw(r0 + 9216 + i * 288));
                    const float2 gc = make_float2(ldw(r1 - i * 288), ldw(r1 + 9216 - i * 288));
                    const float tc = tw[i].z, ts = tw[i].w;
                    const float* z = c[i];
                    const float2 S = make_float2(ga.x + gc.x, ga.y - gc.y), D = make_float2(ga.x - gc.x, ga.y + gc.y);
                    const float2 u = make_float2(ts * z[0] - tc * z[3], ts * z[1] + tc * z[2]), v = make_float2(ts * z[2] - tc * z[1], ts * z[3] + tc * z[0]);
                    uint32_t* o = (i < 2 ? x : y) + 2 * (i & 1);
                    o[0] = pack_bf16(fmaf(S.x, z[0], fmaf(-S.y, z[1], fmaf(D.x, u.x, -D.y * u.y))), fmaf(S.x, z[1], fmaf(S.y, z[0], fmaf(D.x, u.y, D.y * u.x))));
                    o[1] = pack_bf16(fmaf(S.x, z[2], fmaf(-S.y, z[3], fmaf(-D.x, v.x, D.y * v.y))), fmaf(S.x, z[3], fmaf(S.y, z[2], fmaf(-D.x, v.y, -D.y * v.x))));
                }
#pragma unroll
                for (int i = 0; i < 4; i++) { c[i][0] = c[i][1] = c[i][2] = c[i][3] = 0.f; mma16816(c[i], x[0], x[1], x[2], x[3], m[i].x ^ cjm, m[i].y ^ cjm); }
#pragma unroll
                for (int i = 0; i < 4; i++) mma16816(c[i], y[0], y[1], y[2], y[3], m[i].z ^ cjm, m[i].w ^ cjm);
#pragma unroll
                for (int i = 0; i < 4; i++) {
                    uint32_t* o = (i < 2 ? x : y) + 2 * (i & 1);
                    o[0] = pack_bf16(c[i][0] * tw[i].x + c[i][1] * tw[i].y, c[i][1] * tw[i].x - c[i][0] * tw[i].y);
                    o[1] = pack_bf16(c[i][2] * tw[i].x + c[i][3] * tw[i].y, c[i][2] * tw[i].y - c[i][3] * tw[i].x);
                }
                stsm4(a0, x[0], x[1], x[2], x[3]);
                stsm4(a0 ^ 32, y[0], y[1], y[2], y[3]);
            }
        }
#pragma unroll
        for (int i = 0; i < 4; i++) { m[i] = lds128u(tb + (faB ? FT_B1I : FT_F16) + i * 512 + lane * 16); if (!faB) m[i] = conjfrag(m[i]); }
        bar_sync(bar, 256);
        if (lead && k1 + 8 < 129) MID_LOADW(k1 + 8);
        __syncwarp();
#pragma unroll
        for (int q = 0; q < 2; q++)
#pragma unroll
            for (int i = 0; i < 4; i++) in[q][i] = lds128u(buf + (rB ^ ((i & 1) << 6)) + (i >> 1) * 4096 + q * 256);
        __syncwarp();
#pragma unroll
        for (int q = 0; q < 2; q++) {
            dft16<false>(out, in[q], m, m);
#pragma unroll
            for (int i = 0; i < 4; i++) sts128u(buf + (wBi ^ ((i & 1) << 4) ^ (q << 5)) + (i >> 1) * 4096 + q * 256, out[i]);
        }
        m[0] = m[1] = m[2] = conjfrag(lds128u(tb + FT_A8 + lane * 16));
        m[3] = negfrag(m[0]);
        bar_sync(bar, 256);
#pragma unroll
        for (int q = 0; q < 2; q++)
#pragma unroll
            for (int i = 0; i < 4; i++) in[q][i] = lds128u(buf + (rA ^ ((i & 1) * 0x90)) + (i >> 1) * 8192 + q * 16384);
        __syncwarp();
#pragma unroll
        for (int q = 0; q < 2; q++) {
            dft16<false>(out, in[q], m, m);
#pragma unroll
            for (int i = 0; i < 4; i++) sts128u(buf + (wAo ^ ((i & 1) << 4)) + (i >> 1) * 8192 + q * 16384, out[i]);
        }
        fence_async_smem();
        bar_sync(bar, 256);
        if (lead) {
            tma_st3(buf, &fm.y2, 0, k1 * 8);
            if (k1 & 127) tma_st3(buf + 16384, &fm.y2, 0, (256 - k1) * 8);
            bulk_commit();
        }
    }
    if (lead) bulk_wait_all();
}

__device__ unsigned g_start;
__device__ unsigned g_fbar;
__device__ unsigned g_end;
__device__ __forceinline__ unsigned gbar_arrive(unsigned* c, unsigned inc, unsigned total, int lane) {
    unsigned v = 0;
    if (lane == 0) { asm volatile("fence.proxy.async;" ::: "memory"); fence_gpu(); v = atomicAdd(c, inc); }
    return (__shfl_sync(~0u, v, 0) & ~(total - 1)) + total;
}
__device__ __forceinline__ void gbar_wait(unsigned* c, unsigned target, unsigned ns) {
    uint32_t n = 0;
    while (__any_sync(~0u, (int)(ld_acquire(c) - target) < 0)) { if (ns) __nanosleep(ns); if (++n > SPIN_LIMIT) __trap(); }
    asm volatile("fence.proxy.async;" ::: "memory");
}
__device__ __forceinline__ void fft_rest(int cta, const FftMaps& fm, uint32_t sb) {
    const int hi = __shfl_sync(~0u, threadIdx.x >> 8, 0), w = __shfl_sync(~0u, (threadIdx.x >> 5) & 7, 0), lane = threadIdx.x & 31;
    unsigned target = 0;
    if (w == 4) target = gbar_arrive(&g_start, 16, 256, lane);
    if (threadIdx.x < 32) mbar_init(sb + FT_BAR + 8 * threadIdx.x, 1);
    fft_tables(sb, threadIdx.x, 512);
    fence_async_smem();
    __syncthreads();
    const int grp = cta * 2 + hi, bar = 1 + hi;
    const uint32_t gb = sb + hi * FG_SIZE, mb = sb + FT_BAR + hi * 128;
    uint32_t cnt = 0;
    if (w == 4) gbar_wait(&g_start, target, 200);
    GT(1);
    fft_mid(grp, fm, sb, gb, mb, cnt, w, lane, bar);
    if (w == 4) gbar_wait(&g_fbar, gbar_arrive(&g_fbar, 1, 8, lane), 200);
    GT(2);
    fft_col<true, 16>(grp, 0, &fm.y, &fm.o, gb, mb + 64, w, lane, bar);
}

__device__ uint4 g_kvq[4 * 32 * 3 * 8 * 2 * 32];
__device__ uint2 g_alpha[2 * 32 * 3 * 8 * 2 * 32];
__device__ uint4 g_red[5 * 32768 / 16];
__device__ uint4 g_stamp[32];
__device__ uint4 g_qst[128 * 2];
__device__ bf16 g_ox[2048 * 4096];
struct Tune { uint32_t d_alpha, d_r0, d_r1, flags, d_st, d_v, spread, extra; };
#define QKW_EARLY 1
constexpr int RA = 2;
#define AV_POS 2

constexpr uint32_t SM_BASE = 1024;
constexpr uint32_t O_WO = 0;
constexpr uint32_t O_WV = 65536;
constexpr uint32_t O_XB = 131072;
constexpr uint32_t O_MEM = O_XB + 32768;
constexpr uint32_t O_RECV = O_MEM + 8192;
constexpr uint32_t O_KVQ = O_RECV + 12288;
constexpr uint32_t O_STG = O_KVQ + 18432;
constexpr uint32_t O_S = O_STG + 8192;
constexpr uint32_t O_XO = O_STG + 16384;
constexpr uint32_t O_P = O_S + 10240;
constexpr uint32_t O_O = O_P + 1536;
constexpr uint32_t O_VM = O_O + 2048;
constexpr uint32_t O_QST = O_VM + 2048;
constexpr uint32_t O_DBG = O_QST + 128;
constexpr uint32_t O_F1 = 196608;
constexpr uint32_t O_BAR = 232448 - 512;
constexpr uint32_t MAIN_SMEM = 232448;
static_assert(O_DBG + (DBG_TIMING ? 4 * DBG_N * 24 * 4 : 0) <= O_BAR && FFT_SMEM <= MAIN_SMEM && O_F1 + 32768 <= O_BAR, "smem");
constexpr int G_ST = 6;
enum { B_WQ0 = 0, B_WQ1, B_WK0, B_WK1, B_WV, B_WO, B_QDONE, B_KDONE, B_XFULL, B_XEMPTY, B_MEM, B_RFULL, B_AFULL, B_KVFULL,
       B_RECV, B_QKW = B_RECV + 6, B_SDONE, B_SRDY, B_OPDONE, B_F1, B_GF, B_GE = B_GF + G_ST, B_COUNT = B_GE + G_ST };

constexpr float SM_SCALE_LOG2 = 0.08838834764831845f * 1.4426950408889634f;
constexpr float MASK_VAL = -1.0e9f / 0.08838834764831845f;

__device__ __forceinline__ uint32_t red_grp(int grp) { return (uint32_t)((grp >> 1) * 1024 + (grp & 1) * 256); }
__host__ __device__ constexpr uint64_t xdesc(int ks) { return mkdesc(SM_BASE + O_XB + (ks >> 2) * 1024 + (ks & 3) * 32, 16, 8192, 1); }

__device__ __forceinline__ void x_split(const float* d, uint32_t (&sn)[4], uint32_t (&kp)[4], int kh) {
#pragma unroll
    for (int i = 0; i < 4; i++) {
        const uint32_t lo = pack_bf16(d[2 * i], d[2 * i + 1]), hi = pack_bf16(d[8 + 2 * i], d[8 + 2 * i + 1]);
        sn[i] = kh ? lo : hi; kp[i] = kh ? hi : lo;
    }
}
__device__ __forceinline__ void x_send(int R, const uint32_t (&sn)[4], int sg, int tid, uint32_t sb, uint32_t mate) {
    const uint32_t par = sg & 1;
    const uint32_t bar = O_BAR + 8 * (B_RECV + R * 2) + 8 * par;
    if (tid == 0) mbar_expect_tx(sb + bar, 2048);
    asm volatile("st.async.shared::cluster.mbarrier::complete_tx::bytes.v4.b32 [%0], {%1,%2,%3,%4}, [%5];"
                 ::"r"(mate + O_RECV + (par * 3 + R) * 2048 + tid * 16), "r"(sn[0]), "r"(sn[1]), "r"(sn[2]), "r"(sn[3]), "r"(mate + bar) : "memory");
}
__device__ __forceinline__ void x_wait(int R, int sg, uint32_t sb) {
    mbar_wait_cluster(sb + O_BAR + 8 * (B_RECV + R * 2) + 8 * (sg & 1), (sg >> 1) & 1);
}
template <int R>
__device__ __forceinline__ void x_finish(const uint32_t (&kp)[4], int sg, int h, int mt, int kh, int tid, uint32_t sb) {
    const uint4 r = lds128u(sb + O_RECV + ((sg & 1) * 3 + R) * 2048 + tid * 16);
    uint32_t u0 = add_bf16x2(kp[0], r.x), u1 = add_bf16x2(kp[1], r.y), u2 = add_bf16x2(kp[2], r.z), u3 = add_bf16x2(kp[3], r.w);
    if (R < 2) { u0 = movm(u0); u1 = movm(u1); u2 = movm(u2); u3 = movm(u3); }
    const uint32_t tag = ((sg >> 2) & 1) ^ 1;
    u0 = (u0 & ~1u) | tag;
    uint4* const hb = &g_kvq[((sg & 3) * 32 + h) * (3 * 512)];
    if (R == 0) {
        uint2* p = (uint2*)hb + (kh * 16 + mt) * 32 + (tid & 31);
        asm volatile("{\n.reg .pred p;\nsetp.lt.s32 p, %5, 64;\n@p st.relaxed.gpu.global.v2.b32 [%0], {%1,%2};\n@p st.relaxed.gpu.global.v2.b32 [%0+2048], {%3,%4};\n}"
                     ::"l"(p), "r"(u0), "r"(u1), "r"((u2 & ~1u) | tag), "r"(u3), "r"(sg) : "memory");
    } else {
        asm volatile("{\n.reg .pred p;\nsetp.lt.s32 p, %5, 64;\n@p st.relaxed.gpu.global.v4.b32 [%0], {%1,%2,%3,%4};\n}"
                     ::"l"(hb + R * 512 + (mt * 2 + kh) * 32 + (tid & 31)), "r"(u0), "r"(u1), "r"(u2), "r"(u3), "r"(sg) : "memory");
    }
}

__device__ __forceinline__ uint32_t convert_mem(const unsigned char* redp, int s, int kh, int jj, int w, int lane, uint32_t sb) {
    const uint32_t off = red_grp(jj * 16 + w * 4 + (lane >> 3)), o16 = off + (lane & 7) * 16, o8 = off + 512 + ((lane >> 3) & 1) * 64 + (lane & 7) * 8;
    uint32_t ma = sb + O_MEM + (jj * 4 + (lane >> 4)) * 1024 + (lane & 7) * 128 + (((2 * w + ((lane >> 3) & 1)) ^ (lane & 7)) << 4);
    uint32_t a16 = sb + O_STG + o16, a8 = sb + O_STG + o8;
    const uint32_t target = (s & 4) ? 0x42C00000u : 0x42000000u;
    asm volatile("" : "+r"(ma), "+r"(a16), "+r"(a8));
    mbar_wait(sb + O_BAR + 8 * B_RFULL, s & 1);
    uint4 ra = lds128u(a16), rb = lds128u(a16 + 128);
    uint2 rc = lds64u(a8);
    uint32_t n = 0;
    while (true) {
        stsm4t(ma, ra.x, ra.y, ra.z, __byte_perm(ra.w, rc.x, 0x5410));
        stsm4t(ma + 2048, rb.x, rb.y, rb.z, __byte_perm(rb.w, rc.x, 0x7610));
        if (__builtin_expect(!__any_sync(~0u, orx(orx2(ra.w, rb.w, target), rc.y, target) > 0xffffu), 1)) break;
        const unsigned char* pg = redp + (s & 3) * 32768 + kh * 16384;
        ra = ldg_rlx128(pg + o16); rb = ldg_rlx128(pg + o16 + 128); rc = ldg_rlx64(pg + o8);
        if (++n > SPIN_LIMIT) __trap();
    }
    __syncwarp();
    if (lane == 0) mbar_arrive(sb + O_BAR + 8 * B_MEM);
    fence_async_smem();
    __syncwarp();
    if (lane == 0) mbar_arrive(sb + O_BAR + 8 * B_QKW);
    return n;
}

#define F16(d, o) F4(d, o), F4(d, o + 4), F4(d, o + 8), F4(d, o + 12)
__device__ __forceinline__ void wg_ss128(float (&d)[64], uint64_t da, uint64_t db, int sc) {
    asm volatile("{\n.reg .pred p;\nsetp.ne.b32 p, %66, 0;\nwgmma.mma_async.sync.aligned.m64n128k16.f32.bf16.bf16 "
                 "{%0,%1,%2,%3,%4,%5,%6,%7,%8,%9,%10,%11,%12,%13,%14,%15,%16,%17,%18,%19,%20,%21,%22,%23,%24,%25,%26,%27,%28,%29,%30,%31,"
                 "%32,%33,%34,%35,%36,%37,%38,%39,%40,%41,%42,%43,%44,%45,%46,%47,%48,%49,%50,%51,%52,%53,%54,%55,%56,%57,%58,%59,%60,%61,%62,%63}, "
                 "%64, %65, p, 1, 1, 0, 1;\n}"
                 : F16(d, 0), F16(d, 16), F16(d, 32), F16(d, 48) : "l"(da), "l"(db), "r"(sc));
}

__global__ void __cluster_dims__(2, 1, 1) __launch_bounds__(512, 1)
rmt_main(const __grid_constant__ CUtensorMap tm_x, const __grid_constant__ CUtensorMap tm_wq, const __grid_constant__ CUtensorMap tm_wk,
         const __grid_constant__ CUtensorMap tm_wv, const __grid_constant__ CUtensorMap tm_wo, const bf16* __restrict__ mem0, const Tune tn,
         const __grid_constant__ FftMaps fm, const __grid_constant__ CUtensorMap tm_o, const __grid_constant__ CUtensorMap tm_w2, bf16* __restrict__ out) {
    extern __shared__ __align__(1024) unsigned char smem_raw[];
    const uint32_t sb = smem_u32(smem_raw);
    if ((sb & 0x3FFFF) != SM_BASE) __trap();
    const int cid = blockIdx.x >> 1, kh = blockIdx.x & 1;
    const int tpc = cid < 4 ? 62 + cid : cid - 4;
    int h, nh;
    if (tpc < 32) { h = (tpc >> 4) * 8 + (tpc & 7); nh = (tpc >> 3) & 1; }
    else if (tpc < 60) { int u = tpc - 32, r = u % 14; h = 16 + (u / 14) * 7 + r % 7; nh = r / 7; }
    else if (tpc < 62) { GT(0); fft_rest((tpc - 60) * 2 + kh, fm, sb); GT(3); return; }
    else { h = 30 + ((tpc - 62) >> 1); nh = tpc & 1; }
    const int j = nh * 2 + kh, role = h * 4 + j;
    const int wgi = __shfl_sync(~0u, threadIdx.x >> 7, 0);
    const int w = __shfl_sync(~0u, (threadIdx.x >> 5) & 3, 0);
    const int tid = threadIdx.x & 127, lane = tid & 31;
#define OPAQUE_IDS() int tid_ = tid; asm volatile("" : "+r"(tid_)); const int tid = tid_, lane = tid_ & 31; (void)lane
    unsigned char* const redp = (unsigned char*)(((uintptr_t)g_red + 32767) & ~(uintptr_t)32767);
    const uint32_t bars = sb + O_BAR;

    if (threadIdx.x == 0) {
        const uint8_t cnts[B_COUNT] = {1, 1, 1, 1, 1, 1, 4, 4, 1, 12, 8, 1, 1, 1, 1, 1, 1, 1, 1, 1, 16, 4, 4, 4, 1, 1, 1, 1, 1, 1, 1, 8, 8, 8, 8, 8, 8};
#pragma unroll
        for (int i = 0; i < B_COUNT; i++) mbar_init(bars + 8 * i, cnts[i]);
        asm volatile("fence.mbarrier_init.release.cluster;" ::: "memory");
        fence_async_smem();
        mbar_expect_tx(bars + 8 * B_F1, 32768);
        tma_ld4(sb + O_F1, &fm.x, (role & 15) * 64, role >> 4, bars + 8 * B_F1);
        const int c0 = h * 128 + nh * 64, r0 = kh * 512;
        for (int i = 0; i < 2; i++) {
            mbar_expect_tx(bars + 8 * (B_WK0 + i), 32768);
            tma2d(sb + O_XB + i * 32768, &tm_wk, c0, r0 + i * 256, bars + 8 * (B_WK0 + i));
            mbar_expect_tx(bars + 8 * (B_WQ0 + i), 32768);
            tma2d(sb + O_WO + i * 32768, &tm_wq, c0, r0 + i * 256, bars + 8 * (B_WQ0 + i));
        }
        mbar_expect_tx(bars + 8 * B_WV, 65536);
        for (int i = 0; i < 2; i++) tma2d(sb + O_WV + i * 32768, &tm_wv, c0, r0 + i * 256, bars + 8 * B_WV);
        for (int i = 0; i < 4; i++) tma2d_prefetch(&tm_wo, j * 256 + i * 64, h * 128);
        tma4d_prefetch(&tm_x, kh * 8, (role >> 1) * 4);
    }
    __syncthreads();
    uint32_t mate;
    asm volatile("mapa.shared::cluster.u32 %0, %1, %2;" : "=r"(mate) : "r"(sb), "r"(kh ^ 1));

    if (wgi >= 2) {
        fft_col<false, 1>(role >> 4, role & 15, &fm.x, &fm.y, sb + O_F1, bars + 8 * B_F1, (wgi - 2) * 4 + w, lane, 6);
        bar_sync(6, 256);
    }

    if (wgi < 2) {
        asm volatile("setmaxnreg.inc.sync.aligned.u32 176;");
        uint32_t a[32][4];
        {
            const uint32_t stage = sb + (wgi == 0 ? O_WO : O_XB);
            const uint32_t ad = stage + (((lane >> 4) & 1) * 8 + (lane & 7)) * 128 + (((2 * w + ((lane >> 3) & 1)) ^ (lane & 7)) << 4);
#pragma unroll
            for (int i = 0; i < 2; i++) {
                mbar_wait(bars + 8 * (B_WQ0 + 2 * wgi + i), 0);
#pragma unroll
                for (int ks = 0; ks < 16; ks++) ldsm4t(a[i * 16 + ks], ad + (i * 16 + ks) * 2048);
            }
            __syncwarp();
            if (lane == 0) mbar_arrive(bars + 8 * (B_QDONE + wgi));
        }
        asm volatile("barrier.cluster.arrive.release.aligned;" ::: "memory");
        asm volatile("barrier.cluster.wait.acquire.aligned;" ::: "memory");
        uint32_t kp[4], sf = 0;
#define X_PASS(d)                                                                                          \
        wg_fence();                                                                                        \
        _Pragma("unroll") for (int ks = 0; ks < 32; ks++) { if (ks == 0) wg_rs32<0>(d, a[ks], xdesc(ks)); else wg_rs32<1>(d, a[ks], xdesc(ks)); } \
        wg_commit();                                                                                       \
        wg_wait<0>();
#define QK_LOOP(R)                                                                                         \
        _Pragma("unroll 1") for (int sg = 0; sg < RA; sg++) {                                              \
            float d[16]; uint32_t sn[4];                                                                   \
            if (sg > 0) { x_wait(R, sg - 1, sb); x_finish<R>(kp, sg - 1, h, nh * 4 + w, kh, tid, sb); }    \
            mbar_wait(bars + 8 * B_XFULL, sg & 1);                                                         \
            X_PASS(d);                                                                                     \
            x_split(d, sn, kp, kh);                                                                        \
            x_send(R, sn, sg, tid, sb, mate);                                                              \
            if (lane == 0) mbar_arrive(bars + 8 * B_XEMPTY);                                               \
        }                                                                                                  \
        _Pragma("unroll 1") for (int s = 0; s < 64; s++) {                                                 \
            TSI(s);                                                                                        \
            {                                                                                              \
                float d[16]; uint32_t sn[4], kc[4];                                                        \
                x_wait(R, s + RA - 1, sb);                                                                 \
                mbar_wait(bars + 8 * B_XFULL, (s + RA) & 1);                                               \
                mbar_wait(bars + 8 * B_OPDONE, s & 1);                                                     \
                if (R == 1) { x_finish<R>(kp, s + RA - 1, h, nh * 4 + w, kh, tid, sb); TS(5); }            \
                TS(6);                                                                                     \
                X_PASS(d);                                                                                 \
                TS(7);                                                                                     \
                x_split(d, sn, kc, kh);                                                                    \
                x_send(R, sn, s + RA, tid, sb, mate);                                                      \
                if (lane == 0) mbar_arrive(bars + 8 * B_XEMPTY);                                           \
                TS(4);                                                                                     \
                if (R == 0) { x_finish<R>(kp, s + RA - 1, h, nh * 4 + w, kh, tid, sb); TS(5); }            \
                _Pragma("unroll") for (int i = 0; i < 4; i++) kp[i] = kc[i];                               \
            }                                                                                              \
            uint2* ap = &g_alpha[((s & 1) * 32 + h) * (3 * 512) + R * 512 + ((nh * 4 + w) * 2 + kh) * 32 + lane]; \
            uint32_t mb0 = sb + O_MEM + (lane & 7) * 128 + (((lane >> 3) ^ (lane & 7)) << 4), mb1 = mb0 ^ 64; \
            asm volatile("mov.b32 %0, %0;\nmov.b32 %1, %1;" : "+r"(mb0), "+r"(mb1), "+l"(ap));            \
            float e[2][4];                                                                                 \
            _Pragma("unroll") for (int i = 0; i < 4; i++) e[0][i] = e[1][i] = 0.f;                         \
            mbar_wait(bars + 8 * B_MEM, s & 1);                                                            \
            TS(0);                                                                                         \
            _Pragma("unroll") for (int ks = 0; ks < 32; ks += 2) {                                         \
                uint32_t b[4];                                                                             \
                ldsm4(b, ((ks & 2) ? mb1 : mb0) + (ks >> 2) * 1024);                                       \
                mma16816(e[0], a[ks][0], a[ks][1], a[ks][2], a[ks][3], b[0], b[1]);                        \
                mma16816(e[1], a[ks + 1][0], a[ks + 1][1], a[ks + 1][2], a[ks + 1][3], b[2], b[3]);        \
            }                                                                                              \
            TS(2);                                                                                         \
            if (lane < 8) asm volatile("st.relaxed.gpu.global.u32 [%0], %1;" ::"l"((uint32_t*)g_qst + role * 8 + lane), "r"(gtime()) : "memory"); \
            uint32_t u0 = pack_bf16(e[0][0] + e[1][0], e[0][1] + e[1][1]), u1 = pack_bf16(e[0][2] + e[1][2], e[0][3] + e[1][3]); \
            u0 = movm(u0); u1 = movm(u1);                                                                  \
            if (QKW_EARLY) { SCHED_FENCE(); if (lane == 0) mbar_arrive(bars + 8 * B_QKW); }                \
            stg_rlx64(ap, (u0 & ~1u) | (((s >> 1) & 1) ^ 1), u1);                                          \
            if (!QKW_EARLY && lane == 0) mbar_arrive(bars + 8 * B_QKW);                                    \
            TS(3);                                                                                         \
        }                                                                                                  \
        x_wait(R, 63 + RA, sb);
        if (wgi == 0) { QK_LOOP(0); } else { QK_LOOP(1); }
        if (QKW_EARLY) sts32(bars + 508, sf);
        TSDUMP();
        asm volatile("bar.arrive 7, 512;" ::: "memory");
        float d[64];
        int st = 0, ph = 0;
#pragma unroll 1
        for (int kt = 0; kt < 64; kt++) {
            mbar_wait(bars + 8 * (B_GF + st), ph);
            if (kt == 0) GT(4);
            const uint64_t da = mkdesc(SM_BASE + st * 32768 + wgi * 8192, 16, 1024, 1), db = mkdesc(SM_BASE + st * 32768 + 16384, 8192, 1024, 1);
            wg_fence();
#pragma unroll
            for (int k = 0; k < 4; k++) wg_ss128(d, da + k * 2, db + k * 128, kt | k);
            wg_commit();
            if (kt > 0) {
                wg_wait<1>();
                if (lane == 0) mbar_arrive(bars + 8 * (B_GE + (st == 0 ? G_ST - 1 : st - 1)));
            }
            if (++st == G_ST) { st = 0; ph ^= 1; }
        }
        wg_wait<0>();
        bf16* op = out + (size_t)((role >> 3) * 128 + wgi * 64 + w * 16 + (lane >> 2)) * 2048 + 1024 + (role & 7) * 128 + (lane & 3) * 2;
#pragma unroll
        for (int i = 0; i < 16; i++) {
            *(uint32_t*)(op + i * 8) = pack_bf16(d[4 * i], d[4 * i + 1]);
            *(uint32_t*)(op + 8 * 2048 + i * 8) = pack_bf16(d[4 * i + 2], d[4 * i + 3]);
        }
        GT(5);
    } else if (wgi == 2) {
        asm volatile("setmaxnreg.dec.sync.aligned.u32 64;");
        asm volatile("barrier.cluster.arrive.release.aligned;" ::: "memory");
        if (w == 0) {
            mbar_wait(bars + 8 * B_KDONE, 0);
            if (lane == 0) {
                mbar_expect_tx(bars + 8 * B_XFULL, 32768);
                tma4d(sb + O_XB, &tm_x, kh * 8, 0, bars + 8 * B_XFULL);
            }
            mbar_wait(bars + 8 * B_QDONE, 0);
            if (lane == 0) {
                mbar_expect_tx(bars + 8 * B_WO, 65536);
#pragma unroll
                for (int i = 0; i < 4; i++) tma2d(sb + O_WO + i * 16384, &tm_wo, j * 256 + i * 64, h * 128, bars + 8 * B_WO);
            }
        }
        asm volatile("barrier.cluster.wait.acquire.aligned;" ::: "memory");
        mbar_wait(bars + 8 * B_WV, 0);
        sts128u(sb + O_VM + tid * 16, make_uint4(0, 0, 0, 0));
        uint32_t tref = gtime() - 4000;
#define V_PASS(d)                                                                                          \
        wg_fence();                                                                                        \
        _Pragma("unroll") for (int ks = 0; ks < 32; ks++) {                                                \
            constexpr uint64_t da0 = mkdesc(SM_BASE + O_WV, 16, 1024, 1);                                  \
            if (ks == 0) wg_ss40<0>(d, da0 + ks * 128, xdesc(ks)); else wg_ss40<1>(d, da0 + ks * 128, xdesc(ks)); \
        }                                                                                                  \
        wg_commit();                                                                                       \
        wg_wait<0>();
#define X_REFILL(sg)                                                                                       \
        if (lane == 0) {                                                                                   \
            mbar_expect_tx(bars + 8 * B_XFULL, 32768);                                                     \
            tma4d(sb + O_XB, &tm_x, kh * 8, (sg) * 4, bars + 8 * B_XFULL);       \
        }
#pragma unroll 1
        for (int sg = 0; sg < RA; sg++) {
            float d[20]; uint32_t sn[4], kp[4];
            mbar_wait(bars + 8 * B_XFULL, sg & 1);
            V_PASS(d);
            if (lane == 0) mbar_arrive(bars + 8 * B_XEMPTY);
            if (w == 0) { mbar_wait(bars + 8 * B_XEMPTY, sg & 1); X_REFILL(sg + 1); }
            x_split(d, sn, kp, kh);
            x_send(2, sn, sg, tid, sb, mate);
            x_wait(2, sg, sb);
            x_finish<2>(kp, sg, h, nh * 4 + w, kh, tid, sb);
        }
#pragma unroll 1
        for (int s = 0; s < 64; s++) {
            TSI(s);
            OPAQUE_IDS();
            uint2* ap = &g_alpha[((s & 1) * 32 + h) * (3 * 512) + 1024 + ((nh * 4 + w) * 2 + kh) * 32 + lane];
            asm volatile("" : "+l"(ap));
            float d[20];
            mbar_wait(bars + 8 * B_QKW, s & 1);
            TS(0);
            V_PASS(d);
            TS(1);
            stg_rlx64(ap, (pack_bf16(d[16], d[17]) & ~1u) | (((s >> 1) & 1) ^ 1), pack_bf16(d[18], d[19]));
            const uint32_t tv = gtime();
            if (tid == 0) asm volatile("st.relaxed.gpu.global.u32 [%0], %1;" ::"l"((uint32_t*)g_stamp + role), "r"(tv) : "memory");
            if (lane == 0) mbar_arrive(bars + 8 * B_XEMPTY);
            uint32_t sn[4], kp[4];
            x_split(d, sn, kp, kh);
            {
                const uint2* vp = &g_alpha[((s & 1) * 32 + h) * (3 * 512) + 1024 + w * 128 + lane];
                const uint32_t tag = ((s >> 1) & 1) ^ 1;
                mbar_wait(bars + 8 * B_AFULL, s & 1);
                int dt;
                asm volatile("ld.shared.u32 %0, [%1];" : "=r"(dt) : "r"(sb + O_QST + lane * 4) : "memory");
                dt = min(__reduce_max_sync(~0u, dt - (int)tv), 0);
                asm volatile("" : "+l"(vp));
                wait_gtime(tv + dt + tn.d_v);
                uint32_t n = 0, bad;
                do {
                    uint2 va[4];
#pragma unroll
                    for (int i = 0; i < 4; i++) va[i] = ldg_rlx64(vp + i * 32);
                    if (++n > SPIN_LIMIT) __trap();
                    bad = (orx2(va[0].x, va[1].x, tag) | orx2(va[2].x, va[3].x, tag)) & 1;
                    sts128u(sb + O_VM + tid * 16, make_uint4((add_bf16x2(va[0].x, va[1].x) & ~1u) | ((~s ^ bad) & 1), add_bf16x2(va[0].y, va[1].y),
                                                             add_bf16x2(va[2].x, va[3].x), add_bf16x2(va[2].y, va[3].y)));
                } while (__any_sync(~0u, bad));
                TS(2);
                TSV(16 + w, n - 1);
            }
            if (s == 63) break;
            if (w == 0) {
                mbar_wait(bars + 8 * B_XEMPTY, (s + RA) & 1);
                X_REFILL(s + RA + 1);
                if (lane == 0 && nh == 0 && ((h ^ s) & 7) == 0 && s < 61 - RA) tma4d_prefetch(&tm_x, kh * 8, (s + RA + 3) * 4);
                mbar_wait(bars + 8 * B_SRDY, s & 1);
                if (lane == 0) {
                    const uint4* hb = &g_kvq[(((s + 1) & 3) * 32 + h) * (3 * 512)];
                    mbar_expect_tx(bars + 8 * B_KVFULL, 18432);
                    bulk_g2s(sb + O_KVQ, hb + 512, 16384, bars + 8 * B_KVFULL);
                    bulk_g2s(sb + O_KVQ + 16384, hb + j * 128, 2048, bars + 8 * B_KVFULL);
                }
            }
            if (w == 3) {
                wait_clk(clk(), tn.d_st);
                uint32_t n = 0, mx, mn;
                do {
                    const uint4 st = ldg_rlx128(&g_stamp[lane]);
                    mx = __reduce_max_sync(~0u, max(max(st.x - tref, st.y - tref), max(st.z - tref, st.w - tref)));
                    mn = __reduce_min_sync(~0u, min(min(st.x - tref, st.y - tref), min(st.z - tref, st.w - tref)));
                } while (mx >= 200000u && ++n < 64);
                tref = mx < 200000u ? tref + mx + (mx - mn > tn.spread ? tn.extra : 1) : gtime();
                TSV(12, clk()); TSV(13, n); TSV(14, mx - mn);
            }
            mbar_wait(bars + 8 * B_OPDONE, (s + 1) & 1);
            x_send(2, sn, s + RA, tid, sb, mate);
            if (w == 3) {
                wait_gtime(tref + tn.d_r0);
                if (lane == 0) {
                    mbar_expect_tx(bars + 8 * B_RFULL, 16384);
                    bulk_g2s(sb + O_STG, redp + (s & 3) * 32768 + kh * 16384, 16384, bars + 8 * B_RFULL);
                }
                TSV(3, clk());
            }
            x_wait(2, s + RA, sb);
            x_finish<2>(kp, s + RA, h, nh * 4 + w, kh, tid, sb);
            TS(6);
            if (DBG_TIMING) { mbar_wait(bars + 8 * B_RFULL, s & 1); TS(4); }
            const uint32_t n = convert_mem(redp, s, kh, 0, w, lane, sb); (void)n;
            TS(5);
            TSV(8 + w, n);
        }
        TSDUMP();
        asm volatile("bar.arrive 7, 512;" ::: "memory");
    } else {
        asm volatile("setmaxnreg.dec.sync.aligned.u32 96;");
        GT(0);
        asm volatile("barrier.cluster.arrive.release.aligned;" ::: "memory");
#define RED_CLEAR(st)                                                                                           \
        if (lane < 16) {                                                                                        \
            const uint32_t cb = ((st) & 4) ? 0x42800000u : 0u;                                                  \
            stg128(redp + ((st) & 3) * 32768 + role * 256 + lane * 16, 0, (role & 2) ? cb : 0u, 0, cb);        \
        }
#define KQ_BAD(tg) __any_sync(~0u, or3(orx2(kf[0].x, kf[1].x, tg), orx2(kf[2].x, kf[3].x, tg), orx2(qf[0].x, qf[1].x, tg)) & 1)
#define KQ_POLL(st)                                                                                             \
        {                                                                                                       \
            const uint4* hb = &g_kvq[(((st) & 3) * 32 + h) * (3 * 512)];                                        \
            uint32_t n_ = 0;                                                                                    \
            do {                                                                                                \
                _Pragma("unroll") for (int i = 0; i < 4; i++) kf[i] = ldg_rlx128(hb + 512 + w * 128 + i * 32 + lane); \
                _Pragma("unroll") for (int u = 0; u < 2; u++) qf[u] = ldg_rlx64((const uint2*)hb + j * 256 + (2 * w + u) * 32 + lane); \
                if (++n_ > SPIN_LIMIT) __trap();                                                                \
            } while (KQ_BAD((((st) >> 2) & 1) ^ 1));                                                \
        }
        uint32_t start_target = 0;
        if (w == 0) {
            RED_CLEAR(0); RED_CLEAR(1); RED_CLEAR(2);
            if (lane == 0) bulk_wait_all();
            __syncwarp();
            start_target = gbar_arrive(&g_start, 1, 256, lane);
        }
        mbar_wait(bars + 8 * B_KDONE, 0);
        {
            const int kb0 = (w & 1) * 4 + (w >> 1) * 2;
#pragma unroll
            for (int q = 0; q < 4; q++) {
                const int row = (lane >> 3) + (q & 1) * 4, ch = lane & 7, kb = kb0 + (q >> 1);
                const uint4 v = *(const uint4*)(mem0 + row * 1024 + kh * 512 + kb * 64 + ch * 8);
                sts128u(sb + O_MEM + kb * 1024 + row * 128 + ((ch ^ row) << 4), v);
            }
            fence_async_smem();
            __syncwarp();
            if (lane < 2) { mbar_arrive(bars + 8 * B_MEM); mbar_arrive(bars + 8 * B_QKW); }
            if (lane == 0) mbar_arrive(bars + 8 * B_OPDONE);
        }
        asm volatile("barrier.cluster.wait.acquire.aligned;" ::: "memory");
        if (w == 0) gbar_wait(&g_start, start_target, 0);
        mbar_wait(bars + 8 * B_WO, 0);
        GT(1);
        uint32_t sf = 0;
        uint4 kf[4]; uint2 qf[2];
        KQ_POLL(0);
#pragma unroll
        for (int i = 0; i < 4; i++) sts128u(sb + O_KVQ + 8192 + w * 2048 + i * 512 + lane * 16, make_uint4(0, 0, 0, 0));
#pragma unroll 1
        for (int s = 0; s < 64; s++) {
            TSI(s);
            OPAQUE_IDS();
            const uint32_t tg = ((s >> 2) & 1) ^ 1;
            const uint32_t tag = ((s >> 1) & 1) ^ 1;
            const uint2* ap = &g_alpha[((s & 1) * 32 + h) * (3 * 512) + w * 128 + lane];
            uint32_t sw = sb + O_S + w * 2560 + lane * 16, sr = sb + O_S + tid * 4;
            uint32_t pw = sb + O_P + ((lane >> 1) & 1) * 704 + (2 * w + (lane >> 4)) * 16 + ((lane >> 2) & 3) * 4 + (lane & 1) * 2;
            int lim = (lane & 2) ? 8 * j + 2 * w + (lane >> 4) - 2 * ((lane >> 2) & 3) - (lane & 1) : 64;
            uint32_t pr = sb + O_P + lane * 16, oa = sb + O_O + w * 512 + lane * 4;
            uint32_t aa = sb + O_STG + w * 1024 + lane * 8, vv = sb + O_KVQ + 8192 + w * 2048 + lane * 16;
            unsigned char* pa = redp + (s & 3) * 32768 + red_grp(j * 16 + (tid >> 3));
            unsigned char* pb = pa + 512 + ((lane >> 3) & 1) * 64 + (lane & 7) * 8;
            pa += (lane & 7) * 16;
            asm volatile("" : "+r"(sw), "+r"(sr), "+r"(pw), "+r"(lim), "+r"(pr), "+r"(oa), "+r"(aa), "+r"(vv), "+l"(ap), "+l"(pa), "+l"(pb));
            TS(0);
            mbar_wait(bars + 8 * B_QKW, s & 1);
            TS(1);
            if (w == 0) {
                wait_clk(clk(), tn.d_alpha);
                if (lane == 0) {
                    mbar_expect_tx(bars + 8 * B_AFULL, 8192 + 128);
                    bulk_g2s(sb + O_STG, ap, 8192, bars + 8 * B_AFULL);
                    bulk_g2s(sb + O_QST, &g_qst[h * 8], 128, bars + 8 * B_AFULL);
                }
            }
            mbar_wait(bars + 8 * B_AFULL, s & 1);
            TS(12);
            uint4 vf[4];
            {
                uint2 qa[4], ka[4];
#pragma unroll
                for (int i = 0; i < 4; i++) { qa[i] = lds64u(aa + i * 256); ka[i] = lds64u(aa + 4096 + i * 256); }
#define QK_BAD() __any_sync(~0u, or3(orx2(qa[0].x, ka[0].x, tag), orx2(qa[1].x, ka[1].x, tag), orx(orx(orx2(qa[2].x, ka[2].x, tag), qa[3].x, tag), ka[3].x, tag)) & 1)
#define SCORES()                                                                                                                  \
                {                                                                                                                 \
                    float sa[5][4];                                                                                               \
                    _Pragma("unroll") for (int n = 0; n < 5; n++) sa[n][0] = sa[n][1] = sa[n][2] = sa[n][3] = 0.f;                \
                    _Pragma("unroll") for (int u = 0; u < 2; u++) {                                                               \
                        const uint32_t q0 = add_bf16x2(qa[2 * u].x, qa[2 * u + 1].x), q1 = add_bf16x2(qa[2 * u].y, qa[2 * u + 1].y); \
                        const uint32_t k0 = add_bf16x2(ka[2 * u].x, ka[2 * u + 1].x), k1 = add_bf16x2(ka[2 * u].y, ka[2 * u + 1].y); \
                        mma16816(sa[1], q0, qf[u].x, q1, qf[u].y, kf[2 * u].x, kf[2 * u].y);                                      \
                        mma16816(sa[2], q0, qf[u].x, q1, qf[u].y, kf[2 * u].z, kf[2 * u].w);                                      \
                        mma16816(sa[3], q0, qf[u].x, q1, qf[u].y, kf[2 * u + 1].x, kf[2 * u + 1].y);                              \
                        mma16816(sa[4], q0, qf[u].x, q1, qf[u].y, kf[2 * u + 1].z, kf[2 * u + 1].w);                              \
                        mma16816(sa[0], q0, qf[u].x, q1, qf[u].y, k0, k1);                                                        \
                        if (u == 0) SCHED_FENCE();                                                                                \
                    }                                                                                                             \
                    _Pragma("unroll") for (int n = 1; n <= 5; n++) sts128(sw + (n % 5) * 512, sa[n % 5][0], sa[n % 5][1], sa[n % 5][2], sa[n % 5][3]); \
                }
                SCORES();
                uint32_t nr = 0;
                if (__builtin_expect(QK_BAD(), 0)) {
                    do {
#pragma unroll
                        for (int i = 0; i < 4; i++) { qa[i] = ldg_rlx64(ap + i * 32); ka[i] = ldg_rlx64(ap + 512 + i * 32); }
                        if (++nr > SPIN_LIMIT) __trap();
                    } while (QK_BAD());
                    SCORES();
                }
                if (w == 0) TSV(20, nr);
            }
            TS(2);
            bar_sync(1, 128);
            float sc[5];
            {
                float x[4][5];
#pragma unroll
                for (int q = 0; q < 4; q++)
#pragma unroll
                    for (int n = 0; n < 5; n++) asm volatile("ld.shared.f32 %0, [%1];" : "=f"(x[q][n]) : "r"(sr + q * 2560 + n * 512) : "memory");
#pragma unroll
                for (int n = 0; n < 5; n++) sc[n] = (x[0][n] + x[1][n]) + (x[2][n] + x[3][n]);
            }
            TS(15);
#pragma unroll
            for (int n = 1; n < 5; n++) if (8 * (n - 1) > lim) sc[n] = MASK_VAL;
            float m = fmaxf(fmaxf(fmaxf(sc[0], sc[1]), fmaxf(sc[2], sc[3])), sc[4]);
            m = fmaxf(m, __shfl_xor_sync(~0u, m, 1));
            m = fmaxf(m, __shfl_xor_sync(~0u, m, 4));
            m = fmaxf(m, __shfl_xor_sync(~0u, m, 8));
            m *= -SM_SCALE_LOG2;
            SCHED_FENCE();
#pragma unroll
            for (int i = 0; i < 4; i++) vf[i] = lds128u(vv + i * 512);
#pragma unroll
            for (int n = 0; n < 5; n++) {
                const uint32_t pv = pack_bf16(ex2(fmaf(sc[n], SM_SCALE_LOG2, m)), 0.f);
                asm volatile("st.shared.u16 [%0], %1;" ::"r"(pw + n * 128), "h"((uint16_t)pv) : "memory");
            }
            bar_sync(1, 128);
            TS(3);
            uint32_t pf[4], p0, px[4], px0;
            ldsm4(pf, pr + 128);
            asm volatile("ld.shared.u32 %0, [%1];" : "=r"(p0) : "r"(oa - w * 512 + (O_P - O_O)) : "memory");
            ldsm4(px, pr + 128 + 704);
            asm volatile("ld.shared.u32 %0, [%1];" : "=r"(px0) : "r"(oa - w * 512 + (O_P - O_O) + 704) : "memory");
            if (lane == 0) mbar_arrive(bars + 8 * B_SRDY);
            uint4 vm = lds128u(sb + O_VM + tid * 16);
            if (__builtin_expect(__any_sync(~0u, orx(orx(orx2(vf[0].x, vf[1].x, tg), vf[2].x, tg), vf[3].x, tg) & 1), 0)) {
                const uint4* vp = &g_kvq[((s & 3) * 32 + h) * (3 * 512) + 1024 + w * 128 + lane];
                uint32_t nr = 0;
                do {
#pragma unroll
                    for (int i = 0; i < 4; i++) vf[i] = ldg_rlx128(vp + i * 32);
                    if (++nr > SPIN_LIMIT) __trap();
                } while (__any_sync(~0u, orx(orx(orx2(vf[0].x, vf[1].x, tg), vf[2].x, tg), vf[3].x, tg) & 1));
            }
            float o[2][4], ox[2][4], sm[4], sx[4];
#pragma unroll
            for (int i = 0; i < 4; i++) o[0][i] = o[1][i] = ox[0][i] = ox[1][i] = sm[i] = sx[i] = 0.f;
            constexpr uint32_t ONE2 = 0x3f803f80u;
#pragma unroll
            for (int c = 0; c < 2; c++) {
#pragma unroll
                for (int u = 0; u < 2; u++) mma16816(o[u], vf[2 * u + c].x, vf[2 * u + c].y, vf[2 * u + c].z, vf[2 * u + c].w, pf[2 * c], pf[2 * c + 1]);
#pragma unroll
                for (int u = 0; u < 2; u++) mma16816(ox[u], vf[2 * u + c].x, vf[2 * u + c].y, vf[2 * u + c].z, vf[2 * u + c].w, px[2 * c], px[2 * c + 1]);
            }
            {
                uint32_t nr = 0;
                while (__any_sync(~0u, (vm.x ^ ~s) & 1)) { vm = lds128u(sb + O_VM + tid * 16); if (++nr > SPIN_LIMIT) __trap(); }
                if (w == 0) TSV(21, nr);
            }
            mma1688(o[0], vm.x, vm.y, p0);
            mma1688(o[1], vm.z, vm.w, p0);
            mma1688(sm, ONE2, ONE2, p0);
            mma1688(sx, ONE2, ONE2, px0);
            SCHED_FENCE();
            sts32(oa, pack_bf16(o[0][0], o[0][1]));
            sts32(oa + 128, pack_bf16(o[0][2], o[0][3]));
            sts32(oa + 256, pack_bf16(o[1][0], o[1][1]));
            sts32(oa + 384, pack_bf16(o[1][2], o[1][3]));
            mma1688(ox[0], vm.x, vm.y, px0);
            mma1688(ox[1], vm.z, vm.w, px0);
#pragma unroll
            for (int c = 0; c < 2; c++) {
                mma16816(sm, ONE2, ONE2, ONE2, ONE2, pf[2 * c], pf[2 * c + 1]);
                mma16816(sx, ONE2, ONE2, ONE2, ONE2, px[2 * c], px[2 * c + 1]);
            }
            SCHED_FENCE();
            TS(4);
            fence_async_smem();
            bar_sync(1, 128);
            if (s == 0) GT(2);
            TS(5);
            if (s < 63) {
            float cc[4][4];
            wg_fence();
#pragma unroll
            for (int ks = 0; ks < 8; ks++)
#pragma unroll
                for (int t = 0; t < 4; t++) {
                    constexpr uint64_t da0 = mkdesc(SM_BASE + O_WO, 16, 1024, 1), db0 = mkdesc(SM_BASE + O_O, 128, 128, 0);
                    if (ks == 0) wg_ss8<0>(cc[t], da0 + t * 1024, db0); else wg_ss8<1>(cc[t], da0 + t * 1024 + ks * 128, db0 + ks * 16);
                }
            wg_commit();
            const float i0 = rcp(sm[0]), i1 = rcp(sm[1]);
            wg_wait<0>();
            TS(6);
#pragma unroll
            for (int hf = 0; hf < 2; hf++)
                asm volatile("red.relaxed.gpu.global.add.noftz.v4.bf16x2 [%0], {%1,%2,%3,%4};" ::"l"(pa + hf * 128),
                             "r"(pack_bf16(cc[2 * hf][0] * i0, cc[2 * hf][1] * i1)), "r"(pack_bf16(cc[2 * hf][2] * i0, cc[2 * hf][3] * i1)),
                             "r"(pack_bf16(cc[2 * hf + 1][0] * i0, cc[2 * hf + 1][1] * i1)), "r"(pack_bf16(cc[2 * hf + 1][2] * i0, 1.f)) : "memory");
            asm volatile("red.relaxed.gpu.global.add.noftz.v2.bf16x2 [%0], {%1,%2};" ::"l"(pb), "r"(pack_bf16(cc[1][3] * i1, cc[3][3] * i1)), "r"(0x3f800000u) : "memory");
            SCHED_FENCE();
            TS(7);
            if (lane == 0) mbar_arrive(bars + 8 * B_OPDONE);
            }
            if (!FLAG(3)) {
                const float ix0 = rcp(sx[0]), ix1 = rcp(sx[1]);
                const uint32_t xo = sb + O_XO + w * 512;
                stsm4t(xo + (lane & 7) * 64 + (((lane >> 3) ^ ((lane >> 1) & 3)) << 4), pack_bf16(ox[0][0] * ix0, ox[0][1] * ix1),
                       pack_bf16(ox[0][2] * ix0, ox[0][3] * ix1), pack_bf16(ox[1][0] * ix0, ox[1][1] * ix1), pack_bf16(ox[1][2] * ix0, ox[1][3] * ix1));
                __syncwarp();
                const uint4 ov = lds128u(xo + (lane >> 2) * 64 + (((lane & 3) ^ ((lane >> 3) & 3)) << 4));
                stg128(&g_ox[(size_t)(s * 32 + j * 8 + (lane >> 2)) * 4096 + h * 128 + w * 32 + (lane & 3) * 8], ov.x, ov.y, ov.z, ov.w);
            }
            TS(8);
            if (s == 63) { GT(3); break; }
            mbar_wait(bars + 8 * B_KVFULL, s & 1);
#pragma unroll
            for (int i = 0; i < 4; i++) kf[i] = lds128u(vv - 8192 + i * 512);
#pragma unroll
            for (int u = 0; u < 2; u++) qf[u] = lds64u(sb + O_KVQ + 16384 + (2 * w + u) * 256 + lane * 8);
            if (__builtin_expect(KQ_BAD((((s + 1) >> 2) & 1) ^ 1), 0)) { KQ_POLL(s + 1); if (w == 0) TSV(22, 1); }
            TS(9);
            {
                const uint32_t n = convert_mem(redp, s, kh, 1, w, lane, sb); (void)n;
                TS(11);
                TSV(16 + w, n);
            }
            if (w == 0 && s < 61) RED_CLEAR(s + 3);
        }
        sts32(bars + 508, sf);
        TSDUMP();
        bar_sync(7, 512);
        if (w == 0) {
            const int m0 = (role >> 3) * 128, n0 = (role & 7) * 128;
            if (lane == 0) {
                fence_async_smem();
#pragma unroll 1
                for (int kt = 0; kt < G_ST; kt++) {
                    mbar_expect_tx(bars + 8 * (B_GF + kt), 32768);
                    tma2d(sb + kt * 32768 + 16384, &tm_w2, n0, kt * 64, bars + 8 * (B_GF + kt));
                    tma2d(sb + kt * 32768 + 24576, &tm_w2, n0 + 64, kt * 64, bars + 8 * (B_GF + kt));
                }
            }
            gbar_wait(&g_end, gbar_arrive(&g_end, 1, 128, lane), 0);
            int st = 0, ph = 1;
#pragma unroll 1
            for (int kt = 0; kt < 64; kt++) {
                if (kt >= G_ST) mbar_wait(bars + 8 * (B_GE + st), ph);
                if (lane == 0) {
                    if (kt >= G_ST) {
                        mbar_expect_tx(bars + 8 * (B_GF + st), 32768);
                        tma2d(sb + st * 32768 + 16384, &tm_w2, n0, kt * 64, bars + 8 * (B_GF + st));
                        tma2d(sb + st * 32768 + 24576, &tm_w2, n0 + 64, kt * 64, bars + 8 * (B_GF + st));
                    }
                    tma2d(sb + st * 32768, &tm_o, kt * 64, m0, bars + 8 * (B_GF + st));
                }
                if (++st == G_ST) { st = 0; ph ^= 1; }
            }
        }
    }
}

typedef CUresult (*EncodeFn)(CUtensorMap*, CUtensorMapDataType, cuuint32_t, void*, const cuuint64_t*, const cuuint64_t*,
                             const cuuint32_t*, const cuuint32_t*, CUtensorMapInterleave, CUtensorMapSwizzle,
                             CUtensorMapL2promotion, CUtensorMapFloatOOBfill);

static void make_map(EncodeFn fn, CUtensorMap* m, const void* p, uint64_t cols, uint64_t rows, uint32_t bc, uint32_t br) {
    cuuint64_t dims[2] = {cols, rows}, strides[1] = {cols * 2};
    cuuint32_t box[2] = {bc, br}, es[2] = {1, 1};
    fn(m, CU_TENSOR_MAP_DATA_TYPE_BFLOAT16, 2, (void*)p, dims, strides, box, es, CU_TENSOR_MAP_INTERLEAVE_NONE,
       CU_TENSOR_MAP_SWIZZLE_128B, CU_TENSOR_MAP_L2_PROMOTION_L2_128B, CU_TENSOR_MAP_FLOAT_OOB_FILL_NONE);
}

static Tune h_tune = {300, 1120, 1, 0, 0, 672, 4000, 300};

extern "C" void kernel_launch(void* const* d_in, const int* in_sizes, int n_in, void* d_out, int out_size) {
    static bool init = false;
    static FftMaps fm;
    static CUtensorMap tm_x, tm_wq, tm_wk, tm_wv, tm_wo, tm_o, tm_wo2;
    if (!init) {
        void* fp = nullptr; cudaDriverEntryPointQueryResult qr;
        cudaGetDriverEntryPoint("cuTensorMapEncodeTiled", &fp, cudaEnableDefault, &qr);
        EncodeFn fn = (EncodeFn)fp;
        void* ox = nullptr; cudaGetSymbolAddress(&ox, g_ox);
        {
            cuuint64_t dims[4] = {64, 8, 16, 256}, strides[3] = {2048, 128, 16384};
            cuuint32_t box[4] = {64, 8, 8, 4}, es[4] = {1, 1, 1, 1};
            fn(&tm_x, CU_TENSOR_MAP_DATA_TYPE_BFLOAT16, 4, d_in[3], dims, strides, box, es, CU_TENSOR_MAP_INTERLEAVE_NONE,
               CU_TENSOR_MAP_SWIZZLE_128B, CU_TENSOR_MAP_L2_PROMOTION_L2_128B, CU_TENSOR_MAP_FLOAT_OOB_FILL_NONE);
        }
        void* fy = nullptr; cudaGetSymbolAddress(&fy, g_fy);
        for (int i = 0; i < 3; i++) {
            const cuuint64_t pitch = i == 2 ? 4096 : 2048;
            cuuint64_t dims[4] = {1024, 8, 16, 16}, strides[3] = {pitch, 128 * pitch, 8 * pitch};
            cuuint32_t box[4] = {64, 1, 16, 16}, es[4] = {1, 1, 1, 1};
            fn(i == 0 ? &fm.x : i == 1 ? &fm.y : &fm.o, CU_TENSOR_MAP_DATA_TYPE_BFLOAT16, 4, i == 0 ? d_in[0] : i == 1 ? fy : d_out, dims, strides, box, es,
               CU_TENSOR_MAP_INTERLEAVE_NONE, CU_TENSOR_MAP_SWIZZLE_128B, CU_TENSOR_MAP_L2_PROMOTION_L2_256B, CU_TENSOR_MAP_FLOAT_OOB_FILL_NONE);
        }
        {
            cuuint64_t dims[3] = {64, 2048, 16}, strides[2] = {2048, 128};
            cuuint32_t box[3] = {64, 8, 16}, es[3] = {1, 1, 1};
            fn(&fm.y2, CU_TENSOR_MAP_DATA_TYPE_BFLOAT16, 3, fy, dims, strides, box, es, CU_TENSOR_MAP_INTERLEAVE_NONE,
               CU_TENSOR_MAP_SWIZZLE_128B, CU_TENSOR_MAP_L2_PROMOTION_L2_128B, CU_TENSOR_MAP_FLOAT_OOB_FILL_NONE);
        }
        for (int i = 0; i < 2; i++) {
            cuuint64_t dims[3] = {256 * 513 - 448, 8, 8}, strides[2] = {128, 256 * 1026};
            cuuint32_t box[3] = {72, 8, 8}, es[3] = {1, 1, 1};
            fn(i ? &fm.wi : &fm.wr, CU_TENSOR_MAP_DATA_TYPE_BFLOAT16, 3, d_in[1 + i], dims, strides, box, es, CU_TENSOR_MAP_INTERLEAVE_NONE,
               CU_TENSOR_MAP_SWIZZLE_NONE, CU_TENSOR_MAP_L2_PROMOTION_L2_128B, CU_TENSOR_MAP_FLOAT_OOB_FILL_NONE);
        }
        make_map(fn, &tm_wq, d_in[5], 4096, 1024, 64, 256);
        make_map(fn, &tm_wk, d_in[6], 4096, 1024, 64, 256);
        make_map(fn, &tm_wv, d_in[7], 4096, 1024, 64, 256);
        make_map(fn, &tm_wo, d_in[8], 1024, 4096, 64, 128);
        make_map(fn, &tm_o, ox, 4096, 2048, 64, 128);
        make_map(fn, &tm_wo2, d_in[8], 1024, 4096, 64, 64);
        cudaFuncSetAttribute(rmt_main, cudaFuncAttributeMaxDynamicSharedMemorySize, MAIN_SMEM);
        init = true;
    }
    rmt_main<<<132, 512, MAIN_SMEM>>>(tm_x, tm_wq, tm_wk, tm_wv, tm_wo, (const bf16*)d_in[4], h_tune, fm, tm_o, tm_wo2, (bf16*)d_out);
}
```

```cpp
#include <cuda_runtime.h>
#include <cuda_bf16.h>
#include <cuda.h>
#include <stdint.h>

typedef __nv_bfloat16 bf16;

#define DBG_TIMING 0

#define SPIN_LIMIT (1u << 22)

__device__ __forceinline__ uint32_t smem_u32(const void* p) { return (uint32_t)__cvta_generic_to_shared(p); }
__device__ __forceinline__ uint32_t clk() { uint32_t c; asm volatile("mov.u32 %0, %%clock;" : "=r"(c)::"memory"); return c; }
#define SCHED_FENCE() sf ^= (uint32_t)clock64()
#define KEEP2(a, b) asm volatile("lop3.b32 %0, %0, %1, %2, 0x96;" : "+r"(sf) : "r"((uint32_t)(a)), "r"((uint32_t)(b)))
#define KEEPP(p) KEEP2((uintptr_t)(p), (uintptr_t)(p) >> 32)
__device__ __forceinline__ uint32_t gtime() { uint32_t c; asm volatile("mov.u32 %0, %%globaltimer_lo;" : "=r"(c)::"memory"); return c; }
__device__ __forceinline__ void wait_clk(uint32_t t0, uint32_t d) {
    asm volatile("{\n.reg .pred p;\n.reg .s32 t;\n.reg .b64 c;\nWL:\nmov.u64 c, %%clock64;\ncvt.u32.u64 t, c;\nsub.s32 t, t, %0;\nsetp.lt.s32 p, t, 0;\n@p bra.uni WL;\n}" ::"r"(t0 + d) : "memory");
}
__device__ __forceinline__ void wait_gtime(uint32_t t1) {
    asm volatile("{\n.reg .pred p;\n.reg .s32 t;\n.reg .b64 c;\nWL:\nmov.u64 c, %%globaltimer;\ncvt.u32.u64 t, c;\nsub.s32 t, t, %0;\nsetp.lt.s32 p, t, 0;\n@p bra.uni WL;\n}" ::"r"(t1) : "memory");
}

__device__ __forceinline__ void mbar_init(uint32_t bar, uint32_t cnt) {
    asm volatile("mbarrier.init.shared::cta.b64 [%0], %1;" ::"r"(bar), "r"(cnt) : "memory");
}
__device__ __forceinline__ void mbar_arrive(uint32_t bar) {
    asm volatile("mbarrier.arrive.shared::cta.b64 _, [%0];" ::"r"(bar) : "memory");
}
__device__ __forceinline__ void mbar_expect_tx(uint32_t bar, uint32_t bytes) {
    asm volatile("mbarrier.arrive.expect_tx.shared::cta.b64 _, [%0], %1;" ::"r"(bar), "r"(bytes) : "memory");
}
__device__ __forceinline__ void mbar_wait(uint32_t bar, uint32_t parity) {
    asm volatile(
        "{\n.reg .pred p, q;\n.reg .u32 n;\nmov.u32 n, 0;\n"
        "WL:\nmbarrier.try_wait.parity.shared::cta.b64 p, [%0], %1;\n"
        "add.u32 n, n, 1;\nsetp.gt.u32 q, n, %2;\n@q trap;\n@!p bra.uni WL;\n}" ::"r"(bar), "r"(parity), "n"(SPIN_LIMIT) : "memory");
}
__device__ __forceinline__ void mbar_wait_cluster(uint32_t bar, uint32_t parity) {
    asm volatile(
        "{\n.reg .pred p, q;\n.reg .u32 n;\nmov.u32 n, 0;\n"
        "WL:\nmbarrier.try_wait.parity.acquire.cluster.shared::cta.b64 p, [%0], %1;\n"
        "add.u32 n, n, 1;\nsetp.gt.u32 q, n, %2;\n@q trap;\n@!p bra.uni WL;\n}" ::"r"(bar), "r"(parity), "n"(SPIN_LIMIT) : "memory");
}
__device__ __forceinline__ void tma2d(uint32_t dst, const CUtensorMap* m, int c0, int c1, uint32_t bar) {
    asm volatile("cp.async.bulk.tensor.2d.shared::cluster.global.mbarrier::complete_tx::bytes [%0], [%1, {%3, %4}], [%2];"
                 ::"r"(dst), "l"(m), "r"(bar), "r"(c0), "r"(c1) : "memory");
}
__device__ __forceinline__ void tma3d(uint32_t dst, const CUtensorMap* m, int c0, int c1, int c2, uint32_t bar) {
    asm volatile("cp.async.bulk.tensor.3d.shared::cluster.global.mbarrier::complete_tx::bytes [%0], [%1, {%3, %4, %5}], [%2];"
                 ::"r"(dst), "l"(m), "r"(bar), "r"(c0), "r"(c1), "r"(c2) : "memory");
}
__device__ __forceinline__ void tma4d(uint32_t dst, const CUtensorMap* m, int c2, int c3, uint32_t bar) {
    asm volatile("cp.async.bulk.tensor.4d.shared::cluster.global.mbarrier::complete_tx::bytes [%0], [%1, {%5, %5, %3, %4}], [%2];"
                 ::"r"(dst), "l"(m), "r"(bar), "r"(c2), "r"(c3), "r"(0) : "memory");
}
__device__ __forceinline__ void bulk_g2s(uint32_t dst, const void* src, uint32_t bytes, uint32_t bar) {
    asm volatile("cp.async.bulk.shared::cluster.global.mbarrier::complete_tx::bytes [%0], [%1], %2, [%3];"
                 ::"r"(dst), "l"(src), "r"(bytes), "r"(bar) : "memory");
}
__device__ __forceinline__ void tma4d_prefetch(const CUtensorMap* m, int c2, int c3) {
    asm volatile("cp.async.bulk.prefetch.tensor.4d.L2.global [%0, {%3, %3, %1, %2}];" ::"l"(m), "r"(c2), "r"(c3), "r"(0) : "memory");
}
__device__ __forceinline__ void tma2d_prefetch(const CUtensorMap* m, int c0, int c1) {
    asm volatile("cp.async.bulk.prefetch.tensor.2d.L2.global [%0, {%1, %2}];" ::"l"(m), "r"(c0), "r"(c1) : "memory");
}
__device__ __forceinline__ void fence_async_smem() { asm volatile("fence.proxy.async.shared::cta;" ::: "memory"); }
__device__ __forceinline__ void fence_gpu() { asm volatile("fence.acq_rel.gpu;" ::: "memory"); }
__device__ __forceinline__ float rcp(float x) { float r; asm("rcp.approx.ftz.f32 %0, %1;" : "=f"(r) : "f"(x)); return r; }
__device__ __forceinline__ void bar_sync(int id, int n) { asm volatile("bar.sync %0, %1;" ::"r"(id), "r"(n) : "memory"); }

__device__ __forceinline__ bool bar_or(int id, int n, uint32_t x) {
    uint32_t r;
    asm volatile("{\n.reg .pred p, q;\n.reg .b32 t;\nand.b32 t, %3, 1;\nsetp.ne.u32 p, t, 0;\nbar.red.or.pred q, %1, %2, p;\nselp.u32 %0, 1, 0, q;\n}"
                 : "=r"(r) : "r"(id), "r"(n), "r"(x) : "memory");
    return __any_sync(~0u, r);
}
__device__ __forceinline__ uint32_t or3(uint32_t a, uint32_t b, uint32_t c) {
    uint32_t r; asm("lop3.b32 %0, %1, %2, %3, 0xFE;" : "=r"(r) : "r"(a), "r"(b), "r"(c)); return r;
}
__device__ __forceinline__ uint32_t pack_bf16(float lo, float hi) {
    uint32_t r; asm("cvt.rn.bf16x2.f32 %0, %1, %2;" : "=r"(r) : "f"(hi), "f"(lo)); return r;
}
__device__ __forceinline__ uint32_t add_bf16x2(uint32_t a, uint32_t b) {
    uint32_t r; asm volatile("add.rn.bf16x2 %0, %1, %2;" : "=r"(r) : "r"(a), "r"(b)); return r;
}
__device__ __forceinline__ uint32_t movm(uint32_t a) {
    uint32_t r; asm volatile("movmatrix.sync.aligned.m8n8.trans.b16 %0, %1;" : "=r"(r) : "r"(a)); return r;
}
__device__ __forceinline__ uint32_t orx(uint32_t acc, uint32_t a, uint32_t t) {
    uint32_t r; asm("lop3.b32 %0, %1, %2, %3, 0xF6;" : "=r"(r) : "r"(acc), "r"(a), "r"(t)); return r;
}
__device__ __forceinline__ uint32_t orx2(uint32_t a, uint32_t b, uint32_t t) {
    uint32_t r; asm("lop3.b32 %0, %1, %2, %3, 0x7E;" : "=r"(r) : "r"(a), "r"(b), "r"(t)); return r;
}
__device__ __forceinline__ float ex2(float x) { float r; asm("ex2.approx.ftz.f32 %0, %1;" : "=f"(r) : "f"(x)); return r; }
__device__ __forceinline__ void ldsm4t(uint32_t (&r)[4], uint32_t a) {
    asm volatile("ldmatrix.sync.aligned.m8n8.x4.trans.shared.b16 {%0,%1,%2,%3}, [%4];"
                 : "=r"(r[0]), "=r"(r[1]), "=r"(r[2]), "=r"(r[3]) : "r"(a) : "memory");
}
__device__ __forceinline__ void ldsm4(uint32_t (&r)[4], uint32_t a) {
    asm volatile("ldmatrix.sync.aligned.m8n8.x4.shared.b16 {%0,%1,%2,%3}, [%4];"
                 : "=r"(r[0]), "=r"(r[1]), "=r"(r[2]), "=r"(r[3]) : "r"(a) : "memory");
}
__device__ __forceinline__ void stsm4t(uint32_t a, uint32_t r0, uint32_t r1, uint32_t r2, uint32_t r3) {
    asm volatile("stmatrix.sync.aligned.m8n8.x4.trans.shared.b16 [%0], {%1,%2,%3,%4};"
                 ::"r"(a), "r"(r0), "r"(r1), "r"(r2), "r"(r3) : "memory");
}
__device__ __forceinline__ void stsm4(uint32_t a, uint32_t r0, uint32_t r1, uint32_t r2, uint32_t r3) {
    asm volatile("stmatrix.sync.aligned.m8n8.x4.shared.b16 [%0], {%1,%2,%3,%4};"
                 ::"r"(a), "r"(r0), "r"(r1), "r"(r2), "r"(r3) : "memory");
}
__device__ __forceinline__ void mma16816(float* c, uint32_t a0, uint32_t a1, uint32_t a2, uint32_t a3, uint32_t b0, uint32_t b1) {
    asm volatile("mma.sync.aligned.m16n8k16.row.col.f32.bf16.bf16.f32 {%0,%1,%2,%3}, {%4,%5,%6,%7}, {%8,%9}, {%0,%1,%2,%3};"
                 : "+f"(c[0]), "+f"(c[1]), "+f"(c[2]), "+f"(c[3]) : "r"(a0), "r"(a1), "r"(a2), "r"(a3), "r"(b0), "r"(b1));
}
__device__ __forceinline__ void mma1688(float* c, uint32_t a0, uint32_t a1, uint32_t b0) {
    asm volatile("mma.sync.aligned.m16n8k8.row.col.f32.bf16.bf16.f32 {%0,%1,%2,%3}, {%4,%5}, {%6}, {%0,%1,%2,%3};"
                 : "+f"(c[0]), "+f"(c[1]), "+f"(c[2]), "+f"(c[3]) : "r"(a0), "r"(a1), "r"(b0));
}
__device__ __forceinline__ void sts128(uint32_t a, float x, float y, float z, float w) {
    asm volatile("st.shared.v4.f32 [%0], {%1,%2,%3,%4};" ::"r"(a), "f"(x), "f"(y), "f"(z), "f"(w) : "memory");
}
__device__ __forceinline__ void sts64(uint32_t a, float x, float y) {
    asm volatile("st.shared.v2.f32 [%0], {%1,%2};" ::"r"(a), "f"(x), "f"(y) : "memory");
}
__device__ __forceinline__ void sts32(uint32_t a, uint32_t x) { asm volatile("st.shared.b32 [%0], %1;" ::"r"(a), "r"(x) : "memory"); }
__device__ __forceinline__ void sts128u(uint32_t a, uint4 v) {
    asm volatile("st.shared.v4.b32 [%0], {%1,%2,%3,%4};" ::"r"(a), "r"(v.x), "r"(v.y), "r"(v.z), "r"(v.w) : "memory");
}
__device__ __forceinline__ float4 lds128(uint32_t a) {
    float4 v; asm volatile("ld.shared.v4.f32 {%0,%1,%2,%3}, [%4];" : "=f"(v.x), "=f"(v.y), "=f"(v.z), "=f"(v.w) : "r"(a) : "memory"); return v;
}
__device__ __forceinline__ uint4 lds128u(uint32_t a) {
    uint4 v; asm volatile("ld.shared.v4.b32 {%0,%1,%2,%3}, [%4];" : "=r"(v.x), "=r"(v.y), "=r"(v.z), "=r"(v.w) : "r"(a) : "memory"); return v;
}
__device__ __forceinline__ uint4 lds128v(uint32_t a) {
    uint4 v; asm volatile("ld.volatile.shared.v4.b32 {%0,%1,%2,%3}, [%4];" : "=r"(v.x), "=r"(v.y), "=r"(v.z), "=r"(v.w) : "r"(a) : "memory"); return v;
}
__device__ __forceinline__ void sts64u(uint32_t a, uint2 v) { asm volatile("st.shared.v2.b32 [%0], {%1,%2};" ::"r"(a), "r"(v.x), "r"(v.y) : "memory"); }
__device__ __forceinline__ uint2 lds64u(uint32_t a) {
    uint2 v; asm volatile("ld.shared.v2.b32 {%0,%1}, [%2];" : "=r"(v.x), "=r"(v.y) : "r"(a) : "memory"); return v;
}
__device__ __forceinline__ float2 lds64(uint32_t a) {
    float2 v; asm volatile("ld.shared.v2.f32 {%0,%1}, [%2];" : "=f"(v.x), "=f"(v.y) : "r"(a) : "memory"); return v;
}
__device__ __forceinline__ uint2 ldg_rlx64(const void* p) {
    uint2 v; asm volatile("ld.relaxed.gpu.global.v2.b32 {%0,%1}, [%2];" : "=r"(v.x), "=r"(v.y) : "l"(p) : "memory"); return v;
}
__device__ __forceinline__ uint4 ldg_rlx128(const void* p) {
    uint4 v; asm volatile("ld.relaxed.gpu.global.v4.b32 {%0,%1,%2,%3}, [%4];" : "=r"(v.x), "=r"(v.y), "=r"(v.z), "=r"(v.w) : "l"(p) : "memory"); return v;
}
__device__ __forceinline__ void stg_rlx64(void* p, uint32_t x, uint32_t y) {
    asm volatile("st.relaxed.gpu.global.v2.b32 [%0], {%1,%2};" ::"l"(p), "r"(x), "r"(y) : "memory");
}
__device__ __forceinline__ void stg_rlx128(void* p, uint32_t x, uint32_t y, uint32_t z, uint32_t w) {
    asm volatile("st.relaxed.gpu.global.v4.b32 [%0], {%1,%2,%3,%4};" ::"l"(p), "r"(x), "r"(y), "r"(z), "r"(w) : "memory");
}
__device__ __forceinline__ uint32_t ldg_rlx32(const void* p) {
    uint32_t v; asm volatile("ld.relaxed.gpu.global.b32 %0, [%1];" : "=r"(v) : "l"(p) : "memory"); return v;
}
__device__ __forceinline__ void stg128(void* p, uint32_t x, uint32_t y, uint32_t z, uint32_t w) {
    asm volatile("st.global.v4.b32 [%0], {%1,%2,%3,%4};" ::"l"(p), "r"(x), "r"(y), "r"(z), "r"(w) : "memory");
}
__device__ __forceinline__ uint32_t ld_acquire(const unsigned* p) {
    uint32_t v; asm volatile("ld.acquire.gpu.global.u32 %0, [%1];" : "=r"(v) : "l"(p) : "memory"); return v;
}
__device__ __forceinline__ void red_add_u32(unsigned* p, uint32_t v) {
    asm volatile("red.relaxed.gpu.global.add.u32 [%0], %1;" ::"l"(p), "r"(v) : "memory");
}
__device__ __forceinline__ void wait_counter(const unsigned* p, uint32_t target) {
    uint32_t n = 0;
    while (ld_acquire(p) < target) { if (++n > SPIN_LIMIT) __trap(); }
}

__device__ __forceinline__ void wg_fence() { asm volatile("wgmma.fence.sync.aligned;" ::: "memory"); }
__device__ __forceinline__ void wg_commit() { asm volatile("wgmma.commit_group.sync.aligned;" ::: "memory"); }
template <int N> __device__ __forceinline__ void wg_wait() { asm volatile("wgmma.wait_group.sync.aligned %0;" ::"n"(N) : "memory"); }
__host__ __device__ constexpr uint64_t mkdesc(uint32_t addr, uint32_t lbo, uint32_t sbo, uint32_t swz) {
    return (uint64_t)((addr & 0x3FFFF) >> 4) | ((uint64_t)(lbo >> 4) << 16) | ((uint64_t)(sbo >> 4) << 32) | ((uint64_t)swz << 62);
}
#define F4(d, o) "+f"(d[o]), "+f"(d[o + 1]), "+f"(d[o + 2]), "+f"(d[o + 3])
template <int SC> __device__ __forceinline__ void wg_rs32(float (&d)[16], const uint32_t (&a)[4], uint64_t db) {
    asm volatile("wgmma.mma_async.sync.aligned.m64n32k16.f32.bf16.bf16 "
                 "{%0,%1,%2,%3,%4,%5,%6,%7,%8,%9,%10,%11,%12,%13,%14,%15}, {%16,%17,%18,%19}, %20, %21, 1, 1, 0;"
                 : F4(d, 0), F4(d, 4), F4(d, 8), F4(d, 12)
                 : "r"(a[0]), "r"(a[1]), "r"(a[2]), "r"(a[3]), "l"(db), "n"(SC));
}
template <int SC> __device__ __forceinline__ void wg_rs40(float (&d)[20], const uint32_t (&a)[4], uint64_t db) {
    asm volatile("wgmma.mma_async.sync.aligned.m64n40k16.f32.bf16.bf16 "
                 "{%0,%1,%2,%3,%4,%5,%6,%7,%8,%9,%10,%11,%12,%13,%14,%15,%16,%17,%18,%19}, {%20,%21,%22,%23}, %24, %25, 1, 1, 0;"
                 : F4(d, 0), F4(d, 4), F4(d, 8), F4(d, 12), F4(d, 16)
                 : "r"(a[0]), "r"(a[1]), "r"(a[2]), "r"(a[3]), "l"(db), "n"(SC));
}
template <int SC> __device__ __forceinline__ void wg_ss40(float (&d)[20], uint64_t da, uint64_t db) {
    asm volatile("wgmma.mma_async.sync.aligned.m64n40k16.f32.bf16.bf16 "
                 "{%0,%1,%2,%3,%4,%5,%6,%7,%8,%9,%10,%11,%12,%13,%14,%15,%16,%17,%18,%19}, %20, %21, %22, 1, 1, 1, 0;"
                 : F4(d, 0), F4(d, 4), F4(d, 8), F4(d, 12), F4(d, 16)
                 : "l"(da), "l"(db), "n"(SC));
}
template <int SC> __device__ __forceinline__ void wg_ss8(float (&d)[4], uint64_t da, uint64_t db) {
    asm volatile("wgmma.mma_async.sync.aligned.m64n8k16.f32.bf16.bf16 {%0,%1,%2,%3}, %4, %5, %6, 1, 1, 1, 1;"
                 : F4(d, 0) : "l"(da), "l"(db), "n"(SC));
}

constexpr int DBG_N = 12;
#define TSI(st) do {} while (0)
#define TS(k) do {} while (0)
#define TSV(k, v) do {} while (0)
#define TSDUMP() do {} while (0)
#define GT(k) do {} while (0)

__device__ __align__(256) uint4 g_fy[2048 * 128];

constexpr uint32_t FG_SIZE = 2 * 32768 + 36864;
constexpr uint32_t FT_F16 = 2 * FG_SIZE, FT_B1F = FT_F16 + 2048, FT_B1I = FT_B1F + 2048, FT_C = FT_B1I + 2048, FT_A8 = FT_C + 2048,
                   FT_TWC = FT_A8 + 512, FT_TWB = FT_TWC + 8192, FT_BAR = FT_TWB + 8192, FFT_SMEM = FT_BAR + 256;
struct FftMaps { CUtensorMap x, y, o, y2, wr, wi; };

__device__ __forceinline__ float2 wroot(int e) {
    float s, c; sincospif((float)(e & 2047) * (-1.f / 1024.f), &s, &c); return make_float2(c, s);
}
__device__ __forceinline__ uint4 afrag(float2 a, float2 b) {
    return make_uint4(pack_bf16(a.x, -a.y), pack_bf16(a.y, a.x), pack_bf16(b.x, -b.y), pack_bf16(b.y, b.x));
}
__device__ __forceinline__ uint4 conjfrag(uint4 v) { return make_uint4(v.x ^ 0x80000000u, v.y ^ 0x8000u, v.z ^ 0x80000000u, v.w ^ 0x8000u); }
__device__ __forceinline__ uint4 negfrag(uint4 v) { return make_uint4(v.x ^ 0x80008000u, v.y ^ 0x80008000u, v.z ^ 0x80008000u, v.w ^ 0x80008000u); }
__device__ __forceinline__ uint32_t comp(const uint4& v, int i) { return i == 0 ? v.x : i == 1 ? v.y : i == 2 ? v.z : v.w; }
__device__ __forceinline__ void setcomp(uint4& v, int i, uint32_t x) { if (i == 0) v.x = x; else if (i == 1) v.y = x; else if (i == 2) v.z = x; else v.w = x; }
__device__ __forceinline__ float2 cmul(float2 a, float2 b) { return make_float2(a.x * b.x - a.y * b.y, a.x * b.y + a.y * b.x); }
__device__ __forceinline__ float2 cmulc(float2 a, float2 b) { return make_float2(a.x * b.x + a.y * b.y, a.y * b.x - a.x * b.y); }

__device__ __forceinline__ uint32_t pack_h2(float2 a) { uint32_t r; asm("cvt.rn.f16x2.f32 %0, %1, %2;" : "=r"(r) : "f"(a.y), "f"(a.x)); return r; }
__device__ __forceinline__ float2 unpack_h2(uint32_t v) {
    float2 r; asm("{\n.reg .b16 l, h;\nmov.b32 {l, h}, %2;\ncvt.f32.f16 %0, l;\ncvt.f32.f16 %1, h;\n}" : "=f"(r.x), "=f"(r.y) : "r"(v)); return r;
}
__device__ __forceinline__ void fft_tables(uint32_t tb, int tid, int nthr) {
    for (int i = tid; i < 128; i += nthr) {
        const int lane = i & 31, q = i >> 5, g = lane >> 2, t = lane & 3, o = 8 * (q >> 1) + g, in = 8 * (q & 1) + 2 * t;
        sts128u(tb + FT_F16 + i * 16, afrag(wroot(128 * o * in), wroot(128 * o * (in + 1))));
        sts128u(tb + FT_B1F + i * 16, afrag(wroot(64 * (1 + 2 * o) * in), wroot(64 * (1 + 2 * o) * (in + 1))));
        sts128u(tb + FT_B1I + i * 16, afrag(wroot(-64 * o * (1 + 2 * in)), wroot(-64 * o * (3 + 2 * in))));
        uint4 v;
        for (int r = 0; r < 4; r++) {
            const float2 a = wroot(128 * (4 * r + t) * (4 * q + (g >> 1)));
            setcomp(v, r, (g & 1) ? pack_bf16(a.y, a.x) : pack_bf16(a.x, -a.y));
        }
        sts128u(tb + FT_C + i * 16, v);
        if (q == 0) sts128u(tb + FT_A8 + lane * 16, afrag(wroot(256 * g * 2 * t), wroot(256 * g * (2 * t + 1))));
    }
    for (int i = tid; i < 512; i += nthr) {
        const int lane = i & 31, r = (i >> 5) & 3, phi = 8 * (i >> 7) + (lane >> 2), c = 4 * r + (lane & 3);
        const float2 a = wroot(4 * c * phi), b = wroot(2 * (phi + 32 * c));
        constexpr float SC = 1.f / (2.f * 2048.f * 512.f);
        sts128(tb + FT_TWC + i * 16, a.x * SC, a.y * SC, b.x, b.y);
    }
    for (int i = tid; i < 512; i += nthr) {
        const int lane = i & 31, r = (i >> 5) & 3, fa = (i >> 7) & 1, hf = i >> 8, c = 8 * (lane & 1) + r;
        const int p0 = fa + 2 * (lane >> 2), p1 = p0 + 16, s0 = (hf && p0) ? 32 - p0 : p0, s1 = hf ? 32 - p1 : p1;
        sts128u(tb + FT_TWB + i * 16, make_uint4(pack_h2(wroot(4 * c * s0)), pack_h2(wroot(4 * (c + 4) * s0)),
                                                 pack_h2(wroot(4 * c * s1)), pack_h2(wroot(4 * (c + 4) * s1))));
    }
}

template <bool TW>
__device__ __forceinline__ void dft16(uint4 (&out)[4], const uint4 (&in)[4], const uint4 (&m)[4], const uint4 (&tw)[4]) {
#pragma unroll
    for (int i = 0; i < 4; i++)
#pragma unroll
        for (int mt = 0; mt < 2; mt++) {
            float c[4] = {0.f, 0.f, 0.f, 0.f};
            mma16816(c, m[2 * mt].x, m[2 * mt].y, m[2 * mt].z, m[2 * mt].w, comp(in[0], i), comp(in[1], i));
            mma16816(c, m[2 * mt + 1].x, m[2 * mt + 1].y, m[2 * mt + 1].z, m[2 * mt + 1].w, comp(in[2], i), comp(in[3], i));
            if (TW) {
                const float2 a = cmul(make_float2(c[0], c[2]), unpack_h2(comp(tw[i], 2 * mt))), b = cmul(make_float2(c[1], c[3]), unpack_h2(comp(tw[i], 2 * mt + 1)));
                setcomp(out[2 * mt], i, pack_bf16(a.x, a.y));
                setcomp(out[2 * mt + 1], i, pack_bf16(b.x, b.y));
            } else {
                setcomp(out[2 * mt], i, pack_bf16(c[0], c[2]));
                setcomp(out[2 * mt + 1], i, pack_bf16(c[1], c[3]));
            }
        }
}
__device__ __forceinline__ void tma_ld4(uint32_t dst, const CUtensorMap* m, int c0, int c1, uint32_t bar) {
    asm volatile("cp.async.bulk.tensor.4d.shared::cluster.global.mbarrier::complete_tx::bytes [%0], [%1, {%3, %4, %5, %5}], [%2];"
                 ::"r"(dst), "l"(m), "r"(bar), "r"(c0), "r"(c1), "r"(0) : "memory");
}
__device__ __forceinline__ void tma_st4(uint32_t src, const CUtensorMap* m, int c0, int c1) {
    asm volatile("cp.async.bulk.tensor.4d.global.shared::cta.bulk_group [%1, {%2, %3, %4, %4}], [%0];" ::"r"(src), "l"(m), "r"(c0), "r"(c1), "r"(0) : "memory");
}
__device__ __forceinline__ void tma_ld3(uint32_t dst, const CUtensorMap* m, int c0, int c1, uint32_t bar) {
    asm volatile("cp.async.bulk.tensor.3d.shared::cluster.global.mbarrier::complete_tx::bytes [%0], [%1, {%3, %4, %5}], [%2];"
                 ::"r"(dst), "l"(m), "r"(bar), "r"(c0), "r"(c1), "r"(0) : "memory");
}
__device__ __forceinline__ void tma_st3(uint32_t src, const CUtensorMap* m, int c0, int c1) {
    asm volatile("cp.async.bulk.tensor.3d.global.shared::cta.bulk_group [%1, {%2, %3, %4}], [%0];" ::"r"(src), "l"(m), "r"(c0), "r"(c1), "r"(0) : "memory");
}
__device__ __forceinline__ void bulk_commit() { asm volatile("cp.async.bulk.commit_group;" ::: "memory"); }
__device__ __forceinline__ void bulk_wait_read() { asm volatile("cp.async.bulk.wait_group.read 0;" ::: "memory"); }
__device__ __forceinline__ void bulk_wait_all() { asm volatile("cp.async.bulk.wait_group 0;" ::: "memory"); }

__device__ __forceinline__ float2 wroot_fast(int e) {
    float s, c; __sincosf((float)(((e + 1024) & 2047) - 1024) * (-3.14159265358979f / 1024.f), &s, &c); return make_float2(c, s);
}
template <bool INV, int NT>
__device__ __forceinline__ void fft_col(int s2, int t0, const CUtensorMap* src, const CUtensorMap* dst, uint32_t gb, uint32_t mb,
                                        int w, int lane, int bar) {
    const int g = lane >> 2, t = lane & 3;
    const bool lead = w == 4 && lane == 0;
    if (NT > 1 && lead)
        for (int i = 0; i < 2; i++) { mbar_expect_tx(mb + 8 * i, 32768); tma_ld4(gb + i * 32768, src, (t0 + i) * 64, s2, mb + 8 * i); }
    uint4 f[4], m[2][4];
#pragma unroll
    for (int i = 0; i < 4; i++) {
        const int o = 8 * (i >> 1) + g, in = 8 * (i & 1) + 2 * t, sg = INV ? -128 : 128;
        f[i] = afrag(wroot_fast(sg * o * in), wroot_fast(sg * o * (in + 1)));
#pragma unroll
        for (int q = 0; q < 2; q++) {
            const int z = 2 * w + q;
            m[q][i] = INV ? afrag(wroot_fast(-(8 * o + s2) * (z + 16 * in)), wroot_fast(-(8 * o + s2) * (z + 16 * in + 16)))
                          : afrag(wroot_fast((z + 16 * o) * (8 * in + s2)), wroot_fast((z + 16 * o) * (8 * in + 8 + s2)));
        }
    }
    const uint32_t r1 = (32 * w + 2 * t) * 128 + ((g ^ (2 * t)) << 4);
    const uint32_t w1 = (32 * w + g) * 128 + (((2 * t) ^ (((w & 3) << 1) | (g & 1))) << 4);
    const uint32_t r2 = (32 * t + 2 * w) * 128 + ((g ^ (2 * t)) << 4);
    const uint32_t w2 = (32 * w + g) * 128 + (((2 * t) ^ g) << 4);
    int bi = 0, ph = 0;
#pragma unroll 1
    for (int it = 0; it < NT; it++) {
        const uint32_t buf = gb + bi * 32768;
        mbar_wait(mb + 8 * bi, ph);
        uint4 in[2][4], out[4];
#pragma unroll
        for (int q = 0; q < 2; q++)
#pragma unroll
            for (int i = 0; i < 4; i++) in[q][i] = lds128u(buf + (r1 ^ ((i & 1) * 0x90)) + (i >> 1) * 1024 + q * 2048);
        __syncwarp();
#pragma unroll
        for (int q = 0; q < 2; q++) {
            if (INV) dft16<false>(out, in[q], m[q], f); else dft16<false>(out, in[q], f, f);
#pragma unroll
            for (int i = 0; i < 4; i++) sts128u(buf + (w1 ^ ((i & 1) << 4)) + (i >> 1) * 1024 + q * 2048, out[i]);
        }
        bar_sync(bar, 256);
#pragma unroll
        for (int q = 0; q < 2; q++)
#pragma unroll
            for (int i = 0; i < 4; i++) in[q][i] = lds128u(buf + (r2 ^ (q * 0x90)) + (i & 1) * 2048 + (i >> 1) * 16384);
        const int bn = bi == 0 ? 2 : bi - 1;
        if (lead && it < NT - 2) { bulk_wait_read(); mbar_expect_tx(mb + 8 * bn, 32768); tma_ld4(gb + bn * 32768, src, (t0 + it + 2) * 64, s2, mb + 8 * bn); }
        bar_sync(bar, 256);
#pragma unroll
        for (int q = 0; q < 2; q++) {
            if (INV) dft16<false>(out, in[q], f, f); else dft16<false>(out, in[q], m[q], f);
#pragma unroll
            for (int i = 0; i < 4; i++) sts128u(buf + (w2 ^ ((i & 1) << 4)) + (i >> 1) * 1024 + q * 2048, out[i]);
        }
        fence_async_smem();
        bar_sync(bar, 256);
        if (NT > 1 && lead) { tma_st4(buf, dst, (t0 + it) * 64, s2); bulk_commit(); }
        if (++bi == 3) { bi = 0; ph ^= 1; }
    }
    if (NT > 1 && lead) bulk_wait_read();
}

__device__ __forceinline__ float ldw(uint32_t a) {
    uint16_t v; asm volatile("ld.shared.u16 %0, [%1];" : "=h"(v) : "r"(a) : "memory");
    return __uint_as_float((uint32_t)v << 16);
}
__device__ __forceinline__ void fft_mid(int grp, const FftMaps& fm, uint32_t tb,
                                        uint32_t gb, uint32_t mb, uint32_t& cnt, int w, int lane, int bar) {
    const int g = lane >> 2, t = lane & 3;
    const bool lead = w == 4 && lane == 0;
    const uint32_t wb = gb + 65536;
#define MID_LOAD(k, c)                                                                                                  \
    { mbar_expect_tx(mb + 8 * ((c) & 1), 32768);                                                                        \
      tma_ld3(gb + ((c) & 1) * 32768, &fm.y2, 0, (k) * 8, mb + 8 * ((c) & 1));                                          \
      tma_ld3(gb + ((c) & 1) * 32768 + 16384, &fm.y2, 0, ((256 - (k)) & 255) * 8, mb + 8 * ((c) & 1)); }
#define MID_LOADW(k)                                                                                                    \
    { mbar_expect_tx(mb + 16, 36864);                                                                                   \
      tma_ld3(wb, &fm.wr, (k) * 513 & ~7, 0, mb + 16); tma_ld3(wb + 9216, &fm.wi, (k) * 513 & ~7, 0, mb + 16);          \
      tma_ld3(wb + 18432, &fm.wr, ((256 - (k)) & 255) * 513 & ~7, 0, mb + 16); tma_ld3(wb + 27648, &fm.wi, ((256 - (k)) & 255) * 513 & ~7, 0, mb + 16); }
    if (lead) { MID_LOAD(grp, cnt); MID_LOADW(grp); }
    const int hB = w >> 2, faB = (w >> 1) & 1, xB = faB;
    const int phi = 8 * (w & 3) + g;
    const uint32_t rA = (8 * w + 2 * t) * 128 + ((g ^ (2 * t)) << 4);
    const uint32_t wA = (8 * w + g) * 128 + (((2 * t) ^ ((g & 1) | ((w & 3) << 1))) << 4);
    const uint32_t oB = (w >> 1) * 8192 + (w & 1) * 512;
    const uint32_t rB = oB + (8 * t + (g >> 2)) * 128 + (((g & 3) ^ ((g >> 2) | (t << 1)) ^ xB) << 4);
    const uint32_t wB = oB + (8 * (g >> 1) + (t >> 1)) * 128 + (((((g & 1) << 2) | (2 * (t & 1))) ^ ((t >> 1) | ((g >> 1) << 1)) ^ xB) << 4);
    const uint32_t wBi = oB + (8 * (g >> 1) + (t >> 1)) * 128 + (((((g & 1) << 2) | (2 * (t & 1))) ^ ((t >> 1) | ((w & 1) << 2))) << 4);
    const int hC = (lane >> 3) & 1, pr = 8 * (w & 3) + (lane & 7), pc = hC ? (32 - pr) & 31 : pr;
    const uint32_t aC = hC * 16384 + (pc & 1) * 8192 + (pc >> 2) * 1024 + (((((pc & 2) << 1) | (lane >> 4)) ^ (((pc >> 2) & 3) << 1) ^ (pc & 1)) << 4);
    const uint32_t g0 = wb + (t >> 1) * 144 + (32 * (t & 1) + phi) * 2, g1 = wb + 18432 + (7 - (t >> 1)) * 144 + (64 - 32 * (t & 1) - phi) * 2;
    const uint32_t wAo = (8 * w + g) * 128 + (((2 * t) ^ g) << 4);
    uint32_t wph = 0;
#pragma unroll 1
    for (int k1 = grp; k1 < 129; k1 += 8, cnt++, wph ^= 1) {
        const uint32_t buf = gb + (cnt & 1) * 32768;
        uint4 in[2][4], m[4], out[4];
        m[0] = m[1] = m[2] = lds128u(tb + FT_A8 + lane * 16);
        m[3] = negfrag(m[0]);
        mbar_wait(mb + 8 * (cnt & 1), (cnt >> 1) & 1);
#pragma unroll
        for (int q = 0; q < 2; q++)
#pragma unroll
            for (int i = 0; i < 4; i++) in[q][i] = lds128u(buf + (rA ^ ((i & 1) * 0x90)) + (i >> 1) * 8192 + q * 16384);
        __syncwarp();
#pragma unroll
        for (int q = 0; q < 2; q++) {
            dft16<false>(out, in[q], m, m);
#pragma unroll
            for (int i = 0; i < 4; i++) sts128u(buf + (wA ^ (((i ^ (i >> 1)) & 1) << 4)) + (i >> 1) * 8192 + q * 16384, out[i]);
        }
        {
            uint4 tw[4];
#pragma unroll
            for (int i = 0; i < 4; i++) {
                m[i] = lds128u(tb + (faB ? FT_B1F : FT_F16) + i * 512 + lane * 16);
                if (hB) { m[i].y ^= 0x80008000u; m[i].w ^= 0x80008000u; }
                tw[i] = lds128u(tb + FT_TWB + (w >> 1) * 2048 + i * 512 + lane * 16);
            }
            bar_sync(bar, 256);
#pragma unroll
            for (int q = 0; q < 2; q++)
#pragma unroll
                for (int i = 0; i < 4; i++) in[q][i] = lds128u(buf + (rB ^ ((i & 1) << 6)) + (i >> 1) * 4096 + q * 256);
            __syncwarp();
#pragma unroll
            for (int q = 0; q < 2; q++) {
                dft16<true>(out, in[q], m, tw);
#pragma unroll
                for (int i = 0; i < 4; i++) sts128u(buf + (wB ^ ((i & 1) << 4)) + (i >> 1) * 4096 + q * 256, out[i]);
            }
        }
        {
            const uint32_t cjm = (g & 1) ? 0x8000u : 0x80000000u;
            float4 tw[4];
#pragma unroll
            for (int i = 0; i < 4; i++) { m[i] = lds128u(tb + FT_C + i * 512 + lane * 16); tw[i] = lds128(tb + FT_TWC + ((w & 3) * 4 + i) * 512 + lane * 16); }
            if (lead && k1 + 8 < 129) { bulk_wait_read(); MID_LOAD(k1 + 8, cnt + 1); }
            __syncwarp();
            mbar_wait(mb + 16, wph);
            const uint32_t o0 = (k1 & 7) * 2, o1 = (-k1 & 7) * 2;
            if (w == 1 && lane < 16) {
                const int k2 = lane & 7, k2p = k1 ? 7 - k2 : (8 - k2) & 7;
                const uint32_t p0 = wb + (lane >> 3) * 9216 + k2 * 1152 + o0, p1 = wb + 18432 + (lane >> 3) * 9216 + k2p * 1152 + o1;
                const float sg = lane < 8 ? 0.5f : -0.5f;
                const uint32_t v = pack_bf16(0.5f * ldw(p0) + sg * ldw(p1), 0.5f * ldw(p1 + 1136) + sg * ldw(p0 + 1136));
                asm volatile("st.shared.u16 [%0], %1;" ::"r"(p0), "h"((uint16_t)v) : "memory");
                asm volatile("st.shared.u16 [%0], %1;" ::"r"(p1 + 1136), "h"((uint16_t)(v >> 16)) : "memory");
                fence_async_smem();
            }
            bar_sync(bar, 256);
#define FFT_CU 1
            constexpr int CU = FFT_CU;
#pragma unroll CU
            for (int q = 0; q < 4; q++) {
                const int k2 = 4 * (w >> 2) + q, k2p = k1 ? 7 - k2 : (8 - k2) & 7, kr = hC ? k2p : k2;
                const uint32_t a0 = buf + (aC ^ ((kr & 1) << 4)) + kr * 128;
                const uint32_t r0 = g0 + k2 * 1152 + o0, r1 = g1 + k2p * 1152 + o1;
                uint32_t x[4], y[4];
                ldsm4(x, a0); ldsm4(y, a0 ^ 32);
                float c[4][4];
#pragma unroll
                for (int i = 0; i < 4; i++) { c[i][0] = c[i][1] = c[i][2] = c[i][3] = 0.f; mma16816(c[i], x[0], x[1], x[2], x[3], m[i].x, m[i].y); }
#pragma unroll
                for (int i = 0; i < 4; i++) mma16816(c[i], y[0], y[1], y[2], y[3], m[i].z, m[i].w);
#pragma unroll
                for (int i = 0; i < 4; i++) {
                    const float2 ga = make_float2(ldw(r0 + i * 288), ldw(r0 + 9216 + i * 288));
                    const float2 gc = make_float2(ldw(r1 - i * 288), ldw(r1 + 9216 - i * 288));
                    const float tc = tw[i].z, ts = tw[i].w;
                    const float* z = c[i];
                    const float2 S = make_float2(ga.x + gc.x, ga.y - gc.y), D = make_float2(ga.x - gc.x, ga.y + gc.y);
                    const float2 u = make_float2(ts * z[0] - tc * z[3], ts * z[1] + tc * z[2]), v = make_float2(ts * z[2] - tc * z[1], ts * z[3] + tc * z[0]);
                    uint32_t* o = (i < 2 ? x : y) + 2 * (i & 1);
                    o[0] = pack_bf16(fmaf(S.x, z[0], fmaf(-S.y, z[1], fmaf(D.x, u.x, -D.y * u.y))), fmaf(S.x, z[1], fmaf(S.y, z[0], fmaf(D.x, u.y, D.y * u.x))));
                    o[1] = pack_bf16(fmaf(S.x, z[2], fmaf(-S.y, z[3], fmaf(-D.x, v.x, D.y * v.y))), fmaf(S.x, z[3], fmaf(S.y, z[2], fmaf(-D.x, v.y, -D.y * v.x))));
                }
#pragma unroll
                for (int i = 0; i < 4; i++) { c[i][0] = c[i][1] = c[i][2] = c[i][3] = 0.f; mma16816(c[i], x[0], x[1], x[2], x[3], m[i].x ^ cjm, m[i].y ^ cjm); }
#pragma unroll
                for (int i = 0; i < 4; i++) mma16816(c[i], y[0], y[1], y[2], y[3], m[i].z ^ cjm, m[i].w ^ cjm);
#pragma unroll
                for (int i = 0; i < 4; i++) {
                    uint32_t* o = (i < 2 ? x : y) + 2 * (i & 1);
                    o[0] = pack_bf16(c[i][0] * tw[i].x + c[i][1] * tw[i].y, c[i][1] * tw[i].x - c[i][0] * tw[i].y);
                    o[1] = pack_bf16(c[i][2] * tw[i].x + c[i][3] * tw[i].y, c[i][2] * tw[i].y - c[i][3] * tw[i].x);
                }
                stsm4(a0, x[0], x[1], x[2], x[3]);
                stsm4(a0 ^ 32, y[0], y[1], y[2], y[3]);
            }
        }
#pragma unroll
        for (int i = 0; i < 4; i++) { m[i] = lds128u(tb + (faB ? FT_B1I : FT_F16) + i * 512 + lane * 16); if (!faB) m[i] = conjfrag(m[i]); }
        bar_sync(bar, 256);
        if (lead && k1 + 8 < 129) MID_LOADW(k1 + 8);
        __syncwarp();
#pragma unroll
        for (int q = 0; q < 2; q++)
#pragma unroll
            for (int i = 0; i < 4; i++) in[q][i] = lds128u(buf + (rB ^ ((i & 1) << 6)) + (i >> 1) * 4096 + q * 256);
        __syncwarp();
#pragma unroll
        for (int q = 0; q < 2; q++) {
            dft16<false>(out, in[q], m, m);
#pragma unroll
            for (int i = 0; i < 4; i++) sts128u(buf + (wBi ^ ((i & 1) << 4) ^ (q << 5)) + (i >> 1) * 4096 + q * 256, out[i]);
        }
        m[0] = m[1] = m[2] = conjfrag(lds128u(tb + FT_A8 + lane * 16));
        m[3] = negfrag(m[0]);
        bar_sync(bar, 256);
#pragma unroll
        for (int q = 0; q < 2; q++)
#pragma unroll
            for (int i = 0; i < 4; i++) in[q][i] = lds128u(buf + (rA ^ ((i & 1) * 0x90)) + (i >> 1) * 8192 + q * 16384);
        __syncwarp();
#pragma unroll
        for (int q = 0; q < 2; q++) {
            dft16<false>(out, in[q], m, m);
#pragma unroll
            for (int i = 0; i < 4; i++) sts128u(buf + (wAo ^ ((i & 1) << 4)) + (i >> 1) * 8192 + q * 16384, out[i]);
        }
        fence_async_smem();
        bar_sync(bar, 256);
        if (lead) {
            tma_st3(buf, &fm.y2, 0, k1 * 8);
            if (k1 & 127) tma_st3(buf + 16384, &fm.y2, 0, (256 - k1) * 8);
            bulk_commit();
        }
    }
    if (lead) bulk_wait_all();
}

__device__ __align__(128) unsigned g_start;
__device__ __align__(128) unsigned g_fbar;
__device__ __align__(128) unsigned g_end;
__device__ __forceinline__ unsigned gbar_arrive(unsigned* c, unsigned inc, unsigned total, int lane) {
    unsigned v = 0;
    if (lane == 0) { asm volatile("fence.proxy.async;" ::: "memory"); fence_gpu(); v = atomicAdd(c, inc); }
    return (__shfl_sync(~0u, v, 0) & ~(total - 1)) + total;
}
__device__ __forceinline__ void gbar_wait(unsigned* c, unsigned target, unsigned ns) {
    uint32_t n = 0;
    while (__any_sync(~0u, (int)(ld_acquire(c) - target) < 0)) { if (ns) __nanosleep(ns); if (++n > SPIN_LIMIT) __trap(); }
    asm volatile("fence.proxy.async;" ::: "memory");
}
__device__ __forceinline__ void fft_rest(int cta, const FftMaps& fm, uint32_t sb, bool skip) {
    const int hi = __shfl_sync(~0u, threadIdx.x >> 8, 0), w = __shfl_sync(~0u, (threadIdx.x >> 5) & 7, 0), lane = threadIdx.x & 31;
    unsigned target = 0;
    if (w == 4) target = gbar_arrive(&g_start, 16, 256, lane);
    if (threadIdx.x < 32) mbar_init(sb + FT_BAR + 8 * threadIdx.x, 1);
    fft_tables(sb, threadIdx.x, 512);
    fence_async_smem();
    __syncthreads();
    const int grp = cta * 2 + hi, bar = 1 + hi;
    const uint32_t gb = sb + hi * FG_SIZE, mb = sb + FT_BAR + hi * 128;
    uint32_t cnt = 0;
    if (w == 4) gbar_wait(&g_start, target, 200);
    GT(1);
    fft_mid(grp, fm, sb, gb, mb, cnt, w, lane, bar);
    if (w == 4) gbar_wait(&g_fbar, gbar_arrive(&g_fbar, 1, 8, lane), 200);
    GT(2);
    fft_col<true, 16>(grp, 0, &fm.y, &fm.o, gb, mb + 64, w, lane, bar);
}

__device__ __align__(256) uint4 g_kvq[4 * 32 * 3 * 8 * 2 * 32];
__device__ __align__(256) uint2 g_alpha[2 * 32 * 3 * 8 * 2 * 32];
__device__ __align__(256) uint4 g_red[5 * 32768 / 16];
__device__ __align__(256) uint4 g_stamp[32];
__device__ __align__(256) uint4 g_qst[128 * 2];
__device__ __align__(256) bf16 g_ox[2048 * 4096];
struct Tune { uint32_t d_alpha, d_r, opt, d_q, d_v, spread, extra; };
#define OP_SPLIT 1
#define OPD_EARLY 0
constexpr int RA = 2;

constexpr uint32_t SM_BASE = 1024;
constexpr uint32_t O_WO = 0;
constexpr uint32_t O_WV = 65536;
constexpr uint32_t O_XB = 131072;
constexpr uint32_t O_MEM = O_XB + 32768;
constexpr uint32_t O_RECV = O_MEM + 8192;
constexpr uint32_t O_KVQ = O_RECV + 12288;
constexpr uint32_t O_STG = O_KVQ + 18432;
constexpr uint32_t O_S = O_STG + 8192;
constexpr uint32_t O_XO = O_STG + 16384;
constexpr uint32_t O_P = O_S + 10240;
constexpr uint32_t O_O = O_P + 1536;
constexpr uint32_t O_VM = O_O + 2048;
constexpr uint32_t O_DBG = O_VM + 2048;
constexpr uint32_t O_F1 = 196608;
constexpr uint32_t O_BAR = 232448 - 512;
constexpr uint32_t MAIN_SMEM = 232448;
static_assert(O_DBG + (DBG_TIMING ? 4 * DBG_N * 24 * 4 : 0) <= O_BAR && FFT_SMEM <= MAIN_SMEM && O_F1 + 32768 <= O_BAR, "smem");
constexpr int G_ST = 6;
enum { B_WK0 = 0, B_WK1, B_WQ0, B_WQ1, B_WV, B_WO, B_F1, B_XP, B_XFULL, B_RFULL, B_AFULL, B_KVFULL, B_QST, B_RECV, B_GF = B_RECV + 6,
       B_QDONE = B_GF + G_ST, B_KDONE, B_XEMPTY, B_SDONE, B_SRDY, B_OPDONE, B_GE, B_XPE = B_GE + G_ST, B_QKW, B_MEM, B_COUNT };

constexpr float SM_SCALE_LOG2 = 0.08838834764831845f * 1.4426950408889634f;
constexpr float MASK_VAL = -1.0e9f / 0.08838834764831845f;

__device__ __forceinline__ uint32_t red_grp(int grp) { return (uint32_t)((grp >> 1) * 1024 + (grp & 1) * 256); }
__host__ __device__ constexpr uint64_t xdesc(int ks) { return mkdesc(SM_BASE + O_XB + (ks >> 2) * 1024 + (ks & 3) * 32, 16, 8192, 1); }

__device__ __forceinline__ void x_split(const float* d, uint32_t (&sn)[4], uint32_t (&kp)[4], int kh) {
#pragma unroll
    for (int i = 0; i < 4; i++) {
        const uint32_t lo = pack_bf16(d[2 * i], d[2 * i + 1]), hi = pack_bf16(d[8 + 2 * i], d[8 + 2 * i + 1]);
        sn[i] = kh ? lo : hi; kp[i] = kh ? hi : lo;
    }
}
__device__ __forceinline__ void x_send(int R, const uint32_t (&sn)[4], int sg, int tid, uint32_t sb, uint32_t mate) {
    const uint32_t par = sg & 1;
    const uint32_t bar = O_BAR + 8 * (B_RECV + R * 2) + 8 * par;
    if (tid == 0) mbar_expect_tx(sb + bar, 2048);
    asm volatile("st.async.shared::cluster.mbarrier::complete_tx::bytes.v4.b32 [%0], {%1,%2,%3,%4}, [%5];"
                 ::"r"(mate + O_RECV + (par * 3 + R) * 2048 + tid * 16), "r"(sn[0]), "r"(sn[1]), "r"(sn[2]), "r"(sn[3]), "r"(mate + bar) : "memory");
}
__device__ __forceinline__ void x_wait(int R, int sg, uint32_t sb) {
    mbar_wait_cluster(sb + O_BAR + 8 * (B_RECV + R * 2) + 8 * (sg & 1), (sg >> 1) & 1);
}
template <int R>
__device__ __forceinline__ void x_finish(const uint32_t (&kp)[4], int sg, int h, int mt, int kh, int tid, uint32_t sb) {
    const uint4 r = lds128u(sb + O_RECV + ((sg & 1) * 3 + R) * 2048 + tid * 16);
    uint32_t u0 = add_bf16x2(kp[0], r.x), u1 = add_bf16x2(kp[1], r.y), u2 = add_bf16x2(kp[2], r.z), u3 = add_bf16x2(kp[3], r.w);
    if (R < 2) { u0 = movm(u0); u1 = movm(u1); u2 = movm(u2); u3 = movm(u3); }
    const uint32_t tag = ((sg >> 2) & 1) ^ 1;
    u0 = (u0 & ~1u) | tag;
    uint4* const hb = &g_kvq[((sg & 3) * 32 + h) * (3 * 512)];
    if (R == 0) {
        uint2* p = (uint2*)hb + (kh * 16 + mt) * 32 + (tid & 31);
        asm volatile("{\n.reg .pred p;\nsetp.lt.s32 p, %5, 64;\n@p st.relaxed.gpu.global.v2.b32 [%0], {%1,%2};\n@p st.relaxed.gpu.global.v2.b32 [%0+2048], {%3,%4};\n}"
                     ::"l"(p), "r"(u0), "r"(u1), "r"((u2 & ~1u) | tag), "r"(u3), "r"(sg) : "memory");
    } else {
        asm volatile("{\n.reg .pred p;\nsetp.lt.s32 p, %5, 64;\n@p st.relaxed.gpu.global.v4.b32 [%0], {%1,%2,%3,%4};\n}"
                     ::"l"(hb + R * 512 + (mt * 2 + kh) * 32 + (tid & 31)), "r"(u0), "r"(u1), "r"(u2), "r"(u3), "r"(sg) : "memory");
    }
}

__device__ __forceinline__ uint32_t convert_mem(const unsigned char* redp, int s, int kh, int jj, int w, int lane, uint32_t sb, uint32_t& sf) {
    const uint32_t off = red_grp(jj * 16 + w * 4 + (lane >> 3)), o16 = off + (lane & 7) * 16, o8 = off + 512 + ((lane >> 3) & 1) * 64 + (lane & 7) * 8;
    uint32_t ma = sb + O_MEM + (jj * 4 + (lane >> 4)) * 1024 + (lane & 7) * 128 + (((2 * w + ((lane >> 3) & 1)) ^ (lane & 7)) << 4);
    uint32_t a16 = sb + O_STG + o16, a8 = sb + O_STG + o8;
    const uint32_t target = (s & 4) ? 0x42C00000u : 0x42000000u;
    uint32_t n = 0;
    bool redo;
    KEEP2(ma, a16); KEEP2(a8, target);
#pragma unroll 1
    do {
        asm volatile("" : "+r"(n));
        if (n) {
            const unsigned char* pg = redp + (s & 3) * 32768 + kh * 16384;
            const uint4 x = ldg_rlx128(pg + o16), y = ldg_rlx128(pg + o16 + 128);
            const uint2 z = ldg_rlx64(pg + o8);
            sts128u(a16, x); sts128u(a16 + 128, y); sts64u(a8, z);
            if (n > SPIN_LIMIT) __trap();
        }
        n++;
        mbar_wait(sb + O_BAR + 8 * B_RFULL, s & 1);
        const uint4 ra = lds128u(a16), rb = lds128u(a16 + 128);
        const uint2 rc = lds64u(a8);
        stsm4t(ma, ra.x, ra.y, ra.z, __byte_perm(ra.w, rc.x, 0x5410));
        stsm4t(ma + 2048, rb.x, rb.y, rb.z, __byte_perm(rb.w, rc.x, 0x7610));
        redo = __any_sync(~0u, orx(orx2(ra.w, rb.w, target), rc.y, target) > 0xffffu);
    } while (redo);
    if (lane == 0) mbar_arrive(sb + O_BAR + 8 * B_MEM);
    fence_async_smem();
    __syncwarp();
    if (lane == 0) mbar_arrive(sb + O_BAR + 8 * B_QKW);
    return n - 1;
}

#define F16(d, o) F4(d, o), F4(d, o + 4), F4(d, o + 8), F4(d, o + 12)
__device__ __forceinline__ void wg_ss128(float (&d)[64], uint64_t da, uint64_t db, int sc) {
    asm volatile("{\n.reg .pred p;\nsetp.ne.b32 p, %66, 0;\nwgmma.mma_async.sync.aligned.m64n128k16.f32.bf16.bf16 "
                 "{%0,%1,%2,%3,%4,%5,%6,%7,%8,%9,%10,%11,%12,%13,%14,%15,%16,%17,%18,%19,%20,%21,%22,%23,%24,%25,%26,%27,%28,%29,%30,%31,"
                 "%32,%33,%34,%35,%36,%37,%38,%39,%40,%41,%42,%43,%44,%45,%46,%47,%48,%49,%50,%51,%52,%53,%54,%55,%56,%57,%58,%59,%60,%61,%62,%63}, "
                 "%64, %65, p, 1, 1, 0, 1;\n}"
                 : F16(d, 0), F16(d, 16), F16(d, 32), F16(d, 48) : "l"(da), "l"(db), "r"(sc));
}
__device__ __forceinline__ void stg_rlx32(void* p, uint32_t v) { asm volatile("st.relaxed.gpu.global.u32 [%0], %1;" ::"l"(p), "r"(v) : "memory"); }

__global__ void __cluster_dims__(2, 1, 1) __launch_bounds__(512, 1)
rmt_main(const __grid_constant__ CUtensorMap tm_x, const __grid_constant__ CUtensorMap tm_wq, const __grid_constant__ CUtensorMap tm_wk,
         const __grid_constant__ CUtensorMap tm_wv, const __grid_constant__ CUtensorMap tm_wo, const bf16* __restrict__ mem0,
         const Tune tn, const __grid_constant__ FftMaps fm, const __grid_constant__ CUtensorMap tm_o,
         const __grid_constant__ CUtensorMap tm_w2, bf16* __restrict__ out) {
    extern __shared__ __align__(1024) unsigned char smem_raw[];
    const uint32_t sb = smem_u32(smem_raw);
    if ((sb & 0x3FFFF) != SM_BASE) __trap();
    GT(6);
    const int cid = blockIdx.x >> 1, kh = blockIdx.x & 1;
    const int tpc = cid < 4 ? 62 + cid : cid - 4;
    int h, nh;
    if (tpc < 32) { h = (tpc >> 4) * 8 + (tpc & 7); nh = (tpc >> 3) & 1; }
    else if (tpc < 60) { int u = tpc - 32, r = u % 14; h = 16 + (u / 14) * 7 + r % 7; nh = r / 7; }
    else if (tpc < 62) { GT(0); fft_rest((tpc - 60) * 2 + kh, fm, sb, tn.opt & 8); GT(3); return; }
    else { h = 30 + ((tpc - 62) >> 1); nh = tpc & 1; }
    const int j = nh * 2 + kh, role = h * 4 + j;
    const int wgi = __shfl_sync(~0u, threadIdx.x >> 7, 0);
    const int w = __shfl_sync(~0u, (threadIdx.x >> 5) & 3, 0);
    const int tid = threadIdx.x & 127, lane = tid & 31;
#define PIN_IDS() const int tid = __shfl_sync(~0u, threadIdx.x & 127, threadIdx.x & 31), lane = tid & 31
#define OPAQUE_IDS() int tid_ = tid; asm volatile("" : "+r"(tid_)); const int tid = tid_, lane = tid_ & 31; (void)lane
    unsigned char* const redp = (unsigned char*)(((uintptr_t)g_red + 32767) & ~(uintptr_t)32767);
    const uint32_t bars = sb + O_BAR;

    if (threadIdx.x < B_COUNT) {
        const int i = threadIdx.x;
        mbar_init(bars + 8 * i, i < B_QDONE ? 1 : i < B_GE ? 4 : i < B_XPE ? 8 : i < B_QKW ? 12 : 16);
        asm volatile("fence.mbarrier_init.release.cluster;" ::: "memory");
        fence_async_smem();
    } else if (threadIdx.x >= 64 && threadIdx.x < 71) {
        const int i = threadIdx.x - 64;
        const CUtensorMap* m = i == 0 ? &tm_wk : i == 1 ? &tm_wq : i == 2 ? &fm.x : i == 3 ? &tm_x : i == 4 ? &tm_wv : i == 5 ? &tm_wo : &fm.y;
        asm volatile("prefetch.tensormap [%0];" ::"l"(m) : "memory");
    }
    __syncthreads();
    const int wc0 = h * 128 + nh * 64;
    if (wgi < 2 && lane == 0) {
        if (w < 2) {
            const uint32_t bar = bars + 8 * (B_WK0 + 2 * (wgi ^ 1) + w);
            mbar_expect_tx(bar, 32768);
            tma2d(sb + (wgi ? O_XB : O_WO) + w * 32768, wgi ? &tm_wk : &tm_wq, wc0, kh * 512 + w * 256, bar);
        } else if (wgi == 0 && w == 2) {
            mbar_expect_tx(bars + 8 * B_F1, 32768);
            tma_ld4(sb + O_F1, &fm.x, (role & 15) * 64, role >> 4, bars + 8 * B_F1);
        } else if (wgi == 1 && w == 2 && role < 2 * (RA + 3)) tma4d_prefetch(&tm_x, kh * 8, (role >> 1) * 4);
    }
    GT(7);
    uint32_t mate;
    asm volatile("mapa.shared::cluster.u32 %0, %1, %2;" : "=r"(mate) : "r"(sb), "r"(kh ^ 1));
    if (wgi >= 2) fft_col<false, 1>(role >> 4, role & 15, &fm.x, &fm.y, sb + O_F1, bars + 8 * B_F1, (wgi - 2) * 4 + w, lane, 6);

    if (wgi < 2) {
        asm volatile("setmaxnreg.inc.sync.aligned.u32 176;");
        PIN_IDS();
        uint32_t a[32][4], sf = 0;
        {
            const uint32_t stage = sb + (wgi == 0 ? O_WO : O_XB);
            const uint32_t ad = stage + (((lane >> 4) & 1) * 8 + (lane & 7)) * 128 + (((2 * w + ((lane >> 3) & 1)) ^ (lane & 7)) << 4);
#pragma unroll
            for (int i = 0; i < 2; i++) {
                mbar_wait(bars + 8 * (B_WK0 + 2 * (wgi ^ 1) + i), 0);
#pragma unroll
                for (int ks = 0; ks < 16; ks++) ldsm4t(a[i * 16 + ks], ad + (i * 16 + ks) * 2048);
            }
#pragma unroll
            for (int ks = 0; ks < 32; ks += 2) KEEP2(a[ks][0], a[ks + 1][0]);
            SCHED_FENCE();
            if (lane == 0) mbar_arrive(bars + 8 * (B_QDONE + wgi));
            if (wgi == 0) GT(10); else GT(11);
        }
        asm volatile("barrier.cluster.arrive.relaxed.aligned;" ::: "memory");
        asm volatile("barrier.cluster.wait.acquire.aligned;" ::: "memory");
        uint32_t kp[4];
#define X_PASS(d, dofs)                                                                                    \
        wg_fence();                                                                                        \
        _Pragma("unroll") for (int ks = 0; ks < 32; ks++) { if (ks == 0) wg_rs32<0>(d, a[ks], xdesc(ks) + (dofs)); else wg_rs32<1>(d, a[ks], xdesc(ks) + (dofs)); } \
        wg_commit();                                                                                       \
        wg_wait<0>();
#define X_FINISH(sg) { if (wgi == 0) x_finish<0>(kp, sg, h, nh * 4 + w, kh, tid, sb); else x_finish<1>(kp, sg, h, nh * 4 + w, kh, tid, sb); }
        mbar_wait(bars + 8 * B_XP, 0);
        if (wgi == 0) GT(8);
#pragma unroll 1
        for (int sg = 0; sg < RA; sg++) {
            float d[16]; uint32_t sn[4];
            X_PASS(d, sg * 2048 - (int)((O_XB - O_WO) >> 4));
            if (sg > 0) {
                if (lane == 0) mbar_arrive(bars + 8 * B_XPE);
                x_wait(wgi, sg - 1, sb); X_FINISH(sg - 1);
            }
            x_split(d, sn, kp, kh);
            x_send(wgi, sn, sg, tid, sb, mate);
        }
#pragma unroll 1
        for (int s = 0; s < 64; s++) {
            TSI(s);
            {
                float d[16]; uint32_t sn[4], kc[4];
                x_wait(wgi, s + RA - 1, sb);
                mbar_wait(bars + 8 * B_XFULL, s & 1);
                if (wgi == 1) {
                    mbar_wait(bars + 8 * B_OPDONE, s & 1);
                    x_finish<1>(kp, s + RA - 1, h, nh * 4 + w, kh, tid, sb);
                    TS(5);
                } else mbar_wait(bars + 8 * B_OPDONE, s & 1);
                TS(6);
                X_PASS(d, 0);
                TS(7);
                x_split(d, sn, kc, kh);
                x_send(wgi, sn, s + RA, tid, sb, mate);
                TS(4);
                if (wgi == 0) { x_finish<0>(kp, s + RA - 1, h, nh * 4 + w, kh, tid, sb); TS(5); }
#pragma unroll
                for (int i = 0; i < 4; i++) kp[i] = kc[i];
            }
            uint2* ap = &g_alpha[((s & 1) * 32 + h) * (3 * 512) + wgi * 512 + ((nh * 4 + w) * 2 + kh) * 32 + lane];
            uint32_t mb0 = sb + O_MEM + (lane & 7) * 128 + (((lane >> 3) ^ (lane & 7)) << 4), mb1 = mb0 ^ 64;
            const uint32_t tag = ((s >> 1) & 1) ^ 1;
            KEEP2(mb0, mb1); KEEPP(ap);
            float e[2][4];
#pragma unroll
            for (int i = 0; i < 4; i++) e[0][i] = e[1][i] = 0.f;
            if (lane == 0) mbar_arrive(bars + 8 * B_MEM);
            mbar_wait(bars + 8 * B_MEM, s & 1);
            TS(0);
#pragma unroll
            for (int ks = 0; ks < 32; ks += 2) {
                uint32_t b[4];
                ldsm4(b, ((ks & 2) ? mb1 : mb0) + (ks >> 2) * 1024);
                mma16816(e[0], a[ks][0], a[ks][1], a[ks][2], a[ks][3], b[0], b[1]);
                mma16816(e[1], a[ks + 1][0], a[ks + 1][1], a[ks + 1][2], a[ks + 1][3], b[2], b[3]);
            }
            TS(2);
            uint32_t u0 = pack_bf16(e[0][0] + e[1][0], e[0][1] + e[1][1]), u1 = pack_bf16(e[0][2] + e[1][2], e[0][3] + e[1][3]);
            u0 = movm(u0); u1 = movm(u1);
            SCHED_FENCE();
            if (lane == 0) mbar_arrive(bars + 8 * B_QKW);
            stg_rlx64(ap, (u0 & ~1u) | tag, u1);
            TS(3);
            if (wgi == 1) {
                const uint2* vp = &g_alpha[((s & 1) * 32 + h) * (3 * 512) + 1024 + w * 128 + lane];
                const uint32_t vs = sb + O_VM + tid * 16;
                KEEPP(vp); KEEP2(vs, 0);
                mbar_wait(bars + 8 * B_QST, s & 1);
                uint32_t n, bad;
                asm volatile("ld.shared.u32 %0, [%1];" : "=r"(n) : "r"(bars + 504) : "memory");
                wait_gtime(n + tn.d_v);
                TS(8);
                n = 0;
                do {
                    uint2 va[4];
#pragma unroll
                    for (int i = 0; i < 4; i++) va[i] = ldg_rlx64(vp + i * 32);
                    if (++n > SPIN_LIMIT) __trap();
                    bad = (orx2(va[0].x, va[1].x, tag) | orx2(va[2].x, va[3].x, tag)) & 1;
                    sts128u(vs, make_uint4((add_bf16x2(va[0].x, va[1].x) & ~1u) | ((~s ^ bad) & 1), add_bf16x2(va[0].y, va[1].y),
                                                             add_bf16x2(va[2].x, va[3].x), add_bf16x2(va[2].y, va[3].y)));
                } while (__any_sync(~0u, bad));
                TS(9);
                TSV(16 + w, n - 1);
            }
        }
        x_wait(wgi, 63 + RA, sb);
        sts32(bars + 508, sf);
        TSDUMP();
        asm volatile("bar.arrive 7, 512;" ::: "memory");
        float d[64];
        int st = 0, ph = 0;
#pragma unroll 1
        for (int kt = 0; kt < 64; kt++) {
            mbar_wait(bars + 8 * (B_GF + st), ph);
            if (kt == 0) GT(4);
            const uint64_t da = mkdesc(SM_BASE + st * 32768 + wgi * 8192, 16, 1024, 1), db = mkdesc(SM_BASE + st * 32768 + 16384, 8192, 1024, 1);
            wg_fence();
#pragma unroll
            for (int k = 0; k < 4; k++) wg_ss128(d, da + k * 2, db + k * 128, kt | k);
            wg_commit();
            if (kt > 0) {
                wg_wait<1>();
                if (lane == 0) mbar_arrive(bars + 8 * (B_GE + (st == 0 ? G_ST - 1 : st - 1)));
            }
            if (++st == G_ST) { st = 0; ph ^= 1; }
        }
        wg_wait<0>();
        {
            const uint32_t sl = sb + O_F1 + (wgi * 4 + w) * 4096;
#pragma unroll
            for (int i = 0; i < 8; i++)
                stsm4(sl + (lane & 15) * 256 + (((2 * i + (lane >> 4)) ^ (lane & 7)) << 4), pack_bf16(d[8 * i], d[8 * i + 1]),
                      pack_bf16(d[8 * i + 2], d[8 * i + 3]), pack_bf16(d[8 * i + 4], d[8 * i + 5]), pack_bf16(d[8 * i + 6], d[8 * i + 7]));
            __syncwarp();
            bf16* op = out + (size_t)((role >> 3) * 128 + wgi * 64 + w * 16 + (lane >> 4)) * 2048 + 1024 + (role & 7) * 128 + (lane & 15) * 8;
#pragma unroll
            for (int i = 0; i < 8; i++) {
                const int r = 2 * i + (lane >> 4);
                const uint4 v = lds128u(sl + r * 256 + (((lane & 15) ^ (r & 7)) << 4));
                stg128(op + (size_t)i * 4096, v.x, v.y, v.z, v.w);
            }
        }
        GT(5);
    } else if (wgi == 2) {
        asm volatile("setmaxnreg.dec.sync.aligned.u32 64;");
        PIN_IDS();
        asm volatile("barrier.cluster.arrive.relaxed.aligned;" ::: "memory");
#define X_LOAD(dst, sg, bar) tma4d(sb + (dst), &tm_x, kh * 8, (sg) * 4, bars + 8 * (bar))
        if (w == 0) {
#define WV_LOAD(i) tma2d(sb + O_WV + (i) * 32768, &tm_wv, wc0, kh * 512 + (i) * 256, bars + 8 * B_WV)
            const int nearly = (tn.opt >> 5) & 3;
            mbar_wait(bars + 8 * B_WK0, 0);
            if (lane == 0) { mbar_expect_tx(bars + 8 * B_WV, 65536); for (int i = 0; i < nearly; i++) WV_LOAD(i); }
            mbar_wait(bars + 8 * B_QDONE, 0);
            if (lane == 0) { mbar_expect_tx(bars + 8 * B_XP, 65536); X_LOAD(O_WO, 0, B_XP); X_LOAD(O_WO + 32768, 1, B_XP); }
            mbar_wait(bars + 8 * B_KDONE, 0);
            if (lane == 0) {
                mbar_expect_tx(bars + 8 * B_XFULL, 32768); X_LOAD(O_XB, RA, B_XFULL);
                for (int i = nearly; i < 2; i++) WV_LOAD(i);
            }
        }
        asm volatile("barrier.cluster.wait.acquire.aligned;" ::: "memory");
        mbar_wait(bars + 8 * B_WV, 0);
        GT(12);
        uint32_t sf = 0, tref = gtime() - 4000;
#define V_PASS(d, dofs)                                                                                    \
        wg_fence();                                                                                        \
        _Pragma("unroll") for (int ks = 0; ks < 32; ks++) {                                                \
            constexpr uint64_t da0 = mkdesc(SM_BASE + O_WV, 16, 1024, 1);                                  \
            if (ks == 0) wg_ss40<0>(d, da0 + ks * 128, xdesc(ks) + (dofs)); else wg_ss40<1>(d, da0 + ks * 128, xdesc(ks) + (dofs)); \
        }                                                                                                  \
        wg_commit();                                                                                       \
        wg_wait<0>();
        mbar_wait(bars + 8 * B_XP, 0);
        {
            uint32_t kp[4];
#pragma unroll 1
            for (int sg = 0; sg <= RA; sg++) {
                float d[20]; uint32_t sn[4];
                if (sg < RA) { V_PASS(d, sg * 2048 - (int)((O_XB - O_WO) >> 4)); }
                if (sg == RA - 1) {
                    if (lane == 0) mbar_arrive(bars + 8 * B_XPE);
                    if (w == 0) {
                        mbar_wait(bars + 8 * B_XPE, 0);
                        GT(9);
                        if (lane == 0) {
                            mbar_expect_tx(bars + 8 * B_WO, 65536);
#pragma unroll
                            for (int i = 0; i < 4; i++) tma2d(sb + O_WO + i * 16384, &tm_wo, j * 256 + i * 64, h * 128, bars + 8 * B_WO);
                        }
                    }
                }
                if (sg > 0) { x_wait(2, sg - 1, sb); x_finish<2>(kp, sg - 1, h, nh * 4 + w, kh, tid, sb); }
                if (sg < RA) { x_split(d, sn, kp, kh); x_send(2, sn, sg, tid, sb, mate); }
            }
        }
#pragma unroll 1
        for (int s = 0; s < 64; s++) {
            TSI(s);
            OPAQUE_IDS();
            uint2* ap = &g_alpha[((s & 1) * 32 + h) * (3 * 512) + 1024 + ((nh * 4 + w) * 2 + kh) * 32 + lane];
            KEEPP(ap);
            float d[20];
            mbar_wait(bars + 8 * B_QKW, s & 1);
            TS(0);
            V_PASS(d, 0);
            TS(1);
            stg_rlx64(ap, (pack_bf16(d[16], d[17]) & ~1u) | (((s >> 1) & 1) ^ 1), pack_bf16(d[18], d[19]));
            if (lane == 0) mbar_arrive(bars + 8 * B_XEMPTY);
            if (s == 63) break;
            uint32_t sn[4], kp[4];
            x_split(d, sn, kp, kh);
            if (w == 3) {
                uint32_t n = 0, mx, mn;
                do {
                    const uint4 st = ldg_rlx128(&g_stamp[lane]);
                    mx = __reduce_max_sync(~0u, max(max(st.x - tref, st.y - tref), max(st.z - tref, st.w - tref)));
                    mn = __reduce_min_sync(~0u, min(min(st.x - tref, st.y - tref), min(st.z - tref, st.w - tref)));
                } while (mx >= 200000u && ++n < 64);
                tref = mx < 200000u ? tref + mx + (mx - mn > tn.spread ? tn.extra : 1) : gtime();
                TSV(12, clk()); TSV(13, n); TSV(14, mx - mn);
            }
            if (tn.opt & 1) { mbar_wait(bars + 8 * B_SDONE, s & 1); x_send(2, sn, s + RA, tid, sb, mate); }
            if (w == 0) {
                mbar_wait(bars + 8 * B_XEMPTY, s & 1);
                mbar_wait(bars + 8 * ((tn.opt & 2) ? B_SRDY : B_SDONE), s & 1);
                if (lane == 0) {
                    mbar_expect_tx(bars + 8 * B_XFULL, 32768);
                    X_LOAD(O_XB, s + RA + 1, B_XFULL);
                }
                mbar_wait(bars + 8 * B_SRDY, s & 1);
                if (lane == 0) {
                    const uint4* hb = &g_kvq[(((s + 1) & 3) * 32 + h) * (3 * 512)];
                    mbar_expect_tx(bars + 8 * B_KVFULL, 18432);
                    bulk_g2s(sb + O_KVQ, hb + 512, 16384, bars + 8 * B_KVFULL);
                    bulk_g2s(sb + O_KVQ + 16384, hb + j * 128, 2048, bars + 8 * B_KVFULL);
                    if (nh == 0 && ((h ^ s) & 7) == 0 && s < 61 - RA) tma4d_prefetch(&tm_x, kh * 8, (s + RA + 3) * 4);
                }
            }
            mbar_wait(bars + 8 * B_OPDONE, (s + 1) & 1);
            if (!(tn.opt & 1)) x_send(2, sn, s + RA, tid, sb, mate);
            if (w == 3) {
                wait_gtime(tref + tn.d_r);
                if (lane == 0) {
                    mbar_expect_tx(bars + 8 * B_RFULL, 16384);
                    bulk_g2s(sb + O_STG, redp + (s & 3) * 32768 + kh * 16384, 16384, bars + 8 * B_RFULL);
                }
                TSV(3, clk());
            }
            x_wait(2, s + RA, sb);
            const bool late = w == 3 || (tn.opt & 4);
            if (!late) { x_finish<2>(kp, s + RA, h, nh * 4 + w, kh, tid, sb); TS(6); }
            if (DBG_TIMING && w == 0) { mbar_wait(bars + 8 * B_RFULL, s & 1); TS(4); }
            const uint32_t n = convert_mem(redp, s, kh, 0, w, lane, sb, sf); (void)n;
            TS(5);
            TSV(8 + w, n);
            if (late) x_finish<2>(kp, s + RA, h, nh * 4 + w, kh, tid, sb);
        }
        sts32(bars + 508, sf);
        TSDUMP();
        asm volatile("bar.arrive 7, 512;" ::: "memory");
    } else {
        asm volatile("setmaxnreg.dec.sync.aligned.u32 96;");
        PIN_IDS();
        GT(0);
        asm volatile("barrier.cluster.arrive.relaxed.aligned;" ::: "memory");
#define RED_CLEAR(st)                                                                                           \
        if (lane < 16) {                                                                                        \
            const uint32_t cb = ((st) & 4) ? 0x42800000u : 0u;                                                  \
            stg128(redp + ((st) & 3) * 32768 + role * 256 + lane * 16, 0, (role & 2) ? cb : 0u, 0, cb);        \
        }
        uint32_t start_target = 0;
        if (w == 0) {
            RED_CLEAR(0); RED_CLEAR(1); RED_CLEAR(2);
            mbar_wait(bars + 8 * B_XP, 0);
            if (lane < 4) tma2d_prefetch(&tm_wo, j * 256 + lane * 64, h * 128);
            if (lane == 0) { tma_st4(sb + O_F1, &fm.y, (role & 15) * 64, role >> 4); bulk_commit(); bulk_wait_all(); }
            __syncwarp();
            start_target = gbar_arrive(&g_start, 1, 256, lane);
        }
        bar_sync(1, 128);
        sts128u(sb + O_VM + tid * 16, make_uint4(0, 0, 0, 0));
        mbar_wait(bars + 8 * B_KDONE, 0);
        {
#pragma unroll
            for (int q = 0; q < 4; q++) {
                const int row = (lane >> 3) + (q & 1) * 4, ch = lane & 7, kb = 2 * w + (q >> 1);
                const uint4 v = *(const uint4*)(mem0 + row * 1024 + kh * 512 + kb * 64 + ch * 8);
                sts128u(sb + O_MEM + kb * 1024 + row * 128 + ((ch ^ row) << 4), v);
            }
            fence_async_smem();
            __syncwarp();
            if (lane < 2) { mbar_arrive(bars + 8 * B_MEM); mbar_arrive(bars + 8 * B_QKW); }
            if (lane == 0) mbar_arrive(bars + 8 * B_OPDONE);
            if (tid == 0) mbar_arrive(bars + 8 * B_KVFULL);
        }
        asm volatile("barrier.cluster.wait.acquire.aligned;" ::: "memory");
        if (w == 0) gbar_wait(&g_start, start_target, 0);
        uint32_t sf = 0;
#pragma unroll 1
        for (int s = 0; s < 64; s++) {
            TSI(s);
            OPAQUE_IDS();
            uint4 kf[4]; uint2 qf[2];
            const uint32_t tg = ((s >> 2) & 1) ^ 1;
            {
                const uint32_t ka = sb + O_KVQ + w * 2048 + lane * 16, qa = sb + O_KVQ + 16384 + w * 512 + lane * 8;
                uint32_t n = s == 0;
                bool redo;
#pragma unroll 1
                do {
                    asm volatile("" : "+r"(n));
                    if (n) {
                        const uint4* hb = &g_kvq[((s & 3) * 32 + h) * (3 * 512)];
                        uint4 y[4];
                        do {
#pragma unroll
                            for (int i = 0; i < 4; i++) { kf[i] = ldg_rlx128(hb + 512 + w * 128 + i * 32 + lane); y[i] = ldg_rlx128(hb + 1024 + w * 128 + i * 32 + lane); }
#pragma unroll
                            for (int u = 0; u < 2; u++) qf[u] = ldg_rlx64((const uint2*)hb + j * 256 + (2 * w + u) * 32 + lane);
                            if (++n > SPIN_LIMIT) __trap();
                        } while (__any_sync(~0u, (orx2(y[0].x, y[1].x, tg) | orx2(y[2].x, y[3].x, tg)) & 1));
#pragma unroll
                        for (int i = 0; i < 4; i++) { sts128u(ka + i * 512, kf[i]); sts128u(ka + 8192 + i * 512, y[i]); }
#pragma unroll
                        for (int u = 0; u < 2; u++) sts64u(qa + u * 256, qf[u]);
                        fence_async_smem();
                    }
                    n++;
                    mbar_wait(bars + 8 * B_KVFULL, s & 1);
#pragma unroll
                    for (int i = 0; i < 4; i++) kf[i] = lds128u(ka + i * 512);
#pragma unroll
                    for (int u = 0; u < 2; u++) qf[u] = lds64u(qa + u * 256);
                    redo = __any_sync(~0u, or3(orx2(kf[0].x, kf[1].x, tg), orx2(kf[2].x, kf[3].x, tg), orx2(qf[0].x, qf[1].x, tg)) & 1);
                } while (redo);
                if (w == 0) TSV(22, n - 1);
            }
            TS(9);
            if (s > 0) {
                const uint32_t n = convert_mem(redp, s - 1, kh, 1, w, lane, sb, sf); (void)n;
                TS(11);
                TSV(16 + w, n);
                if (w == 1 && s < 62) RED_CLEAR(s + 2);
            }
            const uint32_t tag = ((s >> 1) & 1) ^ 1;
            const uint2* ap = &g_alpha[((s & 1) * 32 + h) * (3 * 512) + w * 128 + lane];
            const uint32_t l16 = sb + lane * 16, l4 = sb + lane * 4;
            const uint32_t sw = l16 + O_S + w * 2560, sr = l4 + O_S + w * 128;
            uint32_t pw = sb + O_P + ((lane >> 1) & 1) * 704 + (2 * w + (lane >> 4)) * 16 + ((lane >> 2) & 3) * 4 + (lane & 1) * 2;
            int lim = (lane & 2) ? 8 * j + 2 * w + (lane >> 4) - 2 * ((lane >> 2) & 3) - (lane & 1) : 64;
            uint32_t aa = sb + O_STG + w * 1024 + lane * 8;
            KEEP2(l16, l4); KEEP2(pw, lim); KEEP2(aa, tag);
            TS(0);
            if (w == 0) {
                mbar_wait(bars + 8 * B_MEM, s & 1);
                uint32_t tq = gtime();
                if (lane < 9) stg_rlx32(lane < 8 ? (uint32_t*)g_qst + role * 8 + lane : (uint32_t*)g_stamp + role, tq);
                wait_clk(clk(), tn.d_q);
                uint32_t n = 0, mx;
                do { mx = __reduce_max_sync(~0u, ldg_rlx32((const uint32_t*)g_qst + h * 32 + lane) - (tq - 1024)); } while (mx > 100000u && ++n < 16);
                TSV(13, n);
                if (mx <= 100000u) tq += mx - 1024;
                if (lane == 0) { sts32(bars + 504, tq); mbar_arrive(bars + 8 * B_QST); }
                TS(14);
                mbar_wait(bars + 8 * B_QKW, s & 1);
                TS(1);
                wait_gtime(tq + tn.d_alpha);
                if (lane == 0) {
                    mbar_expect_tx(bars + 8 * B_AFULL, 8192);
                    bulk_g2s(sb + O_STG, ap, 8192, bars + 8 * B_AFULL);
                }
                if (s == 0) { mbar_wait(bars + 8 * B_WO, 0); GT(1); }
            }
            {
                uint32_t n = 0;
                bool redo;
#pragma unroll 1
                do {
                    asm volatile("" : "+r"(n));
                    if (n) {
                        uint2 x[8];
#pragma unroll
                        for (int q = 0; q < 8; q++) x[q] = ldg_rlx64(ap + (q >> 2) * 512 + (q & 3) * 32);
#pragma unroll
                        for (int q = 0; q < 8; q++) sts64u(aa + (q >> 2) * 4096 + (q & 3) * 256, x[q]);
                        if (n > SPIN_LIMIT) __trap();
                    }
                    n++;
                    mbar_wait(bars + 8 * B_AFULL, s & 1);
                    TS(12);
                    uint2 qa[4], ka[4];
#pragma unroll
                    for (int i = 0; i < 4; i++) qa[i] = lds64u(aa + i * 256);
#pragma unroll
                    for (int i = 0; i < 4; i++) ka[i] = lds64u(aa + 4096 + i * 256);
                    float sa[5][4];
#pragma unroll
                    for (int i = 0; i < 5; i++) sa[i][0] = sa[i][1] = sa[i][2] = sa[i][3] = 0.f;
#pragma unroll
                    for (int u = 0; u < 2; u++) {
                        const uint32_t q0 = add_bf16x2(qa[2 * u].x, qa[2 * u + 1].x), q1 = add_bf16x2(qa[2 * u].y, qa[2 * u + 1].y);
                        mma16816(sa[1], q0, qf[u].x, q1, qf[u].y, kf[2 * u].x, kf[2 * u].y);
                        mma16816(sa[2], q0, qf[u].x, q1, qf[u].y, kf[2 * u].z, kf[2 * u].w);
                        mma16816(sa[3], q0, qf[u].x, q1, qf[u].y, kf[2 * u + 1].x, kf[2 * u + 1].y);
                        mma16816(sa[4], q0, qf[u].x, q1, qf[u].y, kf[2 * u + 1].z, kf[2 * u + 1].w);
                        const uint32_t k0 = add_bf16x2(ka[2 * u].x, ka[2 * u + 1].x), k1 = add_bf16x2(ka[2 * u].y, ka[2 * u + 1].y);
                        mma16816(sa[0], q0, qf[u].x, q1, qf[u].y, k0, k1);
                        if (u == 0) SCHED_FENCE();
                    }
                    redo = __any_sync(~0u, or3(orx2(qa[0].x, ka[0].x, tag), orx2(qa[1].x, ka[1].x, tag),
                                               orx(orx(orx2(qa[2].x, ka[2].x, tag), qa[3].x, tag), ka[3].x, tag)) & 1);
#pragma unroll
                    for (int i = 1; i <= 5; i++) sts128(sw + (i % 5) * 512, sa[i % 5][0], sa[i % 5][1], sa[i % 5][2], sa[i % 5][3]);
                } while (redo);
                if (w == 0) TSV(20, n - 1);
            }
            TS(2);
            bar_sync(1, 128);
            float sc[5];
            {
                float x[4][5];
#pragma unroll
                for (int q = 0; q < 4; q++)
#pragma unroll
                    for (int n = 0; n < 5; n++) asm volatile("ld.shared.f32 %0, [%1];" : "=f"(x[q][n]) : "r"(sr + q * 2560 + n * 512) : "memory");
                if (lane == 0) mbar_arrive(bars + 8 * B_SDONE);
#pragma unroll
                for (int n = 0; n < 5; n++) sc[n] = (x[0][n] + x[1][n]) + (x[2][n] + x[3][n]);
            }
            TS(15);
#pragma unroll
            for (int n = 1; n < 5; n++) if (8 * (n - 1) > lim) sc[n] = MASK_VAL;
            float m = fmaxf(fmaxf(fmaxf(sc[0], sc[1]), fmaxf(sc[2], sc[3])), sc[4]);
            m = fmaxf(m, __shfl_xor_sync(~0u, m, 1));
            m = fmaxf(m, __shfl_xor_sync(~0u, m, 4));
            m = fmaxf(m, __shfl_xor_sync(~0u, m, 8));
            SCHED_FENCE();
            uint4 vf[4];
#pragma unroll
            for (int i = 0; i < 4; i++) vf[i] = lds128u(l16 + O_KVQ + 8192 + w * 2048 + i * 512);
            m *= -SM_SCALE_LOG2;
#pragma unroll
            for (int n = 0; n < 5; n++) {
                const uint32_t pv = pack_bf16(ex2(fmaf(sc[n], SM_SCALE_LOG2, m)), 0.f);
                asm volatile("st.shared.u16 [%0], %1;" ::"r"(pw + n * 128), "h"((uint16_t)pv) : "memory");
            }
            KEEP2(vf[0].x, vf[1].x); KEEP2(vf[2].x, vf[3].x);
            SCHED_FENCE();
            bar_sync(1, 128);
            TS(3);
            if (lane == 0) mbar_arrive(bars + 8 * B_SRDY);
            float ox[2][4], sm[4], sx[4], cc[4][4];
            unsigned char *pa, *pb;
#pragma unroll 1
            for (uint32_t nv = 0;; nv++) {
                uint32_t pf[4], p0, px[4], px0;
                ldsm4(pf, l16 + O_P + 128);
                ldsm4(px, l16 + O_P + 128 + 704);
                asm volatile("ld.shared.u32 %0, [%1];" : "=r"(p0) : "r"(l4 + O_P) : "memory");
                asm volatile("ld.shared.u32 %0, [%1];" : "=r"(px0) : "r"(l4 + O_P + 704) : "memory");
                float o[2][4];
#pragma unroll
                for (int i = 0; i < 4; i++) o[0][i] = o[1][i] = ox[0][i] = ox[1][i] = sm[i] = sx[i] = 0.f;
                constexpr uint32_t ONE2 = 0x3f803f80u;
                mma1688(sm, ONE2, ONE2, p0);
                mma1688(sx, ONE2, ONE2, px0);
#pragma unroll
                for (int c = 0; c < 2; c++) {
#pragma unroll
                    for (int u = 0; u < 2; u++) mma16816(o[u], vf[2 * u + c].x, vf[2 * u + c].y, vf[2 * u + c].z, vf[2 * u + c].w, pf[2 * c], pf[2 * c + 1]);
#pragma unroll
                    for (int u = 0; u < 2; u++) mma16816(ox[u], vf[2 * u + c].x, vf[2 * u + c].y, vf[2 * u + c].z, vf[2 * u + c].w, px[2 * c], px[2 * c + 1]);
                    mma16816(sm, ONE2, ONE2, ONE2, ONE2, pf[2 * c], pf[2 * c + 1]);
                    mma16816(sx, ONE2, ONE2, ONE2, ONE2, px[2 * c], px[2 * c + 1]);
                }
                const uint32_t vbad = orx(orx(orx2(vf[0].x, vf[1].x, tg), vf[2].x, tg), vf[3].x, tg);
                uint4 vm;
                {
                    uint32_t n = 0;
                    bool redo;
#pragma unroll 1
                    do {
                        vm = lds128v(l16 + O_VM + w * 512);
                        float o2[2][4];
#pragma unroll
                        for (int i = 0; i < 4; i++) { o2[0][i] = o[0][i]; o2[1][i] = o[1][i]; }
                        mma1688(o2[0], vm.x, vm.y, p0);
                        mma1688(o2[1], vm.z, vm.w, p0);
                        redo = __any_sync(~0u, ((vm.x ^ ~s) & 1) && ++n < SPIN_LIMIT);
                        const uint32_t oa = l4 + O_O + w * 512;
                        sts32(oa, pack_bf16(o2[0][0], o2[0][1]));
                        sts32(oa + 128, pack_bf16(o2[0][2], o2[0][3]));
                        sts32(oa + 256, pack_bf16(o2[1][0], o2[1][1]));
                        sts32(oa + 384, pack_bf16(o2[1][2], o2[1][3]));
                    } while (redo);
                    if (w == 0) TSV(21, n);
                }
                TS(4);
                fence_async_smem();
                mma1688(ox[0], vm.x, vm.y, px0);
                mma1688(ox[1], vm.z, vm.w, px0);
                sm[0] = rcp(sm[0]); sm[1] = rcp(sm[1]);
                bar_sync(1, 128);
                TS(5);
#define OP_ISSUE(t0, t1)                                                                                       \
                wg_fence();                                                                                    \
                _Pragma("unroll") for (int ks = 0; ks < 8; ks++)                                               \
                    _Pragma("unroll") for (int t = t0; t < t1; t++) {                                          \
                        constexpr uint64_t da0 = mkdesc(SM_BASE + O_WO, 16, 1024, 1), db0 = mkdesc(SM_BASE + O_O, 128, 128, 0); \
                        if (ks == 0) wg_ss8<0>(cc[t], da0 + t * 1024, db0); else wg_ss8<1>(cc[t], da0 + t * 1024 + ks * 128, db0 + ks * 16); \
                    }                                                                                          \
                wg_commit();
                OP_ISSUE(0, (OP_SPLIT ? 2 : 4));
                pa = redp + (s & 3) * 32768 + red_grp(j * 16 + (tid >> 3));
                pb = pa + 512 + ((lane >> 3) & 1) * 64 + (lane & 7) * 8;
                pa += (lane & 7) * 16;
                KEEPP(pa); KEEPP(pb);
                SCHED_FENCE();
                if (!bar_or(1, 128, vbad)) break;
                wg_wait<0>();
                const uint4* vp = &g_kvq[((s & 3) * 32 + h) * (3 * 512) + 1024 + w * 128 + lane];
#pragma unroll
                for (int i = 0; i < 4; i++) vf[i] = ldg_rlx128(vp + i * 32);
                if (nv > SPIN_LIMIT) __trap();
                bar_sync(1, 128);
            }
            {
                const float i0 = sm[0], i1 = sm[1];
#pragma unroll
                for (int hf = 0; hf < 2; hf++) {
                    if (hf == 0 || OP_SPLIT) wg_wait<0>();
                    if (hf == 0) TS(6);
                    if (OPD_EARLY && hf == OP_SPLIT && lane == 0) mbar_arrive(bars + 8 * B_OPDONE);
                    asm volatile("red.relaxed.gpu.global.add.noftz.v4.bf16x2 [%0], {%1,%2,%3,%4};" ::"l"(pa + hf * 128),
                                 "r"(pack_bf16(cc[2 * hf][0] * i0, cc[2 * hf][1] * i1)), "r"(pack_bf16(cc[2 * hf][2] * i0, cc[2 * hf][3] * i1)),
                                 "r"(pack_bf16(cc[2 * hf + 1][0] * i0, cc[2 * hf + 1][1] * i1)), "r"(pack_bf16(cc[2 * hf + 1][2] * i0, 1.f)) : "memory");
                    if (OP_SPLIT && hf == 0) { SCHED_FENCE(); OP_ISSUE(2, 4); }
                }
                asm volatile("red.relaxed.gpu.global.add.noftz.v2.bf16x2 [%0], {%1,%2};" ::"l"(pb), "r"(pack_bf16(cc[1][3] * i1, cc[3][3] * i1)), "r"(0x3f800000u) : "memory");
                if (!OPD_EARLY && lane == 0) mbar_arrive(bars + 8 * B_OPDONE);
                SCHED_FENCE();
                TS(7);
            }
            {
                const float ix0 = rcp(sx[0]), ix1 = rcp(sx[1]);
                const uint32_t xo = sb + O_XO + w * 512;
                stsm4t(xo + (lane & 7) * 64 + (((lane >> 3) ^ ((lane >> 1) & 3)) << 4), pack_bf16(ox[0][0] * ix0, ox[0][1] * ix1),
                       pack_bf16(ox[0][2] * ix0, ox[0][3] * ix1), pack_bf16(ox[1][0] * ix0, ox[1][1] * ix1), pack_bf16(ox[1][2] * ix0, ox[1][3] * ix1));
                __syncwarp();
                const uint4 ov = lds128u(xo + (lane >> 2) * 64 + (((lane & 3) ^ ((lane >> 3) & 3)) << 4));
                stg128(&g_ox[(size_t)(s * 32 + j * 8 + (lane >> 2)) * 4096 + h * 128 + w * 32 + (lane & 3) * 8], ov.x, ov.y, ov.z, ov.w);
            }
            TS(8);
            if (s == 0) GT(2);
        }
        GT(3);
        sts32(bars + 508, sf);
        TSDUMP();
        bar_sync(7, 512);
        const int m0 = (role >> 3) * 128, nb = (role & 7) * 2;
#define W2_LOAD(st, kt) { mbar_expect_tx(bars + 8 * (B_GF + (st)), 32768); tma3d(sb + (st) * 32768 + 16384, &tm_w2, 0, (kt) * 64, nb, bars + 8 * (B_GF + (st))); }
        if (w == 1 && lane == 0) {
            fence_async_smem();
#pragma unroll 1
            for (int kt = 0; kt < G_ST; kt++) W2_LOAD(kt, kt);
        }
        if (w == 0) {
            gbar_wait(&g_end, gbar_arrive(&g_end, 1, 128, lane), 0);
            int st = 0, ph = 1;
#pragma unroll 1
            for (int kt = 0; kt < 64; kt++) {
                if (kt >= G_ST) mbar_wait(bars + 8 * (B_GE + st), ph);
                if (lane == 0) {
                    if (kt >= G_ST) W2_LOAD(st, kt);
                    tma2d(sb + st * 32768, &tm_o, kt * 64, m0, bars + 8 * (B_GF + st));
                }
                if (++st == G_ST) { st = 0; ph ^= 1; }
            }
        }
    }
}

typedef CUresult (*EncodeFn)(CUtensorMap*, CUtensorMapDataType, cuuint32_t, void*, const cuuint64_t*, const cuuint64_t*,
                             const cuuint32_t*, const cuuint32_t*, CUtensorMapInterleave, CUtensorMapSwizzle,
                             CUtensorMapL2promotion, CUtensorMapFloatOOBfill);

static void make_map(EncodeFn fn, CUtensorMap* m, const void* p, uint64_t cols, uint64_t rows, uint32_t bc, uint32_t br) {
    cuuint64_t dims[2] = {cols, rows}, strides[1] = {cols * 2};
    cuuint32_t box[2] = {bc, br}, es[2] = {1, 1};
    fn(m, CU_TENSOR_MAP_DATA_TYPE_BFLOAT16, 2, (void*)p, dims, strides, box, es, CU_TENSOR_MAP_INTERLEAVE_NONE,
       CU_TENSOR_MAP_SWIZZLE_128B, CU_TENSOR_MAP_L2_PROMOTION_L2_128B, CU_TENSOR_MAP_FLOAT_OOB_FILL_NONE);
}

static Tune h_tune = {480, 1856, 6, 200, 960, 4000, 300};

extern "C" void kernel_launch(void* const* d_in, const int* in_sizes, int n_in, void* d_out, int out_size) {
    static bool init = false;
    static FftMaps fm;
    static CUtensorMap tm_x, tm_wq, tm_wk, tm_wv, tm_wo, tm_o, tm_wo2;
    if (!init) {
        void* fp = nullptr; cudaDriverEntryPointQueryResult qr;
        cudaGetDriverEntryPoint("cuTensorMapEncodeTiled", &fp, cudaEnableDefault, &qr);
        EncodeFn fn = (EncodeFn)fp;
        void* ox = nullptr; cudaGetSymbolAddress(&ox, g_ox);
        {
            cuuint64_t dims[4] = {64, 8, 16, 256}, strides[3] = {2048, 128, 16384};
            cuuint32_t box[4] = {64, 8, 8, 4}, es[4] = {1, 1, 1, 1};
            fn(&tm_x, CU_TENSOR_MAP_DATA_TYPE_BFLOAT16, 4, d_in[3], dims, strides, box, es, CU_TENSOR_MAP_INTERLEAVE_NONE,
               CU_TENSOR_MAP_SWIZZLE_128B, CU_TENSOR_MAP_L2_PROMOTION_L2_128B, CU_TENSOR_MAP_FLOAT_OOB_FILL_NONE);
        }
        void* fy = nullptr; cudaGetSymbolAddress(&fy, g_fy);
        for (int i = 0; i < 3; i++) {
            const cuuint64_t pitch = i == 2 ? 4096 : 2048;
            cuuint64_t dims[4] = {1024, 8, 16, 16}, strides[3] = {pitch, 128 * pitch, 8 * pitch};
            cuuint32_t box[4] = {64, 1, 16, 16}, es[4] = {1, 1, 1, 1};
            fn(i == 0 ? &fm.x : i == 1 ? &fm.y : &fm.o, CU_TENSOR_MAP_DATA_TYPE_BFLOAT16, 4, i == 0 ? d_in[0] : i == 1 ? fy : d_out, dims, strides, box, es,
               CU_TENSOR_MAP_INTERLEAVE_NONE, CU_TENSOR_MAP_SWIZZLE_128B, CU_TENSOR_MAP_L2_PROMOTION_L2_256B, CU_TENSOR_MAP_FLOAT_OOB_FILL_NONE);
        }
        {
            cuuint64_t dims[3] = {64, 2048, 16}, strides[2] = {2048, 128};
            cuuint32_t box[3] = {64, 8, 16}, es[3] = {1, 1, 1};
            fn(&fm.y2, CU_TENSOR_MAP_DATA_TYPE_BFLOAT16, 3, fy, dims, strides, box, es, CU_TENSOR_MAP_INTERLEAVE_NONE,
               CU_TENSOR_MAP_SWIZZLE_128B, CU_TENSOR_MAP_L2_PROMOTION_L2_128B, CU_TENSOR_MAP_FLOAT_OOB_FILL_NONE);
        }
        for (int i = 0; i < 2; i++) {
            cuuint64_t dims[3] = {256 * 513 - 448, 8, 8}, strides[2] = {128, 256 * 1026};
            cuuint32_t box[3] = {72, 8, 8}, es[3] = {1, 1, 1};
            fn(i ? &fm.wi : &fm.wr, CU_TENSOR_MAP_DATA_TYPE_BFLOAT16, 3, d_in[1 + i], dims, strides, box, es, CU_TENSOR_MAP_INTERLEAVE_NONE,
               CU_TENSOR_MAP_SWIZZLE_NONE, CU_TENSOR_MAP_L2_PROMOTION_L2_128B, CU_TENSOR_MAP_FLOAT_OOB_FILL_NONE);
        }
        make_map(fn, &tm_wq, d_in[5], 4096, 1024, 64, 256);
        make_map(fn, &tm_wk, d_in[6], 4096, 1024, 64, 256);
        make_map(fn, &tm_wv, d_in[7], 4096, 1024, 64, 256);
        make_map(fn, &tm_wo, d_in[8], 1024, 4096, 64, 128);
        make_map(fn, &tm_o, ox, 4096, 2048, 64, 128);
        {
            cuuint64_t dims[3] = {64, 4096, 16}, strides[2] = {2048, 128};
            cuuint32_t box[3] = {64, 64, 2}, es[3] = {1, 1, 1};
            fn(&tm_wo2, CU_TENSOR_MAP_DATA_TYPE_BFLOAT16, 3, d_in[8], dims, strides, box, es, CU_TENSOR_MAP_INTERLEAVE_NONE,
               CU_TENSOR_MAP_SWIZZLE_128B, CU_TENSOR_MAP_L2_PROMOTION_L2_128B, CU_TENSOR_MAP_FLOAT_OOB_FILL_NONE);
        }
        cudaFuncSetAttribute(rmt_main, cudaFuncAttributeMaxDynamicSharedMemorySize, MAIN_SMEM);
        init = true;
    }
    rmt_main<<<132, 512, MAIN_SMEM>>>(tm_x, tm_wq, tm_wk, tm_wv, tm_wo, (const bf16*)d_in[4], h_tune, fm, tm_o, tm_wo2, (bf16*)d_out);
}
```

```cpp
#include <cuda_runtime.h>
#include <cuda_bf16.h>
#include <cuda.h>
#include <stdint.h>

typedef __nv_bfloat16 bf16;

#define DBG_TIMING 0

#define SPIN_LIMIT (1u << 22)

__device__ __forceinline__ uint32_t smem_u32(const void* p) { return (uint32_t)__cvta_generic_to_shared(p); }
__device__ __forceinline__ uint32_t clk() { uint32_t c; asm volatile("mov.u32 %0, %%clock;" : "=r"(c)::"memory"); return c; }
#define SCHED_FENCE() sf ^= (uint32_t)clock64()
#define KEEP2(a, b) asm volatile("lop3.b32 %0, %0, %1, %2, 0x96;" : "+r"(sf) : "r"((uint32_t)(a)), "r"((uint32_t)(b)))
#define KEEPP(p) KEEP2((uintptr_t)(p), (uintptr_t)(p) >> 32)
__device__ __forceinline__ uint32_t gtime() { uint32_t c; asm volatile("mov.u32 %0, %%globaltimer_lo;" : "=r"(c)::"memory"); return c; }
__device__ __forceinline__ void wait_clk(uint32_t t0, uint32_t d) {
    asm volatile("{\n.reg .pred p;\n.reg .s32 t;\n.reg .b64 c;\nWL:\nmov.u64 c, %%clock64;\ncvt.u32.u64 t, c;\nsub.s32 t, t, %0;\nsetp.lt.s32 p, t, 0;\n@p bra.uni WL;\n}" ::"r"(t0 + d) : "memory");
}
__device__ __forceinline__ void wait_gtime(uint32_t t1) {
    asm volatile("{\n.reg .pred p;\n.reg .s32 t;\n.reg .b64 c;\nWL:\nmov.u64 c, %%globaltimer;\ncvt.u32.u64 t, c;\nsub.s32 t, t, %0;\nsetp.lt.s32 p, t, 0;\n@p bra.uni WL;\n}" ::"r"(t1) : "memory");
}

__device__ __forceinline__ void mbar_init(uint32_t bar, uint32_t cnt) {
    asm volatile("mbarrier.init.shared::cta.b64 [%0], %1;" ::"r"(bar), "r"(cnt) : "memory");
}
__device__ __forceinline__ void mbar_arrive(uint32_t bar) {
    asm volatile("mbarrier.arrive.shared::cta.b64 _, [%0];" ::"r"(bar) : "memory");
}
__device__ __forceinline__ void mbar_expect_tx(uint32_t bar, uint32_t bytes) {
    asm volatile("mbarrier.arrive.expect_tx.shared::cta.b64 _, [%0], %1;" ::"r"(bar), "r"(bytes) : "memory");
}
__device__ __forceinline__ void mbar_wait(uint32_t bar, uint32_t parity) {
    asm volatile(
        "{\n.reg .pred p, q;\n.reg .u32 n;\nmov.u32 n, 0;\n"
        "WL:\nmbarrier.try_wait.parity.shared::cta.b64 p, [%0], %1;\n"
        "add.u32 n, n, 1;\nsetp.gt.u32 q, n, %2;\n@q trap;\n@!p bra.uni WL;\n}" ::"r"(bar), "r"(parity), "n"(SPIN_LIMIT) : "memory");
}
__device__ __forceinline__ void mbar_wait_cluster(uint32_t bar, uint32_t parity) {
    asm volatile(
        "{\n.reg .pred p, q;\n.reg .u32 n;\nmov.u32 n, 0;\n"
        "WL:\nmbarrier.try_wait.parity.acquire.cluster.shared::cta.b64 p, [%0], %1;\n"
        "add.u32 n, n, 1;\nsetp.gt.u32 q, n, %2;\n@q trap;\n@!p bra.uni WL;\n}" ::"r"(bar), "r"(parity), "n"(SPIN_LIMIT) : "memory");
}
__device__ __forceinline__ void tma2d(uint32_t dst, const CUtensorMap* m, int c0, int c1, uint32_t bar) {
    asm volatile("cp.async.bulk.tensor.2d.shared::cluster.global.mbarrier::complete_tx::bytes [%0], [%1, {%3, %4}], [%2];"
                 ::"r"(dst), "l"(m), "r"(bar), "r"(c0), "r"(c1) : "memory");
}
__device__ __forceinline__ void tma3d(uint32_t dst, const CUtensorMap* m, int c0, int c1, int c2, uint32_t bar) {
    asm volatile("cp.async.bulk.tensor.3d.shared::cluster.global.mbarrier::complete_tx::bytes [%0], [%1, {%3, %4, %5}], [%2];"
                 ::"r"(dst), "l"(m), "r"(bar), "r"(c0), "r"(c1), "r"(c2) : "memory");
}
__device__ __forceinline__ void tma4d(uint32_t dst, const CUtensorMap* m, int c2, int c3, uint32_t bar) {
    asm volatile("cp.async.bulk.tensor.4d.shared::cluster.global.mbarrier::complete_tx::bytes [%0], [%1, {%5, %5, %3, %4}], [%2];"
                 ::"r"(dst), "l"(m), "r"(bar), "r"(c2), "r"(c3), "r"(0) : "memory");
}
__device__ __forceinline__ void bulk_g2s(uint32_t dst, const void* src, uint32_t bytes, uint32_t bar) {
    asm volatile("cp.async.bulk.shared::cluster.global.mbarrier::complete_tx::bytes [%0], [%1], %2, [%3];"
                 ::"r"(dst), "l"(src), "r"(bytes), "r"(bar) : "memory");
}
__device__ __forceinline__ void tma4d_prefetch(const CUtensorMap* m, int c2, int c3) {
    asm volatile("cp.async.bulk.prefetch.tensor.4d.L2.global [%0, {%3, %3, %1, %2}];" ::"l"(m), "r"(c2), "r"(c3), "r"(0) : "memory");
}
__device__ __forceinline__ void tma2d_prefetch(const CUtensorMap* m, int c0, int c1) {
    asm volatile("cp.async.bulk.prefetch.tensor.2d.L2.global [%0, {%1, %2}];" ::"l"(m), "r"(c0), "r"(c1) : "memory");
}
__device__ __forceinline__ void fence_async_smem() { asm volatile("fence.proxy.async.shared::cta;" ::: "memory"); }
__device__ __forceinline__ void fence_gpu() { asm volatile("fence.acq_rel.gpu;" ::: "memory"); }
__device__ __forceinline__ float rcp(float x) { float r; asm("rcp.approx.ftz.f32 %0, %1;" : "=f"(r) : "f"(x)); return r; }
__device__ __forceinline__ void bar_sync(int id, int n) { asm volatile("bar.sync %0, %1;" ::"r"(id), "r"(n) : "memory"); }

__device__ __forceinline__ bool bar_or(int id, int n, uint32_t x) {
    uint32_t r;
    asm volatile("{\n.reg .pred p, q;\n.reg .b32 t;\nand.b32 t, %3, 1;\nsetp.ne.u32 p, t, 0;\nbar.red.or.pred q, %1, %2, p;\nselp.u32 %0, 1, 0, q;\n}"
                 : "=r"(r) : "r"(id), "r"(n), "r"(x) : "memory");
    return __any_sync(~0u, r);
}
__device__ __forceinline__ uint32_t or3(uint32_t a, uint32_t b, uint32_t c) {
    uint32_t r; asm("lop3.b32 %0, %1, %2, %3, 0xFE;" : "=r"(r) : "r"(a), "r"(b), "r"(c)); return r;
}
__device__ __forceinline__ uint32_t pack_bf16(float lo, float hi) {
    uint32_t r; asm("cvt.rn.bf16x2.f32 %0, %1, %2;" : "=r"(r) : "f"(hi), "f"(lo)); return r;
}
__device__ __forceinline__ uint32_t add_bf16x2(uint32_t a, uint32_t b) {
    uint32_t r; asm volatile("add.rn.bf16x2 %0, %1, %2;" : "=r"(r) : "r"(a), "r"(b)); return r;
}
__device__ __forceinline__ uint32_t movm(uint32_t a) {
    uint32_t r; asm volatile("movmatrix.sync.aligned.m8n8.trans.b16 %0, %1;" : "=r"(r) : "r"(a)); return r;
}
__device__ __forceinline__ uint32_t orx(uint32_t acc, uint32_t a, uint32_t t) {
    uint32_t r; asm("lop3.b32 %0, %1, %2, %3, 0xF6;" : "=r"(r) : "r"(acc), "r"(a), "r"(t)); return r;
}
__device__ __forceinline__ uint32_t orx2(uint32_t a, uint32_t b, uint32_t t) {
    uint32_t r; asm("lop3.b32 %0, %1, %2, %3, 0x7E;" : "=r"(r) : "r"(a), "r"(b), "r"(t)); return r;
}
__device__ __forceinline__ float ex2(float x) { float r; asm("ex2.approx.ftz.f32 %0, %1;" : "=f"(r) : "f"(x)); return r; }
__device__ __forceinline__ void ldsm4t(uint32_t (&r)[4], uint32_t a) {
    asm volatile("ldmatrix.sync.aligned.m8n8.x4.trans.shared.b16 {%0,%1,%2,%3}, [%4];"
                 : "=r"(r[0]), "=r"(r[1]), "=r"(r[2]), "=r"(r[3]) : "r"(a) : "memory");
}
__device__ __forceinline__ void ldsm4(uint32_t (&r)[4], uint32_t a) {
    asm volatile("ldmatrix.sync.aligned.m8n8.x4.shared.b16 {%0,%1,%2,%3}, [%4];"
                 : "=r"(r[0]), "=r"(r[1]), "=r"(r[2]), "=r"(r[3]) : "r"(a) : "memory");
}
__device__ __forceinline__ void stsm4t(uint32_t a, uint32_t r0, uint32_t r1, uint32_t r2, uint32_t r3) {
    asm volatile("stmatrix.sync.aligned.m8n8.x4.trans.shared.b16 [%0], {%1,%2,%3,%4};"
                 ::"r"(a), "r"(r0), "r"(r1), "r"(r2), "r"(r3) : "memory");
}
__device__ __forceinline__ void stsm4(uint32_t a, uint32_t r0, uint32_t r1, uint32_t r2, uint32_t r3) {
    asm volatile("stmatrix.sync.aligned.m8n8.x4.shared.b16 [%0], {%1,%2,%3,%4};"
                 ::"r"(a), "r"(r0), "r"(r1), "r"(r2), "r"(r3) : "memory");
}
__device__ __forceinline__ void mma16816(float* c, uint32_t a0, uint32_t a1, uint32_t a2, uint32_t a3, uint32_t b0, uint32_t b1) {
    asm volatile("mma.sync.aligned.m16n8k16.row.col.f32.bf16.bf16.f32 {%0,%1,%2,%3}, {%4,%5,%6,%7}, {%8,%9}, {%0,%1,%2,%3};"
                 : "+f"(c[0]), "+f"(c[1]), "+f"(c[2]), "+f"(c[3]) : "r"(a0), "r"(a1), "r"(a2), "r"(a3), "r"(b0), "r"(b1));
}
__device__ __forceinline__ void mma1688(float* c, uint32_t a0, uint32_t a1, uint32_t b0) {
    asm volatile("mma.sync.aligned.m16n8k8.row.col.f32.bf16.bf16.f32 {%0,%1,%2,%3}, {%4,%5}, {%6}, {%0,%1,%2,%3};"
                 : "+f"(c[0]), "+f"(c[1]), "+f"(c[2]), "+f"(c[3]) : "r"(a0), "r"(a1), "r"(b0));
}
__device__ __forceinline__ void sts128(uint32_t a, float x, float y, float z, float w) {
    asm volatile("st.shared.v4.f32 [%0], {%1,%2,%3,%4};" ::"r"(a), "f"(x), "f"(y), "f"(z), "f"(w) : "memory");
}
__device__ __forceinline__ void sts64(uint32_t a, float x, float y) {
    asm volatile("st.shared.v2.f32 [%0], {%1,%2};" ::"r"(a), "f"(x), "f"(y) : "memory");
}
__device__ __forceinline__ void sts32(uint32_t a, uint32_t x) { asm volatile("st.shared.b32 [%0], %1;" ::"r"(a), "r"(x) : "memory"); }
__device__ __forceinline__ void sts128u(uint32_t a, uint4 v) {
    asm volatile("st.shared.v4.b32 [%0], {%1,%2,%3,%4};" ::"r"(a), "r"(v.x), "r"(v.y), "r"(v.z), "r"(v.w) : "memory");
}
__device__ __forceinline__ float4 lds128(uint32_t a) {
    float4 v; asm volatile("ld.shared.v4.f32 {%0,%1,%2,%3}, [%4];" : "=f"(v.x), "=f"(v.y), "=f"(v.z), "=f"(v.w) : "r"(a) : "memory"); return v;
}
__device__ __forceinline__ uint4 lds128u(uint32_t a) {
    uint4 v; asm volatile("ld.shared.v4.b32 {%0,%1,%2,%3}, [%4];" : "=r"(v.x), "=r"(v.y), "=r"(v.z), "=r"(v.w) : "r"(a) : "memory"); return v;
}
__device__ __forceinline__ uint4 lds128v(uint32_t a) {
    uint4 v; asm volatile("ld.volatile.shared.v4.b32 {%0,%1,%2,%3}, [%4];" : "=r"(v.x), "=r"(v.y), "=r"(v.z), "=r"(v.w) : "r"(a) : "memory"); return v;
}
__device__ __forceinline__ void sts64u(uint32_t a, uint2 v) { asm volatile("st.shared.v2.b32 [%0], {%1,%2};" ::"r"(a), "r"(v.x), "r"(v.y) : "memory"); }
__device__ __forceinline__ uint2 lds64u(uint32_t a) {
    uint2 v; asm volatile("ld.shared.v2.b32 {%0,%1}, [%2];" : "=r"(v.x), "=r"(v.y) : "r"(a) : "memory"); return v;
}
__device__ __forceinline__ float2 lds64(uint32_t a) {
    float2 v; asm volatile("ld.shared.v2.f32 {%0,%1}, [%2];" : "=f"(v.x), "=f"(v.y) : "r"(a) : "memory"); return v;
}
__device__ __forceinline__ uint2 ldg_rlx64(const void* p) {
    uint2 v; asm volatile("ld.relaxed.gpu.global.v2.b32 {%0,%1}, [%2];" : "=r"(v.x), "=r"(v.y) : "l"(p) : "memory"); return v;
}
__device__ __forceinline__ uint4 ldg_rlx128(const void* p) {
    uint4 v; asm volatile("ld.relaxed.gpu.global.v4.b32 {%0,%1,%2,%3}, [%4];" : "=r"(v.x), "=r"(v.y), "=r"(v.z), "=r"(v.w) : "l"(p) : "memory"); return v;
}
__device__ __forceinline__ void stg_rlx64(void* p, uint32_t x, uint32_t y) {
    asm volatile("st.relaxed.gpu.global.v2.b32 [%0], {%1,%2};" ::"l"(p), "r"(x), "r"(y) : "memory");
}
__device__ __forceinline__ void stg_rlx128(void* p, uint32_t x, uint32_t y, uint32_t z, uint32_t w) {
    asm volatile("st.relaxed.gpu.global.v4.b32 [%0], {%1,%2,%3,%4};" ::"l"(p), "r"(x), "r"(y), "r"(z), "r"(w) : "memory");
}
__device__ __forceinline__ uint32_t ldg_rlx32(const void* p) {
    uint32_t v; asm volatile("ld.relaxed.gpu.global.b32 %0, [%1];" : "=r"(v) : "l"(p) : "memory"); return v;
}
__device__ __forceinline__ void stg128(void* p, uint32_t x, uint32_t y, uint32_t z, uint32_t w) {
    asm volatile("st.global.v4.b32 [%0], {%1,%2,%3,%4};" ::"l"(p), "r"(x), "r"(y), "r"(z), "r"(w) : "memory");
}
__device__ __forceinline__ uint32_t ld_acquire(const unsigned* p) {
    uint32_t v; asm volatile("ld.acquire.gpu.global.u32 %0, [%1];" : "=r"(v) : "l"(p) : "memory"); return v;
}
__device__ __forceinline__ void red_add_u32(unsigned* p, uint32_t v) {
    asm volatile("red.relaxed.gpu.global.add.u32 [%0], %1;" ::"l"(p), "r"(v) : "memory");
}
__device__ __forceinline__ void wait_counter(const unsigned* p, uint32_t target) {
    uint32_t n = 0;
    while (ld_acquire(p) < target) { if (++n > SPIN_LIMIT) __trap(); }
}

__device__ __forceinline__ void wg_fence() { asm volatile("wgmma.fence.sync.aligned;" ::: "memory"); }
__device__ __forceinline__ void wg_commit() { asm volatile("wgmma.commit_group.sync.aligned;" ::: "memory"); }
template <int N> __device__ __forceinline__ void wg_wait() { asm volatile("wgmma.wait_group.sync.aligned %0;" ::"n"(N) : "memory"); }
__host__ __device__ constexpr uint64_t mkdesc(uint32_t addr, uint32_t lbo, uint32_t sbo, uint32_t swz) {
    return (uint64_t)((addr & 0x3FFFF) >> 4) | ((uint64_t)(lbo >> 4) << 16) | ((uint64_t)(sbo >> 4) << 32) | ((uint64_t)swz << 62);
}
#define F4(d, o) "+f"(d[o]), "+f"(d[o + 1]), "+f"(d[o + 2]), "+f"(d[o + 3])
template <int SC> __device__ __forceinline__ void wg_rs32(float (&d)[16], const uint32_t (&a)[4], uint64_t db) {
    asm volatile("wgmma.mma_async.sync.aligned.m64n32k16.f32.bf16.bf16 "
                 "{%0,%1,%2,%3,%4,%5,%6,%7,%8,%9,%10,%11,%12,%13,%14,%15}, {%16,%17,%18,%19}, %20, %21, 1, 1, 0;"
                 : F4(d, 0), F4(d, 4), F4(d, 8), F4(d, 12)
                 : "r"(a[0]), "r"(a[1]), "r"(a[2]), "r"(a[3]), "l"(db), "n"(SC));
}
template <int SC> __device__ __forceinline__ void wg_rs40(float (&d)[20], const uint32_t (&a)[4], uint64_t db) {
    asm volatile("wgmma.mma_async.sync.aligned.m64n40k16.f32.bf16.bf16 "
                 "{%0,%1,%2,%3,%4,%5,%6,%7,%8,%9,%10,%11,%12,%13,%14,%15,%16,%17,%18,%19}, {%20,%21,%22,%23}, %24, %25, 1, 1, 0;"
                 : F4(d, 0), F4(d, 4), F4(d, 8), F4(d, 12), F4(d, 16)
                 : "r"(a[0]), "r"(a[1]), "r"(a[2]), "r"(a[3]), "l"(db), "n"(SC));
}
template <int SC> __device__ __forceinline__ void wg_ss40(float (&d)[20], uint64_t da, uint64_t db) {
    asm volatile("wgmma.mma_async.sync.aligned.m64n40k16.f32.bf16.bf16 "
                 "{%0,%1,%2,%3,%4,%5,%6,%7,%8,%9,%10,%11,%12,%13,%14,%15,%16,%17,%18,%19}, %20, %21, %22, 1, 1, 1, 0;"
                 : F4(d, 0), F4(d, 4), F4(d, 8), F4(d, 12), F4(d, 16)
                 : "l"(da), "l"(db), "n"(SC));
}
template <int SC> __device__ __forceinline__ void wg_ss8(float (&d)[4], uint64_t da, uint64_t db) {
    asm volatile("wgmma.mma_async.sync.aligned.m64n8k16.f32.bf16.bf16 {%0,%1,%2,%3}, %4, %5, %6, 1, 1, 1, 1;"
                 : F4(d, 0) : "l"(da), "l"(db), "n"(SC));
}

constexpr int DBG_N = 12;
#define TSI(st) do {} while (0)
#define TS(k) do {} while (0)
#define TSV(k, v) do {} while (0)
#define TSDUMP() do {} while (0)
#define GT(k) do {} while (0)

__device__ __align__(256) uint4 g_fy[2048 * 128];

constexpr uint32_t FG_SIZE = 2 * 32768 + 36864;
constexpr uint32_t FT_F16 = 2 * FG_SIZE, FT_B1F = FT_F16 + 2048, FT_B1I = FT_B1F + 2048, FT_C = FT_B1I + 2048, FT_A8 = FT_C + 2048,
                   FT_TWC = FT_A8 + 512, FT_TWB = FT_TWC + 8192, FT_BAR = FT_TWB + 8192, FFT_SMEM = FT_BAR + 256;
struct FftMaps { CUtensorMap x, y, o, y2, wr, wi; };

__device__ __forceinline__ float2 wroot(int e) {
    float s, c; sincospif((float)(e & 2047) * (-1.f / 1024.f), &s, &c); return make_float2(c, s);
}
__device__ __forceinline__ uint4 afrag(float2 a, float2 b) {
    return make_uint4(pack_bf16(a.x, -a.y), pack_bf16(a.y, a.x), pack_bf16(b.x, -b.y), pack_bf16(b.y, b.x));
}
__device__ __forceinline__ uint4 conjfrag(uint4 v) { return make_uint4(v.x ^ 0x80000000u, v.y ^ 0x8000u, v.z ^ 0x80000000u, v.w ^ 0x8000u); }
__device__ __forceinline__ uint4 negfrag(uint4 v) { return make_uint4(v.x ^ 0x80008000u, v.y ^ 0x80008000u, v.z ^ 0x80008000u, v.w ^ 0x80008000u); }
__device__ __forceinline__ uint32_t comp(const uint4& v, int i) { return i == 0 ? v.x : i == 1 ? v.y : i == 2 ? v.z : v.w; }
__device__ __forceinline__ void setcomp(uint4& v, int i, uint32_t x) { if (i == 0) v.x = x; else if (i == 1) v.y = x; else if (i == 2) v.z = x; else v.w = x; }
__device__ __forceinline__ float2 cmul(float2 a, float2 b) { return make_float2(a.x * b.x - a.y * b.y, a.x * b.y + a.y * b.x); }
__device__ __forceinline__ float2 cmulc(float2 a, float2 b) { return make_float2(a.x * b.x + a.y * b.y, a.y * b.x - a.x * b.y); }

__device__ __forceinline__ uint32_t pack_h2(float2 a) { uint32_t r; asm("cvt.rn.f16x2.f32 %0, %1, %2;" : "=r"(r) : "f"(a.y), "f"(a.x)); return r; }
__device__ __forceinline__ float2 unpack_h2(uint32_t v) {
    float2 r; asm("{\n.reg .b16 l, h;\nmov.b32 {l, h}, %2;\ncvt.f32.f16 %0, l;\ncvt.f32.f16 %1, h;\n}" : "=f"(r.x), "=f"(r.y) : "r"(v)); return r;
}
__device__ __forceinline__ void fft_tables(uint32_t tb, int tid, int nthr) {
    for (int i = tid; i < 128; i += nthr) {
        const int lane = i & 31, q = i >> 5, g = lane >> 2, t = lane & 3, o = 8 * (q >> 1) + g, in = 8 * (q & 1) + 2 * t;
        sts128u(tb + FT_F16 + i * 16, afrag(wroot(128 * o * in), wroot(128 * o * (in + 1))));
        sts128u(tb + FT_B1F + i * 16, afrag(wroot(64 * (1 + 2 * o) * in), wroot(64 * (1 + 2 * o) * (in + 1))));
        sts128u(tb + FT_B1I + i * 16, afrag(wroot(-64 * o * (1 + 2 * in)), wroot(-64 * o * (3 + 2 * in))));
        uint4 v;
        for (int r = 0; r < 4; r++) {
            const float2 a = wroot(128 * (4 * r + t) * (4 * q + (g >> 1)));
            setcomp(v, r, (g & 1) ? pack_bf16(a.y, a.x) : pack_bf16(a.x, -a.y));
        }
        sts128u(tb + FT_C + i * 16, v);
        if (q == 0) sts128u(tb + FT_A8 + lane * 16, afrag(wroot(256 * g * 2 * t), wroot(256 * g * (2 * t + 1))));
    }
    for (int i = tid; i < 512; i += nthr) {
        const int lane = i & 31, r = (i >> 5) & 3, phi = 8 * (i >> 7) + (lane >> 2), c = 4 * r + (lane & 3);
        const float2 a = wroot(4 * c * phi), b = wroot(2 * (phi + 32 * c));
        constexpr float SC = 1.f / (2.f * 2048.f * 512.f);
        sts128(tb + FT_TWC + i * 16, a.x * SC, a.y * SC, b.x, b.y);
    }
    for (int i = tid; i < 512; i += nthr) {
        const int lane = i & 31, r = (i >> 5) & 3, fa = (i >> 7) & 1, hf = i >> 8, c = 8 * (lane & 1) + r;
        const int p0 = fa + 2 * (lane >> 2), p1 = p0 + 16, s0 = (hf && p0) ? 32 - p0 : p0, s1 = hf ? 32 - p1 : p1;
        sts128u(tb + FT_TWB + i * 16, make_uint4(pack_h2(wroot(4 * c * s0)), pack_h2(wroot(4 * (c + 4) * s0)),
                                                 pack_h2(wroot(4 * c * s1)), pack_h2(wroot(4 * (c + 4) * s1))));
    }
}

template <bool TW>
__device__ __forceinline__ void dft16(uint4 (&out)[4], const uint4 (&in)[4], const uint4 (&m)[4], const uint4 (&tw)[4]) {
#pragma unroll
    for (int i = 0; i < 4; i++)
#pragma unroll
        for (int mt = 0; mt < 2; mt++) {
            float c[4] = {0.f, 0.f, 0.f, 0.f};
            mma16816(c, m[2 * mt].x, m[2 * mt].y, m[2 * mt].z, m[2 * mt].w, comp(in[0], i), comp(in[1], i));
            mma16816(c, m[2 * mt + 1].x, m[2 * mt + 1].y, m[2 * mt + 1].z, m[2 * mt + 1].w, comp(in[2], i), comp(in[3], i));
            if (TW) {
                const float2 a = cmul(make_float2(c[0], c[2]), unpack_h2(comp(tw[i], 2 * mt))), b = cmul(make_float2(c[1], c[3]), unpack_h2(comp(tw[i], 2 * mt + 1)));
                setcomp(out[2 * mt], i, pack_bf16(a.x, a.y));
                setcomp(out[2 * mt + 1], i, pack_bf16(b.x, b.y));
            } else {
                setcomp(out[2 * mt], i, pack_bf16(c[0], c[2]));
                setcomp(out[2 * mt + 1], i, pack_bf16(c[1], c[3]));
            }
        }
}
__device__ __forceinline__ void tma_ld4(uint32_t dst, const CUtensorMap* m, int c0, int c1, uint32_t bar) {
    asm volatile("cp.async.bulk.tensor.4d.shared::cluster.global.mbarrier::complete_tx::bytes [%0], [%1, {%3, %4, %5, %5}], [%2];"
                 ::"r"(dst), "l"(m), "r"(bar), "r"(c0), "r"(c1), "r"(0) : "memory");
}
__device__ __forceinline__ void tma_st4(uint32_t src, const CUtensorMap* m, int c0, int c1) {
    asm volatile("cp.async.bulk.tensor.4d.global.shared::cta.bulk_group [%1, {%2, %3, %4, %4}], [%0];" ::"r"(src), "l"(m), "r"(c0), "r"(c1), "r"(0) : "memory");
}
__device__ __forceinline__ void tma_ld3(uint32_t dst, const CUtensorMap* m, int c0, int c1, uint32_t bar) {
    asm volatile("cp.async.bulk.tensor.3d.shared::cluster.global.mbarrier::complete_tx::bytes [%0], [%1, {%3, %4, %5}], [%2];"
                 ::"r"(dst), "l"(m), "r"(bar), "r"(c0), "r"(c1), "r"(0) : "memory");
}
__device__ __forceinline__ void tma_st3(uint32_t src, const CUtensorMap* m, int c0, int c1) {
    asm volatile("cp.async.bulk.tensor.3d.global.shared::cta.bulk_group [%1, {%2, %3, %4}], [%0];" ::"r"(src), "l"(m), "r"(c0), "r"(c1), "r"(0) : "memory");
}
__device__ __forceinline__ void bulk_commit() { asm volatile("cp.async.bulk.commit_group;" ::: "memory"); }
__device__ __forceinline__ void bulk_wait_read() { asm volatile("cp.async.bulk.wait_group.read 0;" ::: "memory"); }
__device__ __forceinline__ void bulk_wait_all() { asm volatile("cp.async.bulk.wait_group 0;" ::: "memory"); }

__device__ __forceinline__ float2 wroot_fast(int e) {
    float s, c; __sincosf((float)(((e + 1024) & 2047) - 1024) * (-3.14159265358979f / 1024.f), &s, &c); return make_float2(c, s);
}
template <bool INV, int NT>
__device__ __forceinline__ void fft_col(int s2, int t0, const CUtensorMap* src, const CUtensorMap* dst, uint32_t gb, uint32_t mb,
                                        int w, int lane, int bar) {
    const int g = lane >> 2, t = lane & 3;
    const bool lead = w == 4 && lane == 0;
    if (NT > 1 && lead)
        for (int i = 0; i < 2; i++) { mbar_expect_tx(mb + 8 * i, 32768); tma_ld4(gb + i * 32768, src, (t0 + i) * 64, s2, mb + 8 * i); }
    uint4 f[4], m[2][4];
#pragma unroll
    for (int i = 0; i < 4; i++) {
        const int o = 8 * (i >> 1) + g, in = 8 * (i & 1) + 2 * t, sg = INV ? -128 : 128;
        f[i] = afrag(wroot_fast(sg * o * in), wroot_fast(sg * o * (in + 1)));
#pragma unroll
        for (int q = 0; q < 2; q++) {
            const int z = 2 * w + q;
            m[q][i] = INV ? afrag(wroot_fast(-(8 * o + s2) * (z + 16 * in)), wroot_fast(-(8 * o + s2) * (z + 16 * in + 16)))
                          : afrag(wroot_fast((z + 16 * o) * (8 * in + s2)), wroot_fast((z + 16 * o) * (8 * in + 8 + s2)));
        }
    }
    const uint32_t r1 = (32 * w + 2 * t) * 128 + ((g ^ (2 * t)) << 4);
    const uint32_t w1 = (32 * w + g) * 128 + (((2 * t) ^ (((w & 3) << 1) | (g & 1))) << 4);
    const uint32_t r2 = (32 * t + 2 * w) * 128 + ((g ^ (2 * t)) << 4);
    const uint32_t w2 = (32 * w + g) * 128 + (((2 * t) ^ g) << 4);
    int bi = 0, ph = 0;
#pragma unroll 1
    for (int it = 0; it < NT; it++) {
        const uint32_t buf = gb + bi * 32768;
        mbar_wait(mb + 8 * bi, ph);
        uint4 in[2][4], out[4];
#pragma unroll
        for (int q = 0; q < 2; q++)
#pragma unroll
            for (int i = 0; i < 4; i++) in[q][i] = lds128u(buf + (r1 ^ ((i & 1) * 0x90)) + (i >> 1) * 1024 + q * 2048);
        __syncwarp();
#pragma unroll
        for (int q = 0; q < 2; q++) {
            if (INV) dft16<false>(out, in[q], m[q], f); else dft16<false>(out, in[q], f, f);
#pragma unroll
            for (int i = 0; i < 4; i++) sts128u(buf + (w1 ^ ((i & 1) << 4)) + (i >> 1) * 1024 + q * 2048, out[i]);
        }
        bar_sync(bar, 256);
#pragma unroll
        for (int q = 0; q < 2; q++)
#pragma unroll
            for (int i = 0; i < 4; i++) in[q][i] = lds128u(buf + (r2 ^ (q * 0x90)) + (i & 1) * 2048 + (i >> 1) * 16384);
        const int bn = bi == 0 ? 2 : bi - 1;
        if (lead && it < NT - 2) { bulk_wait_read(); mbar_expect_tx(mb + 8 * bn, 32768); tma_ld4(gb + bn * 32768, src, (t0 + it + 2) * 64, s2, mb + 8 * bn); }
        bar_sync(bar, 256);
#pragma unroll
        for (int q = 0; q < 2; q++) {
            if (INV) dft16<false>(out, in[q], f, f); else dft16<false>(out, in[q], m[q], f);
#pragma unroll
            for (int i = 0; i < 4; i++) sts128u(buf + (w2 ^ ((i & 1) << 4)) + (i >> 1) * 1024 + q * 2048, out[i]);
        }
        fence_async_smem();
        bar_sync(bar, 256);
        if (NT > 1 && lead) { tma_st4(buf, dst, (t0 + it) * 64, s2); bulk_commit(); }
        if (++bi == 3) { bi = 0; ph ^= 1; }
    }
    if (NT > 1 && lead) bulk_wait_read();
}

__device__ __forceinline__ float ldw(uint32_t a) {
    uint16_t v; asm volatile("ld.shared.u16 %0, [%1];" : "=h"(v) : "r"(a) : "memory");
    return __uint_as_float((uint32_t)v << 16);
}
__device__ __forceinline__ void fft_mid(int grp, const FftMaps& fm, uint32_t tb,
                                        uint32_t gb, uint32_t mb, uint32_t& cnt, int w, int lane, int bar) {
    const int g = lane >> 2, t = lane & 3;
    const bool lead = w == 4 && lane == 0;
    const uint32_t wb = gb + 65536;
#define MID_LOAD(k, c)                                                                                                  \
    { mbar_expect_tx(mb + 8 * ((c) & 1), 32768);                                                                        \
      tma_ld3(gb + ((c) & 1) * 32768, &fm.y2, 0, (k) * 8, mb + 8 * ((c) & 1));                                          \
      tma_ld3(gb + ((c) & 1) * 32768 + 16384, &fm.y2, 0, ((256 - (k)) & 255) * 8, mb + 8 * ((c) & 1)); }
#define MID_LOADW(k)                                                                                                    \
    { mbar_expect_tx(mb + 16, 36864);                                                                                   \
      tma_ld3(wb, &fm.wr, (k) * 513 & ~7, 0, mb + 16); tma_ld3(wb + 9216, &fm.wi, (k) * 513 & ~7, 0, mb + 16);          \
      tma_ld3(wb + 18432, &fm.wr, ((256 - (k)) & 255) * 513 & ~7, 0, mb + 16); tma_ld3(wb + 27648, &fm.wi, ((256 - (k)) & 255) * 513 & ~7, 0, mb + 16); }
    if (lead) { MID_LOAD(grp, cnt); MID_LOADW(grp); }
    const int hB = w >> 2, faB = (w >> 1) & 1, xB = faB;
    const int phi = 8 * (w & 3) + g;
    const uint32_t rA = (8 * w + 2 * t) * 128 + ((g ^ (2 * t)) << 4);
    const uint32_t wA = (8 * w + g) * 128 + (((2 * t) ^ ((g & 1) | ((w & 3) << 1))) << 4);
    const uint32_t oB = (w >> 1) * 8192 + (w & 1) * 512;
    const uint32_t rB = oB + (8 * t + (g >> 2)) * 128 + (((g & 3) ^ ((g >> 2) | (t << 1)) ^ xB) << 4);
    const uint32_t wB = oB + (8 * (g >> 1) + (t >> 1)) * 128 + (((((g & 1) << 2) | (2 * (t & 1))) ^ ((t >> 1) | ((g >> 1) << 1)) ^ xB) << 4);
    const uint32_t wBi = oB + (8 * (g >> 1) + (t >> 1)) * 128 + (((((g & 1) << 2) | (2 * (t & 1))) ^ ((t >> 1) | ((w & 1) << 2))) << 4);
    const int hC = (lane >> 3) & 1, pr = 8 * (w & 3) + (lane & 7), pc = hC ? (32 - pr) & 31 : pr;
    const uint32_t aC = hC * 16384 + (pc & 1) * 8192 + (pc >> 2) * 1024 + (((((pc & 2) << 1) | (lane >> 4)) ^ (((pc >> 2) & 3) << 1) ^ (pc & 1)) << 4);
    const uint32_t g0 = wb + (t >> 1) * 144 + (32 * (t & 1) + phi) * 2, g1 = wb + 18432 + (7 - (t >> 1)) * 144 + (64 - 32 * (t & 1) - phi) * 2;
    const uint32_t wAo = (8 * w + g) * 128 + (((2 * t) ^ g) << 4);
    uint32_t wph = 0;
#pragma unroll 1
    for (int k1 = grp; k1 < 129; k1 += 8, cnt++, wph ^= 1) {
        const uint32_t buf = gb + (cnt & 1) * 32768;
        uint4 in[2][4], m[4], out[4];
        m[0] = m[1] = m[2] = lds128u(tb + FT_A8 + lane * 16);
        m[3] = negfrag(m[0]);
        mbar_wait(mb + 8 * (cnt & 1), (cnt >> 1) & 1);
#pragma unroll
        for (int q = 0; q < 2; q++)
#pragma unroll
            for (int i = 0; i < 4; i++) in[q][i] = lds128u(buf + (rA ^ ((i & 1) * 0x90)) + (i >> 1) * 8192 + q * 16384);
        __syncwarp();
#pragma unroll
        for (int q = 0; q < 2; q++) {
            dft16<false>(out, in[q], m, m);
#pragma unroll
            for (int i = 0; i < 4; i++) sts128u(buf + (wA ^ (((i ^ (i >> 1)) & 1) << 4)) + (i >> 1) * 8192 + q * 16384, out[i]);
        }
        {
            uint4 tw[4];
#pragma unroll
            for (int i = 0; i < 4; i++) {
                m[i] = lds128u(tb + (faB ? FT_B1F : FT_F16) + i * 512 + lane * 16);
                if (hB) { m[i].y ^= 0x80008000u; m[i].w ^= 0x80008000u; }
                tw[i] = lds128u(tb + FT_TWB + (w >> 1) * 2048 + i * 512 + lane * 16);
            }
            bar_sync(bar, 256);
#pragma unroll
            for (int q = 0; q < 2; q++)
#pragma unroll
                for (int i = 0; i < 4; i++) in[q][i] = lds128u(buf + (rB ^ ((i & 1) << 6)) + (i >> 1) * 4096 + q * 256);
            __syncwarp();
#pragma unroll
            for (int q = 0; q < 2; q++) {
                dft16<true>(out, in[q], m, tw);
#pragma unroll
                for (int i = 0; i < 4; i++) sts128u(buf + (wB ^ ((i & 1) << 4)) + (i >> 1) * 4096 + q * 256, out[i]);
            }
        }
        {
            const uint32_t cjm = (g & 1) ? 0x8000u : 0x80000000u;
            float4 tw[4];
#pragma unroll
            for (int i = 0; i < 4; i++) { m[i] = lds128u(tb + FT_C + i * 512 + lane * 16); tw[i] = lds128(tb + FT_TWC + ((w & 3) * 4 + i) * 512 + lane * 16); }
            if (lead && k1 + 8 < 129) { bulk_wait_read(); MID_LOAD(k1 + 8, cnt + 1); }
            __syncwarp();
            mbar_wait(mb + 16, wph);
            const uint32_t o0 = (k1 & 7) * 2, o1 = (-k1 & 7) * 2;
            if (w == 1 && lane < 16) {
                const int k2 = lane & 7, k2p = k1 ? 7 - k2 : (8 - k2) & 7;
                const uint32_t p0 = wb + (lane >> 3) * 9216 + k2 * 1152 + o0, p1 = wb + 18432 + (lane >> 3) * 9216 + k2p * 1152 + o1;
                const float sg = lane < 8 ? 0.5f : -0.5f;
                const uint32_t v = pack_bf16(0.5f * ldw(p0) + sg * ldw(p1), 0.5f * ldw(p1 + 1136) + sg * ldw(p0 + 1136));
                asm volatile("st.shared.u16 [%0], %1;" ::"r"(p0), "h"((uint16_t)v) : "memory");
                asm volatile("st.shared.u16 [%0], %1;" ::"r"(p1 + 1136), "h"((uint16_t)(v >> 16)) : "memory");
                fence_async_smem();
            }
            bar_sync(bar, 256);
#define FFT_CU 1
            constexpr int CU = FFT_CU;
#pragma unroll CU
            for (int q = 0; q < 4; q++) {
                const int k2 = 4 * (w >> 2) + q, k2p = k1 ? 7 - k2 : (8 - k2) & 7, kr = hC ? k2p : k2;
                const uint32_t a0 = buf + (aC ^ ((kr & 1) << 4)) + kr * 128;
                const uint32_t r0 = g0 + k2 * 1152 + o0, r1 = g1 + k2p * 1152 + o1;
                uint32_t x[4], y[4];
                ldsm4(x, a0); ldsm4(y, a0 ^ 32);
                float c[4][4];
#pragma unroll
                for (int i = 0; i < 4; i++) { c[i][0] = c[i][1] = c[i][2] = c[i][3] = 0.f; mma16816(c[i], x[0], x[1], x[2], x[3], m[i].x, m[i].y); }
#pragma unroll
                for (int i = 0; i < 4; i++) mma16816(c[i], y[0], y[1], y[2], y[3], m[i].z, m[i].w);
#pragma unroll
                for (int i = 0; i < 4; i++) {
                    const float2 ga = make_float2(ldw(r0 + i * 288), ldw(r0 + 9216 + i * 288));
                    const float2 gc = make_float2(ldw(r1 - i * 288), ldw(r1 + 9216 - i * 288));
                    const float tc = tw[i].z, ts = tw[i].w;
                    const float* z = c[i];
                    const float2 S = make_float2(ga.x + gc.x, ga.y - gc.y), D = make_float2(ga.x - gc.x, ga.y + gc.y);
                    const float2 u = make_float2(ts * z[0] - tc * z[3], ts * z[1] + tc * z[2]), v = make_float2(ts * z[2] - tc * z[1], ts * z[3] + tc * z[0]);
                    uint32_t* o = (i < 2 ? x : y) + 2 * (i & 1);
                    o[0] = pack_bf16(fmaf(S.x, z[0], fmaf(-S.y, z[1], fmaf(D.x, u.x, -D.y * u.y))), fmaf(S.x, z[1], fmaf(S.y, z[0], fmaf(D.x, u.y, D.y * u.x))));
                    o[1] = pack_bf16(fmaf(S.x, z[2], fmaf(-S.y, z[3], fmaf(-D.x, v.x, D.y * v.y))), fmaf(S.x, z[3], fmaf(S.y, z[2], fmaf(-D.x, v.y, -D.y * v.x))));
                }
#pragma unroll
                for (int i = 0; i < 4; i++) { c[i][0] = c[i][1] = c[i][2] = c[i][3] = 0.f; mma16816(c[i], x[0], x[1], x[2], x[3], m[i].x ^ cjm, m[i].y ^ cjm); }
#pragma unroll
                for (int i = 0; i < 4; i++) mma16816(c[i], y[0], y[1], y[2], y[3], m[i].z ^ cjm, m[i].w ^ cjm);
#pragma unroll
                for (int i = 0; i < 4; i++) {
                    uint32_t* o = (i < 2 ? x : y) + 2 * (i & 1);
                    o[0] = pack_bf16(c[i][0] * tw[i].x + c[i][1] * tw[i].y, c[i][1] * tw[i].x - c[i][0] * tw[i].y);
                    o[1] = pack_bf16(c[i][2] * tw[i].x + c[i][3] * tw[i].y, c[i][2] * tw[i].y - c[i][3] * tw[i].x);
                }
                stsm4(a0, x[0], x[1], x[2], x[3]);
                stsm4(a0 ^ 32, y[0], y[1], y[2], y[3]);
            }
        }
#pragma unroll
        for (int i = 0; i < 4; i++) { m[i] = lds128u(tb + (faB ? FT_B1I : FT_F16) + i * 512 + lane * 16); if (!faB) m[i] = conjfrag(m[i]); }
        bar_sync(bar, 256);
        if (lead && k1 + 8 < 129) MID_LOADW(k1 + 8);
        __syncwarp();
#pragma unroll
        for (int q = 0; q < 2; q++)
#pragma unroll
            for (int i = 0; i < 4; i++) in[q][i] = lds128u(buf + (rB ^ ((i & 1) << 6)) + (i >> 1) * 4096 + q * 256);
        __syncwarp();
#pragma unroll
        for (int q = 0; q < 2; q++) {
            dft16<false>(out, in[q], m, m);
#pragma unroll
            for (int i = 0; i < 4; i++) sts128u(buf + (wBi ^ ((i & 1) << 4) ^ (q << 5)) + (i >> 1) * 4096 + q * 256, out[i]);
        }
        m[0] = m[1] = m[2] = conjfrag(lds128u(tb + FT_A8 + lane * 16));
        m[3] = negfrag(m[0]);
        bar_sync(bar, 256);
#pragma unroll
        for (int q = 0; q < 2; q++)
#pragma unroll
            for (int i = 0; i < 4; i++) in[q][i] = lds128u(buf + (rA ^ ((i & 1) * 0x90)) + (i >> 1) * 8192 + q * 16384);
        __syncwarp();
#pragma unroll
        for (int q = 0; q < 2; q++) {
            dft16<false>(out, in[q], m, m);
#pragma unroll
            for (int i = 0; i < 4; i++) sts128u(buf + (wAo ^ ((i & 1) << 4)) + (i >> 1) * 8192 + q * 16384, out[i]);
        }
        fence_async_smem();
        bar_sync(bar, 256);
        if (lead) {
            tma_st3(buf, &fm.y2, 0, k1 * 8);
            if (k1 & 127) tma_st3(buf + 16384, &fm.y2, 0, (256 - k1) * 8);
            bulk_commit();
        }
    }
    if (lead) bulk_wait_all();
}

__device__ __align__(128) unsigned g_start;
__device__ __align__(128) unsigned g_fbar;
__device__ __align__(128) unsigned g_end;
__device__ __forceinline__ unsigned gbar_arrive(unsigned* c, unsigned inc, unsigned total, int lane) {
    unsigned v = 0;
    if (lane == 0) { asm volatile("fence.proxy.async;" ::: "memory"); fence_gpu(); v = atomicAdd(c, inc); }
    return (__shfl_sync(~0u, v, 0) & ~(total - 1)) + total;
}
__device__ __forceinline__ void gbar_wait(unsigned* c, unsigned target, unsigned ns) {
    uint32_t n = 0;
    while (__any_sync(~0u, (int)(ld_acquire(c) - target) < 0)) { if (ns) __nanosleep(ns); if (++n > SPIN_LIMIT) __trap(); }
    asm volatile("fence.proxy.async;" ::: "memory");
}
__device__ __forceinline__ void fft_rest(int cta, const FftMaps& fm, uint32_t sb, bool skip) {
    const int hi = __shfl_sync(~0u, threadIdx.x >> 8, 0), w = __shfl_sync(~0u, (threadIdx.x >> 5) & 7, 0), lane = threadIdx.x & 31;
    unsigned target = 0;
    if (w == 4) target = gbar_arrive(&g_start, 16, 256, lane);
    if (threadIdx.x < 32) mbar_init(sb + FT_BAR + 8 * threadIdx.x, 1);
    fft_tables(sb, threadIdx.x, 512);
    fence_async_smem();
    __syncthreads();
    const int grp = cta * 2 + hi, bar = 1 + hi;
    const uint32_t gb = sb + hi * FG_SIZE, mb = sb + FT_BAR + hi * 128;
    uint32_t cnt = 0;
    if (w == 4) gbar_wait(&g_start, target, 200);
    GT(1);
    fft_mid(grp, fm, sb, gb, mb, cnt, w, lane, bar);
    if (w == 4) gbar_wait(&g_fbar, gbar_arrive(&g_fbar, 1, 8, lane), 200);
    GT(2);
    fft_col<true, 16>(grp, 0, &fm.y, &fm.o, gb, mb + 64, w, lane, bar);
}

__device__ __align__(256) uint4 g_kvq[4 * 32 * 3 * 8 * 2 * 32];
__device__ __align__(256) uint2 g_alpha[2 * 32 * 3 * 8 * 2 * 32];
__device__ __align__(256) uint4 g_red[5 * 32768 / 16];
__device__ __align__(256) uint4 g_stamp[32];
__device__ __align__(256) uint4 g_qst[128 * 2];
__device__ __align__(256) bf16 g_ox[2048 * 4096];
struct Tune { uint32_t d_alpha, d_r, opt, d_q, d_v, spread, extra; };
#define OP_SPLIT 1
#define X_SEQ 24
#define OPD_EARLY 0
constexpr int RA = 2;

constexpr uint32_t SM_BASE = 1024;
constexpr uint32_t O_WO = 0;
constexpr uint32_t O_WV = 65536;
constexpr uint32_t O_XB = 131072;
constexpr uint32_t O_MEM = O_XB + 32768;
constexpr uint32_t O_RECV = O_MEM + 8192;
constexpr uint32_t O_KVQ = O_RECV + 12288;
constexpr uint32_t O_STG = O_KVQ + 18432;
constexpr uint32_t O_S = O_STG + 8192;
constexpr uint32_t O_XO = O_STG + 16384;
constexpr uint32_t O_P = O_S + 10240;
constexpr uint32_t O_O = O_P + 1536;
constexpr uint32_t O_VM = O_O + 2048;
constexpr uint32_t O_DBG = O_VM + 2048;
constexpr uint32_t O_F1 = 196608;
constexpr uint32_t O_BAR = 232448 - 512;
constexpr uint32_t MAIN_SMEM = 232448;
static_assert(O_DBG + (DBG_TIMING ? 4 * DBG_N * 24 * 4 : 0) <= O_BAR && FFT_SMEM <= MAIN_SMEM && O_F1 + 32768 <= O_BAR, "smem");
constexpr int G_ST = 6;
enum { B_WK0 = 0, B_WK1, B_WQ0, B_WQ1, B_WV, B_WO, B_F1, B_XP, B_XFULL, B_RFULL, B_AFULL, B_KVFULL, B_QST, B_RECV, B_GF = B_RECV + 6,
       B_QDONE = B_GF + G_ST, B_KDONE, B_XEMPTY, B_SDONE, B_SRDY, B_OPDONE, B_QX, B_GE, B_XPE = B_GE + G_ST, B_QKW, B_MEM, B_COUNT };

constexpr float SM_SCALE_LOG2 = 0.08838834764831845f * 1.4426950408889634f;
constexpr float MASK_VAL = -1.0e9f / 0.08838834764831845f;

__device__ __forceinline__ uint32_t red_grp(int grp) { return (uint32_t)((grp >> 1) * 1024 + (grp & 1) * 256); }
__host__ __device__ constexpr uint64_t xdesc(int ks) { return mkdesc(SM_BASE + O_XB + (ks >> 2) * 1024 + (ks & 3) * 32, 16, 8192, 1); }

__device__ __forceinline__ void x_split(const float* d, uint32_t (&sn)[4], uint32_t (&kp)[4], int kh) {
#pragma unroll
    for (int i = 0; i < 4; i++) {
        const uint32_t lo = pack_bf16(d[2 * i], d[2 * i + 1]), hi = pack_bf16(d[8 + 2 * i], d[8 + 2 * i + 1]);
        sn[i] = kh ? lo : hi; kp[i] = kh ? hi : lo;
    }
}
__device__ __forceinline__ void x_send(int R, const uint32_t (&sn)[4], int sg, int tid, uint32_t sb, uint32_t mate) {
    const uint32_t par = sg & 1;
    const uint32_t bar = O_BAR + 8 * (B_RECV + R * 2) + 8 * par;
    if (tid == 0) mbar_expect_tx(sb + bar, 2048);
    asm volatile("st.async.shared::cluster.mbarrier::complete_tx::bytes.v4.b32 [%0], {%1,%2,%3,%4}, [%5];"
                 ::"r"(mate + O_RECV + (par * 3 + R) * 2048 + tid * 16), "r"(sn[0]), "r"(sn[1]), "r"(sn[2]), "r"(sn[3]), "r"(mate + bar) : "memory");
}
__device__ __forceinline__ void x_wait(int R, int sg, uint32_t sb) {
    mbar_wait_cluster(sb + O_BAR + 8 * (B_RECV + R * 2) + 8 * (sg & 1), (sg >> 1) & 1);
}
template <int R>
__device__ __forceinline__ void x_finish(const uint32_t (&kp)[4], int sg, int h, int mt, int kh, int tid, uint32_t sb) {
    const uint4 r = lds128u(sb + O_RECV + ((sg & 1) * 3 + R) * 2048 + tid * 16);
    uint32_t u0 = add_bf16x2(kp[0], r.x), u1 = add_bf16x2(kp[1], r.y), u2 = add_bf16x2(kp[2], r.z), u3 = add_bf16x2(kp[3], r.w);
    if (R < 2) { u0 = movm(u0); u1 = movm(u1); u2 = movm(u2); u3 = movm(u3); }
    const uint32_t tag = ((sg >> 2) & 1) ^ 1;
    u0 = (u0 & ~1u) | tag;
    uint4* const hb = &g_kvq[((sg & 3) * 32 + h) * (3 * 512)];
    if (R == 0) {
        uint2* p = (uint2*)hb + (kh * 16 + mt) * 32 + (tid & 31);
        asm volatile("{\n.reg .pred p;\nsetp.lt.s32 p, %5, 64;\n@p st.relaxed.gpu.global.v2.b32 [%0], {%1,%2};\n@p st.relaxed.gpu.global.v2.b32 [%0+2048], {%3,%4};\n}"
                     ::"l"(p), "r"(u0), "r"(u1), "r"((u2 & ~1u) | tag), "r"(u3), "r"(sg) : "memory");
    } else {
        asm volatile("{\n.reg .pred p;\nsetp.lt.s32 p, %5, 64;\n@p st.relaxed.gpu.global.v4.b32 [%0], {%1,%2,%3,%4};\n}"
                     ::"l"(hb + R * 512 + (mt * 2 + kh) * 32 + (tid & 31)), "r"(u0), "r"(u1), "r"(u2), "r"(u3), "r"(sg) : "memory");
    }
}

__device__ __forceinline__ uint32_t convert_mem(const unsigned char* redp, int s, int kh, int jj, int w, int lane, uint32_t sb, uint32_t& sf) {
    const uint32_t off = red_grp(jj * 16 + w * 4 + (lane >> 3)), o16 = off + (lane & 7) * 16, o8 = off + 512 + ((lane >> 3) & 1) * 64 + (lane & 7) * 8;
    uint32_t ma = sb + O_MEM + (jj * 4 + (lane >> 4)) * 1024 + (lane & 7) * 128 + (((2 * w + ((lane >> 3) & 1)) ^ (lane & 7)) << 4);
    uint32_t a16 = sb + O_STG + o16, a8 = sb + O_STG + o8;
    const uint32_t target = (s & 4) ? 0x42C00000u : 0x42000000u;
    uint32_t n = 0;
    bool redo;
    KEEP2(ma, a16); KEEP2(a8, target);
#pragma unroll 1
    do {
        asm volatile("" : "+r"(n));
        if (n) {
            const unsigned char* pg = redp + (s & 3) * 32768 + kh * 16384;
            const uint4 x = ldg_rlx128(pg + o16), y = ldg_rlx128(pg + o16 + 128);
            const uint2 z = ldg_rlx64(pg + o8);
            sts128u(a16, x); sts128u(a16 + 128, y); sts64u(a8, z);
            if (n > SPIN_LIMIT) __trap();
        }
        n++;
        mbar_wait(sb + O_BAR + 8 * B_RFULL, s & 1);
        const uint4 ra = lds128u(a16), rb = lds128u(a16 + 128);
        const uint2 rc = lds64u(a8);
        stsm4t(ma, ra.x, ra.y, ra.z, __byte_perm(ra.w, rc.x, 0x5410));
        stsm4t(ma + 2048, rb.x, rb.y, rb.z, __byte_perm(rb.w, rc.x, 0x7610));
        redo = __any_sync(~0u, orx(orx2(ra.w, rb.w, target), rc.y, target) > 0xffffu);
    } while (redo);
    if (lane == 0) mbar_arrive(sb + O_BAR + 8 * B_MEM);
    fence_async_smem();
    __syncwarp();
    if (lane == 0) mbar_arrive(sb + O_BAR + 8 * B_QKW);
    return n - 1;
}

#define F16(d, o) F4(d, o), F4(d, o + 4), F4(d, o + 8), F4(d, o + 12)
__device__ __forceinline__ void wg_ss128(float (&d)[64], uint64_t da, uint64_t db, int sc) {
    asm volatile("{\n.reg .pred p;\nsetp.ne.b32 p, %66, 0;\nwgmma.mma_async.sync.aligned.m64n128k16.f32.bf16.bf16 "
                 "{%0,%1,%2,%3,%4,%5,%6,%7,%8,%9,%10,%11,%12,%13,%14,%15,%16,%17,%18,%19,%20,%21,%22,%23,%24,%25,%26,%27,%28,%29,%30,%31,"
                 "%32,%33,%34,%35,%36,%37,%38,%39,%40,%41,%42,%43,%44,%45,%46,%47,%48,%49,%50,%51,%52,%53,%54,%55,%56,%57,%58,%59,%60,%61,%62,%63}, "
                 "%64, %65, p, 1, 1, 0, 1;\n}"
                 : F16(d, 0), F16(d, 16), F16(d, 32), F16(d, 48) : "l"(da), "l"(db), "r"(sc));
}
__device__ __forceinline__ void stg_rlx32(void* p, uint32_t v) { asm volatile("st.relaxed.gpu.global.u32 [%0], %1;" ::"l"(p), "r"(v) : "memory"); }

__global__ void __cluster_dims__(2, 1, 1) __launch_bounds__(512, 1)
rmt_main(const __grid_constant__ CUtensorMap tm_x, const __grid_constant__ CUtensorMap tm_wq, const __grid_constant__ CUtensorMap tm_wk,
         const __grid_constant__ CUtensorMap tm_wv, const __grid_constant__ CUtensorMap tm_wo, const bf16* __restrict__ mem0,
         const Tune tn, const __grid_constant__ FftMaps fm, const __grid_constant__ CUtensorMap tm_o,
         const __grid_constant__ CUtensorMap tm_w2, bf16* __restrict__ out) {
    extern __shared__ __align__(1024) unsigned char smem_raw[];
    const uint32_t sb = smem_u32(smem_raw);
    if ((sb & 0x3FFFF) != SM_BASE) __trap();
    GT(6);
    const int cid = blockIdx.x >> 1, kh = blockIdx.x & 1;
    const int tpc = cid < 4 ? 62 + cid : cid - 4;
    int h, nh;
    if (tpc < 32) { h = (tpc >> 4) * 8 + (tpc & 7); nh = (tpc >> 3) & 1; }
    else if (tpc < 60) { int u = tpc - 32, r = u % 14; h = 16 + (u / 14) * 7 + r % 7; nh = r / 7; }
    else if (tpc < 62) { GT(0); fft_rest((tpc - 60) * 2 + kh, fm, sb, tn.opt & 8); GT(3); return; }
    else { h = 30 + ((tpc - 62) >> 1); nh = tpc & 1; }
    const int j = nh * 2 + kh, role = h * 4 + j;
    const int wgi = __shfl_sync(~0u, threadIdx.x >> 7, 0);
    const int w = __shfl_sync(~0u, (threadIdx.x >> 5) & 3, 0);
    const int tid = threadIdx.x & 127, lane = tid & 31;
#define PIN_IDS() const int tid = __shfl_sync(~0u, threadIdx.x & 127, threadIdx.x & 31), lane = tid & 31
#define OPAQUE_IDS() int tid_ = tid; asm volatile("" : "+r"(tid_)); const int tid = tid_, lane = tid_ & 31; (void)lane
    unsigned char* const redp = (unsigned char*)(((uintptr_t)g_red + 32767) & ~(uintptr_t)32767);
    const uint32_t bars = sb + O_BAR;

    if (threadIdx.x < B_COUNT) {
        const int i = threadIdx.x;
        mbar_init(bars + 8 * i, i < B_QDONE ? 1 : i < B_GE ? 4 : i < B_XPE ? 8 : i < B_QKW ? 12 : 16);
        asm volatile("fence.mbarrier_init.release.cluster;" ::: "memory");
        fence_async_smem();
    } else if (threadIdx.x >= 64 && threadIdx.x < 71) {
        const int i = threadIdx.x - 64;
        const CUtensorMap* m = i == 0 ? &tm_wk : i == 1 ? &tm_wq : i == 2 ? &fm.x : i == 3 ? &tm_x : i == 4 ? &tm_wv : i == 5 ? &tm_wo : &fm.y;
        asm volatile("prefetch.tensormap [%0];" ::"l"(m) : "memory");
    }
    __syncthreads();
    const int wc0 = h * 128 + nh * 64;
    if (wgi < 2 && lane == 0) {
        if (w < 2) {
            const uint32_t bar = bars + 8 * (B_WK0 + 2 * (wgi ^ 1) + w);
            mbar_expect_tx(bar, 32768);
            tma2d(sb + (wgi ? O_XB : O_WO) + w * 32768, wgi ? &tm_wk : &tm_wq, wc0, kh * 512 + w * 256, bar);
        } else if (wgi == 0 && w == 2) {
            mbar_expect_tx(bars + 8 * B_F1, 32768);
            tma_ld4(sb + O_F1, &fm.x, (role & 15) * 64, role >> 4, bars + 8 * B_F1);
        } else if (wgi == 1 && w == 2 && role < 2 * (RA + 3)) tma4d_prefetch(&tm_x, kh * 8, (role >> 1) * 4);
    }
    GT(7);
    uint32_t mate;
    asm volatile("mapa.shared::cluster.u32 %0, %1, %2;" : "=r"(mate) : "r"(sb), "r"(kh ^ 1));
    if (wgi >= 2) fft_col<false, 1>(role >> 4, role & 15, &fm.x, &fm.y, sb + O_F1, bars + 8 * B_F1, (wgi - 2) * 4 + w, lane, 6);

    if (wgi < 2) {
        asm volatile("setmaxnreg.inc.sync.aligned.u32 176;");
        PIN_IDS();
        uint32_t a[32][4], sf = 0;
        {
            const uint32_t stage = sb + (wgi == 0 ? O_WO : O_XB);
            const uint32_t ad = stage + (((lane >> 4) & 1) * 8 + (lane & 7)) * 128 + (((2 * w + ((lane >> 3) & 1)) ^ (lane & 7)) << 4);
#pragma unroll
            for (int i = 0; i < 2; i++) {
                mbar_wait(bars + 8 * (B_WK0 + 2 * (wgi ^ 1) + i), 0);
#pragma unroll
                for (int ks = 0; ks < 16; ks++) ldsm4t(a[i * 16 + ks], ad + (i * 16 + ks) * 2048);
            }
#pragma unroll
            for (int ks = 0; ks < 32; ks += 2) KEEP2(a[ks][0], a[ks + 1][0]);
            SCHED_FENCE();
            if (lane == 0) mbar_arrive(bars + 8 * (B_QDONE + wgi));
            if (wgi == 0) GT(10); else GT(11);
        }
        asm volatile("barrier.cluster.arrive.relaxed.aligned;" ::: "memory");
        asm volatile("barrier.cluster.wait.acquire.aligned;" ::: "memory");
        uint32_t kp[4];
#define X_PASS(d, dofs)                                                                                    \
        wg_fence();                                                                                        \
        _Pragma("unroll") for (int ks = 0; ks < 32; ks++) { if (ks == 0) wg_rs32<0>(d, a[ks], xdesc(ks) + (dofs)); else wg_rs32<1>(d, a[ks], xdesc(ks) + (dofs)); } \
        wg_commit();                                                                                       \
        wg_wait<0>();
#define X_FINISH(sg) { if (wgi == 0) x_finish<0>(kp, sg, h, nh * 4 + w, kh, tid, sb); else x_finish<1>(kp, sg, h, nh * 4 + w, kh, tid, sb); }
        mbar_wait(bars + 8 * B_XP, 0);
        if (wgi == 0) GT(8);
#pragma unroll 1
        for (int sg = 0; sg < RA; sg++) {
            float d[16]; uint32_t sn[4];
            X_PASS(d, sg * 2048 - (int)((O_XB - O_WO) >> 4));
            if (sg > 0) {
                if (lane == 0) mbar_arrive(bars + 8 * B_XPE);
                x_wait(wgi, sg - 1, sb); X_FINISH(sg - 1);
            }
            x_split(d, sn, kp, kh);
            x_send(wgi, sn, sg, tid, sb, mate);
        }
        const int lq = wgi == 0 ? 4 : 0;
#pragma unroll 1
        for (int s = 0; s < 64; s++) {
            TSI(s);
            {
                float d[16]; uint32_t sn[4], kc[4];
                x_wait(wgi, s + RA - 1, sb);
                mbar_wait(bars + 8 * B_XFULL, s & 1);
                if (wgi == 1) {
                    mbar_wait(bars + 8 * B_OPDONE, s & 1);
                    x_finish<1>(kp, s + RA - 1, h, nh * 4 + w, kh, tid, sb);
                    TS(5);
                    mbar_wait(bars + 8 * B_QX, s & 1);
                } else mbar_wait(bars + 8 * B_OPDONE, s & 1);
                TS(6);
                wg_fence();
#pragma unroll
                for (int ks = 0; ks < 32; ks++) {
                    if (ks == 0) wg_rs32<0>(d, a[ks], xdesc(ks)); else wg_rs32<1>(d, a[ks], xdesc(ks));
                    if (ks == X_SEQ - 1) wg_commit();
                }
                wg_commit();
                wg_wait<1>();
                if (tid < lq) mbar_arrive(bars + 8 * B_QX);
                wg_wait<0>();
                TS(7);
                x_split(d, sn, kc, kh);
                x_send(wgi, sn, s + RA, tid, sb, mate);
                TS(4);
                if (wgi == 0) { x_finish<0>(kp, s + RA - 1, h, nh * 4 + w, kh, tid, sb); TS(5); }
#pragma unroll
                for (int i = 0; i < 4; i++) kp[i] = kc[i];
            }
            uint2* ap = &g_alpha[((s & 1) * 32 + h) * (3 * 512) + wgi * 512 + ((nh * 4 + w) * 2 + kh) * 32 + lane];
            uint32_t mb0 = sb + O_MEM + (lane & 7) * 128 + (((lane >> 3) ^ (lane & 7)) << 4), mb1 = mb0 ^ 64;
            const uint32_t tag = ((s >> 1) & 1) ^ 1;
            KEEP2(mb0, mb1); KEEPP(ap);
            float e[2][4];
#pragma unroll
            for (int i = 0; i < 4; i++) e[0][i] = e[1][i] = 0.f;
            if (lane == 0) mbar_arrive(bars + 8 * B_MEM);
            mbar_wait(bars + 8 * B_MEM, s & 1);
            TS(0);
#pragma unroll
            for (int ks = 0; ks < 32; ks += 2) {
                uint32_t b[4];
                ldsm4(b, ((ks & 2) ? mb1 : mb0) + (ks >> 2) * 1024);
                mma16816(e[0], a[ks][0], a[ks][1], a[ks][2], a[ks][3], b[0], b[1]);
                mma16816(e[1], a[ks + 1][0], a[ks + 1][1], a[ks + 1][2], a[ks + 1][3], b[2], b[3]);
            }
            TS(2);
            uint32_t u0 = pack_bf16(e[0][0] + e[1][0], e[0][1] + e[1][1]), u1 = pack_bf16(e[0][2] + e[1][2], e[0][3] + e[1][3]);
            u0 = movm(u0); u1 = movm(u1);
            SCHED_FENCE();
            if (lane == 0) mbar_arrive(bars + 8 * B_QKW);
            stg_rlx64(ap, (u0 & ~1u) | tag, u1);
            TS(3);
            if (wgi == 1) {
                const uint2* vp = &g_alpha[((s & 1) * 32 + h) * (3 * 512) + 1024 + w * 128 + lane];
                const uint32_t vs = sb + O_VM + tid * 16;
                KEEPP(vp); KEEP2(vs, 0);
                mbar_wait(bars + 8 * B_QST, s & 1);
                uint32_t n, bad;
                asm volatile("ld.shared.u32 %0, [%1];" : "=r"(n) : "r"(bars + 504) : "memory");
                wait_gtime(n + tn.d_v);
                TS(8);
                n = 0;
                do {
                    uint2 va[4];
#pragma unroll
                    for (int i = 0; i < 4; i++) va[i] = ldg_rlx64(vp + i * 32);
                    if (++n > SPIN_LIMIT) __trap();
                    bad = (orx2(va[0].x, va[1].x, tag) | orx2(va[2].x, va[3].x, tag)) & 1;
                    sts128u(vs, make_uint4((add_bf16x2(va[0].x, va[1].x) & ~1u) | ((~s ^ bad) & 1), add_bf16x2(va[0].y, va[1].y),
                                                             add_bf16x2(va[2].x, va[3].x), add_bf16x2(va[2].y, va[3].y)));
                } while (__any_sync(~0u, bad));
                TS(9);
                TSV(16 + w, n - 1);
            }
        }
        x_wait(wgi, 63 + RA, sb);
        sts32(bars + 508, sf);
        TSDUMP();
        asm volatile("bar.arrive 7, 512;" ::: "memory");
        float d[64];
        int st = 0, ph = 0;
#pragma unroll 1
        for (int kt = 0; kt < 64; kt++) {
            mbar_wait(bars + 8 * (B_GF + st), ph);
            if (kt == 0) GT(4);
            const uint64_t da = mkdesc(SM_BASE + st * 32768 + wgi * 8192, 16, 1024, 1), db = mkdesc(SM_BASE + st * 32768 + 16384, 8192, 1024, 1);
            wg_fence();
#pragma unroll
            for (int k = 0; k < 4; k++) wg_ss128(d, da + k * 2, db + k * 128, kt | k);
            wg_commit();
            if (kt > 0) {
                wg_wait<1>();
                if (lane == 0) mbar_arrive(bars + 8 * (B_GE + (st == 0 ? G_ST - 1 : st - 1)));
            }
            if (++st == G_ST) { st = 0; ph ^= 1; }
        }
        wg_wait<0>();
        {
            const uint32_t sl = sb + O_F1 + (wgi * 4 + w) * 4096;
#pragma unroll
            for (int i = 0; i < 8; i++)
                stsm4(sl + (lane & 15) * 256 + (((2 * i + (lane >> 4)) ^ (lane & 7)) << 4), pack_bf16(d[8 * i], d[8 * i + 1]),
                      pack_bf16(d[8 * i + 2], d[8 * i + 3]), pack_bf16(d[8 * i + 4], d[8 * i + 5]), pack_bf16(d[8 * i + 6], d[8 * i + 7]));
            __syncwarp();
            bf16* op = out + (size_t)((role >> 3) * 128 + wgi * 64 + w * 16 + (lane >> 4)) * 2048 + 1024 + (role & 7) * 128 + (lane & 15) * 8;
#pragma unroll
            for (int i = 0; i < 8; i++) {
                const int r = 2 * i + (lane >> 4);
                const uint4 v = lds128u(sl + r * 256 + (((lane & 15) ^ (r & 7)) << 4));
                stg128(op + (size_t)i * 4096, v.x, v.y, v.z, v.w);
            }
        }
        GT(5);
    } else if (wgi == 2) {
        asm volatile("setmaxnreg.dec.sync.aligned.u32 64;");
        PIN_IDS();
        asm volatile("barrier.cluster.arrive.relaxed.aligned;" ::: "memory");
#define X_LOAD(dst, sg, bar) tma4d(sb + (dst), &tm_x, kh * 8, (sg) * 4, bars + 8 * (bar))
        if (w == 0) {
#define WV_LOAD(i) tma2d(sb + O_WV + (i) * 32768, &tm_wv, wc0, kh * 512 + (i) * 256, bars + 8 * B_WV)
            const int nearly = (tn.opt >> 5) & 3;
            mbar_wait(bars + 8 * B_WK0, 0);
            if (lane == 0) { mbar_expect_tx(bars + 8 * B_WV, 65536); for (int i = 0; i < nearly; i++) WV_LOAD(i); }
            mbar_wait(bars + 8 * B_QDONE, 0);
            if (lane == 0) { mbar_expect_tx(bars + 8 * B_XP, 65536); X_LOAD(O_WO, 0, B_XP); X_LOAD(O_WO + 32768, 1, B_XP); }
            mbar_wait(bars + 8 * B_KDONE, 0);
            if (lane == 0) {
                mbar_expect_tx(bars + 8 * B_XFULL, 32768); X_LOAD(O_XB, RA, B_XFULL);
                for (int i = nearly; i < 2; i++) WV_LOAD(i);
            }
        }
        asm volatile("barrier.cluster.wait.acquire.aligned;" ::: "memory");
        mbar_wait(bars + 8 * B_WV, 0);
        GT(12);
        uint32_t sf = 0, tref = gtime() - 4000;
#define V_PASS(d, dofs)                                                                                    \
        wg_fence();                                                                                        \
        _Pragma("unroll") for (int ks = 0; ks < 32; ks++) {                                                \
            constexpr uint64_t da0 = mkdesc(SM_BASE + O_WV, 16, 1024, 1);                                  \
            if (ks == 0) wg_ss40<0>(d, da0 + ks * 128, xdesc(ks) + (dofs)); else wg_ss40<1>(d, da0 + ks * 128, xdesc(ks) + (dofs)); \
        }                                                                                                  \
        wg_commit();                                                                                       \
        wg_wait<0>();
        mbar_wait(bars + 8 * B_XP, 0);
        {
            uint32_t kp[4];
#pragma unroll 1
            for (int sg = 0; sg <= RA; sg++) {
                float d[20]; uint32_t sn[4];
                if (sg < RA) { V_PASS(d, sg * 2048 - (int)((O_XB - O_WO) >> 4)); }
                if (sg == RA - 1) {
                    if (lane == 0) mbar_arrive(bars + 8 * B_XPE);
                    if (w == 0) {
                        mbar_wait(bars + 8 * B_XPE, 0);
                        GT(9);
                        if (lane == 0) {
                            mbar_expect_tx(bars + 8 * B_WO, 65536);
#pragma unroll
                            for (int i = 0; i < 4; i++) tma2d(sb + O_WO + i * 16384, &tm_wo, j * 256 + i * 64, h * 128, bars + 8 * B_WO);
                        }
                    }
                }
                if (sg > 0) { x_wait(2, sg - 1, sb); x_finish<2>(kp, sg - 1, h, nh * 4 + w, kh, tid, sb); }
                if (sg < RA) { x_split(d, sn, kp, kh); x_send(2, sn, sg, tid, sb, mate); }
            }
        }
#pragma unroll 1
        for (int s = 0; s < 64; s++) {
            TSI(s);
            OPAQUE_IDS();
            uint2* ap = &g_alpha[((s & 1) * 32 + h) * (3 * 512) + 1024 + ((nh * 4 + w) * 2 + kh) * 32 + lane];
            KEEPP(ap);
            float d[20];
            mbar_wait(bars + 8 * B_QKW, s & 1);
            TS(0);
            V_PASS(d, 0);
            TS(1);
            stg_rlx64(ap, (pack_bf16(d[16], d[17]) & ~1u) | (((s >> 1) & 1) ^ 1), pack_bf16(d[18], d[19]));
            if (lane == 0) mbar_arrive(bars + 8 * B_XEMPTY);
            if (s == 63) break;
            uint32_t sn[4], kp[4];
            x_split(d, sn, kp, kh);
            if (w == 3) {
                uint32_t n = 0, mx, mn;
                do {
                    const uint4 st = ldg_rlx128(&g_stamp[lane]);
                    mx = __reduce_max_sync(~0u, max(max(st.x - tref, st.y - tref), max(st.z - tref, st.w - tref)));
                    mn = __reduce_min_sync(~0u, min(min(st.x - tref, st.y - tref), min(st.z - tref, st.w - tref)));
                } while (mx >= 200000u && ++n < 64);
                tref = mx < 200000u ? tref + mx + (mx - mn > tn.spread ? tn.extra : 1) : gtime();
                TSV(12, clk()); TSV(13, n); TSV(14, mx - mn);
            }
            if (tn.opt & 1) { mbar_wait(bars + 8 * B_SDONE, s & 1); x_send(2, sn, s + RA, tid, sb, mate); }
            if (w == 0) {
                mbar_wait(bars + 8 * B_XEMPTY, s & 1);
                mbar_wait(bars + 8 * ((tn.opt & 2) ? B_SRDY : B_SDONE), s & 1);
                if (lane == 0) {
                    mbar_expect_tx(bars + 8 * B_XFULL, 32768);
                    X_LOAD(O_XB, s + RA + 1, B_XFULL);
                }
                mbar_wait(bars + 8 * B_SRDY, s & 1);
                if (lane == 0) {
                    const uint4* hb = &g_kvq[(((s + 1) & 3) * 32 + h) * (3 * 512)];
                    mbar_expect_tx(bars + 8 * B_KVFULL, 18432);
                    bulk_g2s(sb + O_KVQ, hb + 512, 16384, bars + 8 * B_KVFULL);
                    bulk_g2s(sb + O_KVQ + 16384, hb + j * 128, 2048, bars + 8 * B_KVFULL);
                    if (nh == 0 && ((h ^ s) & 7) == 0 && s < 61 - RA) tma4d_prefetch(&tm_x, kh * 8, (s + RA + 3) * 4);
                }
            }
            mbar_wait(bars + 8 * B_OPDONE, (s + 1) & 1);
            if (!(tn.opt & 1)) x_send(2, sn, s + RA, tid, sb, mate);
            if (w == 3) {
                wait_gtime(tref + tn.d_r);
                if (lane == 0) {
                    mbar_expect_tx(bars + 8 * B_RFULL, 16384);
                    bulk_g2s(sb + O_STG, redp + (s & 3) * 32768 + kh * 16384, 16384, bars + 8 * B_RFULL);
                }
                TSV(3, clk());
            }
            x_wait(2, s + RA, sb);
            const bool late = w == 3 || (tn.opt & 4);
            if (!late) { x_finish<2>(kp, s + RA, h, nh * 4 + w, kh, tid, sb); TS(6); }
            if (DBG_TIMING && w == 0) { mbar_wait(bars + 8 * B_RFULL, s & 1); TS(4); }
            const uint32_t n = convert_mem(redp, s, kh, 0, w, lane, sb, sf); (void)n;
            TS(5);
            TSV(8 + w, n);
            if (late) x_finish<2>(kp, s + RA, h, nh * 4 + w, kh, tid, sb);
        }
        sts32(bars + 508, sf);
        TSDUMP();
        asm volatile("bar.arrive 7, 512;" ::: "memory");
    } else {
        asm volatile("setmaxnreg.dec.sync.aligned.u32 96;");
        PIN_IDS();
        GT(0);
        asm volatile("barrier.cluster.arrive.relaxed.aligned;" ::: "memory");
#define RED_CLEAR(st)                                                                                           \
        if (lane < 16) {                                                                                        \
            const uint32_t cb = ((st) & 4) ? 0x42800000u : 0u;                                                  \
            stg128(redp + ((st) & 3) * 32768 + role * 256 + lane * 16, 0, (role & 2) ? cb : 0u, 0, cb);        \
        }
        uint32_t start_target = 0;
        if (w == 0) {
            RED_CLEAR(0); RED_CLEAR(1); RED_CLEAR(2);
            mbar_wait(bars + 8 * B_XP, 0);
            if (lane < 4) tma2d_prefetch(&tm_wo, j * 256 + lane * 64, h * 128);
            if (lane == 0) { tma_st4(sb + O_F1, &fm.y, (role & 15) * 64, role >> 4); bulk_commit(); bulk_wait_all(); }
            __syncwarp();
            start_target = gbar_arrive(&g_start, 1, 256, lane);
        }
        bar_sync(1, 128);
        sts128u(sb + O_VM + tid * 16, make_uint4(0, 0, 0, 0));
        mbar_wait(bars + 8 * B_KDONE, 0);
        {
#pragma unroll
            for (int q = 0; q < 4; q++) {
                const int row = (lane >> 3) + (q & 1) * 4, ch = lane & 7, kb = 2 * w + (q >> 1);
                const uint4 v = *(const uint4*)(mem0 + row * 1024 + kh * 512 + kb * 64 + ch * 8);
                sts128u(sb + O_MEM + kb * 1024 + row * 128 + ((ch ^ row) << 4), v);
            }
            fence_async_smem();
            __syncwarp();
            if (lane < 2) { mbar_arrive(bars + 8 * B_MEM); mbar_arrive(bars + 8 * B_QKW); }
            if (lane == 0) mbar_arrive(bars + 8 * B_OPDONE);
            if (tid == 0) mbar_arrive(bars + 8 * B_KVFULL);
        }
        asm volatile("barrier.cluster.wait.acquire.aligned;" ::: "memory");
        if (w == 0) gbar_wait(&g_start, start_target, 0);
        uint32_t sf = 0;
#pragma unroll 1
        for (int s = 0; s < 64; s++) {
            TSI(s);
            OPAQUE_IDS();
            uint4 kf[4]; uint2 qf[2];
            const uint32_t tg = ((s >> 2) & 1) ^ 1;
            {
                const uint32_t ka = sb + O_KVQ + w * 2048 + lane * 16, qa = sb + O_KVQ + 16384 + w * 512 + lane * 8;
                uint32_t n = s == 0;
                bool redo;
#pragma unroll 1
                do {
                    asm volatile("" : "+r"(n));
                    if (n) {
                        const uint4* hb = &g_kvq[((s & 3) * 32 + h) * (3 * 512)];
                        uint4 y[4];
                        do {
#pragma unroll
                            for (int i = 0; i < 4; i++) { kf[i] = ldg_rlx128(hb + 512 + w * 128 + i * 32 + lane); y[i] = ldg_rlx128(hb + 1024 + w * 128 + i * 32 + lane); }
#pragma unroll
                            for (int u = 0; u < 2; u++) qf[u] = ldg_rlx64((const uint2*)hb + j * 256 + (2 * w + u) * 32 + lane);
                            if (++n > SPIN_LIMIT) __trap();
                        } while (__any_sync(~0u, (orx2(y[0].x, y[1].x, tg) | orx2(y[2].x, y[3].x, tg)) & 1));
#pragma unroll
                        for (int i = 0; i < 4; i++) { sts128u(ka + i * 512, kf[i]); sts128u(ka + 8192 + i * 512, y[i]); }
#pragma unroll
                        for (int u = 0; u < 2; u++) sts64u(qa + u * 256, qf[u]);
                        fence_async_smem();
                    }
                    n++;
                    mbar_wait(bars + 8 * B_KVFULL, s & 1);
#pragma unroll
                    for (int i = 0; i < 4; i++) kf[i] = lds128u(ka + i * 512);
#pragma unroll
                    for (int u = 0; u < 2; u++) qf[u] = lds64u(qa + u * 256);
                    redo = __any_sync(~0u, or3(orx2(kf[0].x, kf[1].x, tg), orx2(kf[2].x, kf[3].x, tg), orx2(qf[0].x, qf[1].x, tg)) & 1);
                } while (redo);
                if (w == 0) TSV(22, n - 1);
            }
            TS(9);
            if (s > 0) {
                const uint32_t n = convert_mem(redp, s - 1, kh, 1, w, lane, sb, sf); (void)n;
                TS(11);
                TSV(16 + w, n);
                if (w == 1 && s < 62) RED_CLEAR(s + 2);
            }
            const uint32_t tag = ((s >> 1) & 1) ^ 1;
            const uint2* ap = &g_alpha[((s & 1) * 32 + h) * (3 * 512) + w * 128 + lane];
            const uint32_t l16 = sb + lane * 16, l4 = sb + lane * 4;
            const uint32_t sw = l16 + O_S + w * 2560, sr = l4 + O_S + w * 128;
            uint32_t pw = sb + O_P + ((lane >> 1) & 1) * 704 + (2 * w + (lane >> 4)) * 16 + ((lane >> 2) & 3) * 4 + (lane & 1) * 2;
            int lim = (lane & 2) ? 8 * j + 2 * w + (lane >> 4) - 2 * ((lane >> 2) & 3) - (lane & 1) : 64;
            uint32_t aa = sb + O_STG + w * 1024 + lane * 8;
            KEEP2(l16, l4); KEEP2(pw, lim); KEEP2(aa, tag);
            TS(0);
            if (w == 0) {
                mbar_wait(bars + 8 * B_MEM, s & 1);
                uint32_t tq = gtime();
                if (lane < 9) stg_rlx32(lane < 8 ? (uint32_t*)g_qst + role * 8 + lane : (uint32_t*)g_stamp + role, tq);
                wait_clk(clk(), tn.d_q);
                uint32_t n = 0, mx;
                do { mx = __reduce_max_sync(~0u, ldg_rlx32((const uint32_t*)g_qst + h * 32 + lane) - (tq - 1024)); } while (mx > 100000u && ++n < 16);
                TSV(13, n);
                if (mx <= 100000u) tq += mx - 1024;
                if (lane == 0) { sts32(bars + 504, tq); mbar_arrive(bars + 8 * B_QST); }
                TS(14);
                mbar_wait(bars + 8 * B_QKW, s & 1);
                TS(1);
                wait_gtime(tq + tn.d_alpha);
                if (lane == 0) {
                    mbar_expect_tx(bars + 8 * B_AFULL, 8192);
                    bulk_g2s(sb + O_STG, ap, 8192, bars + 8 * B_AFULL);
                }
                if (s == 0) { mbar_wait(bars + 8 * B_WO, 0); GT(1); }
            }
            {
                uint32_t n = 0;
                bool redo;
#pragma unroll 1
                do {
                    asm volatile("" : "+r"(n));
                    if (n) {
                        uint2 x[8];
#pragma unroll
                        for (int q = 0; q < 8; q++) x[q] = ldg_rlx64(ap + (q >> 2) * 512 + (q & 3) * 32);
#pragma unroll
                        for (int q = 0; q < 8; q++) sts64u(aa + (q >> 2) * 4096 + (q & 3) * 256, x[q]);
                        if (n > SPIN_LIMIT) __trap();
                    }
                    n++;
                    mbar_wait(bars + 8 * B_AFULL, s & 1);
                    TS(12);
                    uint2 qa[4], ka[4];
#pragma unroll
                    for (int i = 0; i < 4; i++) qa[i] = lds64u(aa + i * 256);
#pragma unroll
                    for (int i = 0; i < 4; i++) ka[i] = lds64u(aa + 4096 + i * 256);
                    float sa[5][4];
#pragma unroll
                    for (int i = 0; i < 5; i++) sa[i][0] = sa[i][1] = sa[i][2] = sa[i][3] = 0.f;
#pragma unroll
                    for (int u = 0; u < 2; u++) {
                        const uint32_t q0 = add_bf16x2(qa[2 * u].x, qa[2 * u + 1].x), q1 = add_bf16x2(qa[2 * u].y, qa[2 * u + 1].y);
                        mma16816(sa[1], q0, qf[u].x, q1, qf[u].y, kf[2 * u].x, kf[2 * u].y);
                        mma16816(sa[2], q0, qf[u].x, q1, qf[u].y, kf[2 * u].z, kf[2 * u].w);
                        mma16816(sa[3], q0, qf[u].x, q1, qf[u].y, kf[2 * u + 1].x, kf[2 * u + 1].y);
                        mma16816(sa[4], q0, qf[u].x, q1, qf[u].y, kf[2 * u + 1].z, kf[2 * u + 1].w);
                        const uint32_t k0 = add_bf16x2(ka[2 * u].x, ka[2 * u + 1].x), k1 = add_bf16x2(ka[2 * u].y, ka[2 * u + 1].y);
                        mma16816(sa[0], q0, qf[u].x, q1, qf[u].y, k0, k1);
                        if (u == 0) SCHED_FENCE();
                    }
                    redo = __any_sync(~0u, or3(orx2(qa[0].x, ka[0].x, tag), orx2(qa[1].x, ka[1].x, tag),
                                               orx(orx(orx2(qa[2].x, ka[2].x, tag), qa[3].x, tag), ka[3].x, tag)) & 1);
#pragma unroll
                    for (int i = 1; i <= 5; i++) sts128(sw + (i % 5) * 512, sa[i % 5][0], sa[i % 5][1], sa[i % 5][2], sa[i % 5][3]);
                } while (redo);
                if (w == 0) TSV(20, n - 1);
            }
            TS(2);
            bar_sync(1, 128);
            float sc[5];
            {
                float x[4][5];
#pragma unroll
                for (int q = 0; q < 4; q++)
#pragma unroll
                    for (int n = 0; n < 5; n++) asm volatile("ld.shared.f32 %0, [%1];" : "=f"(x[q][n]) : "r"(sr + q * 2560 + n * 512) : "memory");
                if (lane == 0) mbar_arrive(bars + 8 * B_SDONE);
#pragma unroll
                for (int n = 0; n < 5; n++) sc[n] = (x[0][n] + x[1][n]) + (x[2][n] + x[3][n]);
            }
            TS(15);
#pragma unroll
            for (int n = 1; n < 5; n++) if (8 * (n - 1) > lim) sc[n] = MASK_VAL;
            float m = fmaxf(fmaxf(fmaxf(sc[0], sc[1]), fmaxf(sc[2], sc[3])), sc[4]);
            m = fmaxf(m, __shfl_xor_sync(~0u, m, 1));
            m = fmaxf(m, __shfl_xor_sync(~0u, m, 4));
            m = fmaxf(m, __shfl_xor_sync(~0u, m, 8));
            SCHED_FENCE();
            uint4 vf[4];
#pragma unroll
            for (int i = 0; i < 4; i++) vf[i] = lds128u(l16 + O_KVQ + 8192 + w * 2048 + i * 512);
            m *= -SM_SCALE_LOG2;
#pragma unroll
            for (int n = 0; n < 5; n++) {
                const uint32_t pv = pack_bf16(ex2(fmaf(sc[n], SM_SCALE_LOG2, m)), 0.f);
                asm volatile("st.shared.u16 [%0], %1;" ::"r"(pw + n * 128), "h"((uint16_t)pv) : "memory");
            }
            KEEP2(vf[0].x, vf[1].x); KEEP2(vf[2].x, vf[3].x);
            SCHED_FENCE();
            bar_sync(1, 128);
            TS(3);
            if (lane == 0) mbar_arrive(bars + 8 * B_SRDY);
            float ox[2][4], sm[4], sx[4], cc[4][4];
            unsigned char *pa, *pb;
#pragma unroll 1
            for (uint32_t nv = 0;; nv++) {
                uint32_t pf[4], p0, px[4], px0;
                ldsm4(pf, l16 + O_P + 128);
                ldsm4(px, l16 + O_P + 128 + 704);
                asm volatile("ld.shared.u32 %0, [%1];" : "=r"(p0) : "r"(l4 + O_P) : "memory");
                asm volatile("ld.shared.u32 %0, [%1];" : "=r"(px0) : "r"(l4 + O_P + 704) : "memory");
                float o[2][4];
#pragma unroll
                for (int i = 0; i < 4; i++) o[0][i] = o[1][i] = ox[0][i] = ox[1][i] = sm[i] = sx[i] = 0.f;
                constexpr uint32_t ONE2 = 0x3f803f80u;
                mma1688(sm, ONE2, ONE2, p0);
                mma1688(sx, ONE2, ONE2, px0);
#pragma unroll
                for (int c = 0; c < 2; c++) {
#pragma unroll
                    for (int u = 0; u < 2; u++) mma16816(o[u], vf[2 * u + c].x, vf[2 * u + c].y, vf[2 * u + c].z, vf[2 * u + c].w, pf[2 * c], pf[2 * c + 1]);
#pragma unroll
                    for (int u = 0; u < 2; u++) mma16816(ox[u], vf[2 * u + c].x, vf[2 * u + c].y, vf[2 * u + c].z, vf[2 * u + c].w, px[2 * c], px[2 * c + 1]);
                    mma16816(sm, ONE2, ONE2, ONE2, ONE2, pf[2 * c], pf[2 * c + 1]);
                    mma16816(sx, ONE2, ONE2, ONE2, ONE2, px[2 * c], px[2 * c + 1]);
                }
                const uint32_t vbad = orx(orx(orx2(vf[0].x, vf[1].x, tg), vf[2].x, tg), vf[3].x, tg);
                uint4 vm;
                {
                    uint32_t n = 0;
                    bool redo;
#pragma unroll 1
                    do {
                        vm = lds128v(l16 + O_VM + w * 512);
                        float o2[2][4];
#pragma unroll
                        for (int i = 0; i < 4; i++) { o2[0][i] = o[0][i]; o2[1][i] = o[1][i]; }
                        mma1688(o2[0], vm.x, vm.y, p0);
                        mma1688(o2[1], vm.z, vm.w, p0);
                        redo = __any_sync(~0u, ((vm.x ^ ~s) & 1) && ++n < SPIN_LIMIT);
                        const uint32_t oa = l4 + O_O + w * 512;
                        sts32(oa, pack_bf16(o2[0][0], o2[0][1]));
                        sts32(oa + 128, pack_bf16(o2[0][2], o2[0][3]));
                        sts32(oa + 256, pack_bf16(o2[1][0], o2[1][1]));
                        sts32(oa + 384, pack_bf16(o2[1][2], o2[1][3]));
                    } while (redo);
                    if (w == 0) TSV(21, n);
                }
                TS(4);
                fence_async_smem();
                mma1688(ox[0], vm.x, vm.y, px0);
                mma1688(ox[1], vm.z, vm.w, px0);
                sm[0] = rcp(sm[0]); sm[1] = rcp(sm[1]);
                bar_sync(1, 128);
                TS(5);
#define OP_ISSUE(t0, t1)                                                                                       \
                wg_fence();                                                                                    \
                _Pragma("unroll") for (int ks = 0; ks < 8; ks++)                                               \
                    _Pragma("unroll") for (int t = t0; t < t1; t++) {                                          \
                        constexpr uint64_t da0 = mkdesc(SM_BASE + O_WO, 16, 1024, 1), db0 = mkdesc(SM_BASE + O_O, 128, 128, 0); \
                        if (ks == 0) wg_ss8<0>(cc[t], da0 + t * 1024, db0); else wg_ss8<1>(cc[t], da0 + t * 1024 + ks * 128, db0 + ks * 16); \
                    }                                                                                          \
                wg_commit();
                OP_ISSUE(0, (OP_SPLIT ? 2 : 4));
                pa = redp + (s & 3) * 32768 + red_grp(j * 16 + (tid >> 3));
                pb = pa + 512 + ((lane >> 3) & 1) * 64 + (lane & 7) * 8;
                pa += (lane & 7) * 16;
                KEEPP(pa); KEEPP(pb);
                SCHED_FENCE();
                if (!bar_or(1, 128, vbad)) break;
                wg_wait<0>();
                const uint4* vp = &g_kvq[((s & 3) * 32 + h) * (3 * 512) + 1024 + w * 128 + lane];
#pragma unroll
                for (int i = 0; i < 4; i++) vf[i] = ldg_rlx128(vp + i * 32);
                if (nv > SPIN_LIMIT) __trap();
                bar_sync(1, 128);
            }
            {
                const float i0 = sm[0], i1 = sm[1];
#pragma unroll
                for (int hf = 0; hf < 2; hf++) {
                    if (hf == 0 || OP_SPLIT) wg_wait<0>();
                    if (hf == 0) TS(6);
                    if (OPD_EARLY && hf == OP_SPLIT && lane == 0) mbar_arrive(bars + 8 * B_OPDONE);
                    asm volatile("red.relaxed.gpu.global.add.noftz.v4.bf16x2 [%0], {%1,%2,%3,%4};" ::"l"(pa + hf * 128),
                                 "r"(pack_bf16(cc[2 * hf][0] * i0, cc[2 * hf][1] * i1)), "r"(pack_bf16(cc[2 * hf][2] * i0, cc[2 * hf][3] * i1)),
                                 "r"(pack_bf16(cc[2 * hf + 1][0] * i0, cc[2 * hf + 1][1] * i1)), "r"(pack_bf16(cc[2 * hf + 1][2] * i0, 1.f)) : "memory");
                    if (OP_SPLIT && hf == 0) { SCHED_FENCE(); OP_ISSUE(2, 4); }
                }
                asm volatile("red.relaxed.gpu.global.add.noftz.v2.bf16x2 [%0], {%1,%2};" ::"l"(pb), "r"(pack_bf16(cc[1][3] * i1, cc[3][3] * i1)), "r"(0x3f800000u) : "memory");
                if (!OPD_EARLY && lane == 0) mbar_arrive(bars + 8 * B_OPDONE);
                SCHED_FENCE();
                TS(7);
            }
            {
                const float ix0 = rcp(sx[0]), ix1 = rcp(sx[1]);
                const uint32_t xo = sb + O_XO + w * 512;
                stsm4t(xo + (lane & 7) * 64 + (((lane >> 3) ^ ((lane >> 1) & 3)) << 4), pack_bf16(ox[0][0] * ix0, ox[0][1] * ix1),
                       pack_bf16(ox[0][2] * ix0, ox[0][3] * ix1), pack_bf16(ox[1][0] * ix0, ox[1][1] * ix1), pack_bf16(ox[1][2] * ix0, ox[1][3] * ix1));
                __syncwarp();
                const uint4 ov = lds128u(xo + (lane >> 2) * 64 + (((lane & 3) ^ ((lane >> 3) & 3)) << 4));
                stg128(&g_ox[(size_t)(s * 32 + j * 8 + (lane >> 2)) * 4096 + h * 128 + w * 32 + (lane & 3) * 8], ov.x, ov.y, ov.z, ov.w);
            }
            TS(8);
            if (s == 0) GT(2);
        }
        GT(3);
        sts32(bars + 508, sf);
        TSDUMP();
        bar_sync(7, 512);
        const int m0 = (role >> 3) * 128, nb = (role & 7) * 2;
#define W2_LOAD(st, kt) { mbar_expect_tx(bars + 8 * (B_GF + (st)), 32768); tma3d(sb + (st) * 32768 + 16384, &tm_w2, 0, (kt) * 64, nb, bars + 8 * (B_GF + (st))); }
        if (w == 1 && lane == 0) {
            fence_async_smem();
#pragma unroll 1
            for (int kt = 0; kt < G_ST; kt++) W2_LOAD(kt, kt);
        }
        if (w == 0) {
            gbar_wait(&g_end, gbar_arrive(&g_end, 1, 128, lane), 0);
            int st = 0, ph = 1;
#pragma unroll 1
            for (int kt = 0; kt < 64; kt++) {
                if (kt >= G_ST) mbar_wait(bars + 8 * (B_GE + st), ph);
                if (lane == 0) {
                    if (kt >= G_ST) W2_LOAD(st, kt);
                    tma2d(sb + st * 32768, &tm_o, kt * 64, m0, bars + 8 * (B_GF + st));
                }
                if (++st == G_ST) { st = 0; ph ^= 1; }
            }
        }
    }
}

typedef CUresult (*EncodeFn)(CUtensorMap*, CUtensorMapDataType, cuuint32_t, void*, const cuuint64_t*, const cuuint64_t*,
                             const cuuint32_t*, const cuuint32_t*, CUtensorMapInterleave, CUtensorMapSwizzle,
                             CUtensorMapL2promotion, CUtensorMapFloatOOBfill);

static void make_map(EncodeFn fn, CUtensorMap* m, const void* p, uint64_t cols, uint64_t rows, uint32_t bc, uint32_t br) {
    cuuint64_t dims[2] = {cols, rows}, strides[1] = {cols * 2};
    cuuint32_t box[2] = {bc, br}, es[2] = {1, 1};
    fn(m, CU_TENSOR_MAP_DATA_TYPE_BFLOAT16, 2, (void*)p, dims, strides, box, es, CU_TENSOR_MAP_INTERLEAVE_NONE,
       CU_TENSOR_MAP_SWIZZLE_128B, CU_TENSOR_MAP_L2_PROMOTION_L2_128B, CU_TENSOR_MAP_FLOAT_OOB_FILL_NONE);
}

static Tune h_tune = {480, 1888, 38, 200, 960, 4000, 300};

extern "C" void kernel_launch(void* const* d_in, const int* in_sizes, int n_in, void* d_out, int out_size) {
    static bool init = false;
    static FftMaps fm;
    static CUtensorMap tm_x, tm_wq, tm_wk, tm_wv, tm_wo, tm_o, tm_wo2;
    if (!init) {
        void* fp = nullptr; cudaDriverEntryPointQueryResult qr;
        cudaGetDriverEntryPoint("cuTensorMapEncodeTiled", &fp, cudaEnableDefault, &qr);
        EncodeFn fn = (EncodeFn)fp;
        void* ox = nullptr; cudaGetSymbolAddress(&ox, g_ox);
        {
            cuuint64_t dims[4] = {64, 8, 16, 256}, strides[3] = {2048, 128, 16384};
            cuuint32_t box[4] = {64, 8, 8, 4}, es[4] = {1, 1, 1, 1};
            fn(&tm_x, CU_TENSOR_MAP_DATA_TYPE_BFLOAT16, 4, d_in[3], dims, strides, box, es, CU_TENSOR_MAP_INTERLEAVE_NONE,
               CU_TENSOR_MAP_SWIZZLE_128B, CU_TENSOR_MAP_L2_PROMOTION_L2_128B, CU_TENSOR_MAP_FLOAT_OOB_FILL_NONE);
        }
        void* fy = nullptr; cudaGetSymbolAddress(&fy, g_fy);
        for (int i = 0; i < 3; i++) {
            const cuuint64_t pitch = i == 2 ? 4096 : 2048;
            cuuint64_t dims[4] = {1024, 8, 16, 16}, strides[3] = {pitch, 128 * pitch, 8 * pitch};
            cuuint32_t box[4] = {64, 1, 16, 16}, es[4] = {1, 1, 1, 1};
            fn(i == 0 ? &fm.x : i == 1 ? &fm.y : &fm.o, CU_TENSOR_MAP_DATA_TYPE_BFLOAT16, 4, i == 0 ? d_in[0] : i == 1 ? fy : d_out, dims, strides, box, es,
               CU_TENSOR_MAP_INTERLEAVE_NONE, CU_TENSOR_MAP_SWIZZLE_128B, CU_TENSOR_MAP_L2_PROMOTION_L2_256B, CU_TENSOR_MAP_FLOAT_OOB_FILL_NONE);
        }
        {
            cuuint64_t dims[3] = {64, 2048, 16}, strides[2] = {2048, 128};
            cuuint32_t box[3] = {64, 8, 16}, es[3] = {1, 1, 1};
            fn(&fm.y2, CU_TENSOR_MAP_DATA_TYPE_BFLOAT16, 3, fy, dims, strides, box, es, CU_TENSOR_MAP_INTERLEAVE_NONE,
               CU_TENSOR_MAP_SWIZZLE_128B, CU_TENSOR_MAP_L2_PROMOTION_L2_128B, CU_TENSOR_MAP_FLOAT_OOB_FILL_NONE);
        }
        for (int i = 0; i < 2; i++) {
            cuuint64_t dims[3] = {256 * 513 - 448, 8, 8}, strides[2] = {128, 256 * 1026};
            cuuint32_t box[3] = {72, 8, 8}, es[3] = {1, 1, 1};
            fn(i ? &fm.wi : &fm.wr, CU_TENSOR_MAP_DATA_TYPE_BFLOAT16, 3, d_in[1 + i], dims, strides, box, es, CU_TENSOR_MAP_INTERLEAVE_NONE,
               CU_TENSOR_MAP_SWIZZLE_NONE, CU_TENSOR_MAP_L2_PROMOTION_L2_128B, CU_TENSOR_MAP_FLOAT_OOB_FILL_NONE);
        }
        make_map(fn, &tm_wq, d_in[5], 4096, 1024, 64, 256);
        make_map(fn, &tm_wk, d_in[6], 4096, 1024, 64, 256);
        make_map(fn, &tm_wv, d_in[7], 4096, 1024, 64, 256);
        make_map(fn, &tm_wo, d_in[8], 1024, 4096, 64, 128);
        make_map(fn, &tm_o, ox, 4096, 2048, 64, 128);
        {
            cuuint64_t dims[3] = {64, 4096, 16}, strides[2] = {2048, 128};
            cuuint32_t box[3] = {64, 64, 2}, es[3] = {1, 1, 1};
            fn(&tm_wo2, CU_TENSOR_MAP_DATA_TYPE_BFLOAT16, 3, d_in[8], dims, strides, box, es, CU_TENSOR_MAP_INTERLEAVE_NONE,
               CU_TENSOR_MAP_SWIZZLE_128B, CU_TENSOR_MAP_L2_PROMOTION_L2_128B, CU_TENSOR_MAP_FLOAT_OOB_FILL_NONE);
        }
        cudaFuncSetAttribute(rmt_main, cudaFuncAttributeMaxDynamicSharedMemorySize, MAIN_SMEM);
        init = true;
    }
    rmt_main<<<132, 512, MAIN_SMEM>>>(tm_x, tm_wq, tm_wk, tm_wv, tm_wo, (const bf16*)d_in[4], h_tune, fm, tm_o, tm_wo2, (bf16*)d_out);
}
```

```cpp
#include <cuda_runtime.h>
#include <cuda_bf16.h>
#include <cuda.h>
#include <stdint.h>

typedef __nv_bfloat16 bf16;

#define DBG_TIMING 0

#define SPIN_LIMIT (1u << 22)

__device__ __forceinline__ uint32_t smem_u32(const void* p) { return (uint32_t)__cvta_generic_to_shared(p); }
__device__ __forceinline__ uint32_t clk() { uint32_t c; asm volatile("mov.u32 %0, %%clock;" : "=r"(c)::"memory"); return c; }
#define SCHED_FENCE() sf ^= (uint32_t)clock64()
#define KEEP2(a, b) asm volatile("lop3.b32 %0, %0, %1, %2, 0x96;" : "+r"(sf) : "r"((uint32_t)(a)), "r"((uint32_t)(b)))
#define KEEPP(p) KEEP2((uintptr_t)(p), (uintptr_t)(p) >> 32)
__device__ __forceinline__ uint32_t gtime() { uint32_t c; asm volatile("mov.u32 %0, %%globaltimer_lo;" : "=r"(c)::"memory"); return c; }
__device__ __forceinline__ void wait_clk(uint32_t t0, uint32_t d) {
    asm volatile("{\n.reg .pred p;\n.reg .s32 t;\n.reg .b64 c;\nWL:\nmov.u64 c, %%clock64;\ncvt.u32.u64 t, c;\nsub.s32 t, t, %0;\nsetp.lt.s32 p, t, 0;\n@p bra.uni WL;\n}" ::"r"(t0 + d) : "memory");
}
__device__ __forceinline__ void wait_gtime(uint32_t t1) {
    asm volatile("{\n.reg .pred p;\n.reg .s32 t;\n.reg .b64 c;\nWL:\nmov.u64 c, %%globaltimer;\ncvt.u32.u64 t, c;\nsub.s32 t, t, %0;\nsetp.lt.s32 p, t, 0;\n@p bra.uni WL;\n}" ::"r"(t1) : "memory");
}

__device__ __forceinline__ void mbar_init(uint32_t bar, uint32_t cnt) {
    asm volatile("mbarrier.init.shared::cta.b64 [%0], %1;" ::"r"(bar), "r"(cnt) : "memory");
}
__device__ __forceinline__ void mbar_arrive(uint32_t bar) {
    asm volatile("mbarrier.arrive.shared::cta.b64 _, [%0];" ::"r"(bar) : "memory");
}
__device__ __forceinline__ void mbar_expect_tx(uint32_t bar, uint32_t bytes) {
    asm volatile("mbarrier.arrive.expect_tx.shared::cta.b64 _, [%0], %1;" ::"r"(bar), "r"(bytes) : "memory");
}
__device__ __forceinline__ void mbar_wait(uint32_t bar, uint32_t parity) {
    asm volatile(
        "{\n.reg .pred p, q;\n.reg .u32 n;\nmov.u32 n, 0;\n"
        "WL:\nmbarrier.try_wait.parity.shared::cta.b64 p, [%0], %1;\n"
        "add.u32 n, n, 1;\nsetp.gt.u32 q, n, %2;\n@q trap;\n@!p bra.uni WL;\n}" ::"r"(bar), "r"(parity), "n"(SPIN_LIMIT) : "memory");
}
__device__ __forceinline__ void mbar_wait_cluster(uint32_t bar, uint32_t parity) {
    asm volatile(
        "{\n.reg .pred p, q;\n.reg .u32 n;\nmov.u32 n, 0;\n"
        "WL:\nmbarrier.try_wait.parity.acquire.cluster.shared::cta.b64 p, [%0], %1;\n"
        "add.u32 n, n, 1;\nsetp.gt.u32 q, n, %2;\n@q trap;\n@!p bra.uni WL;\n}" ::"r"(bar), "r"(parity), "n"(SPIN_LIMIT) : "memory");
}
__device__ __forceinline__ void tma2d(uint32_t dst, const CUtensorMap* m, int c0, int c1, uint32_t bar) {
    asm volatile("cp.async.bulk.tensor.2d.shared::cluster.global.mbarrier::complete_tx::bytes [%0], [%1, {%3, %4}], [%2];"
                 ::"r"(dst), "l"(m), "r"(bar), "r"(c0), "r"(c1) : "memory");
}
__device__ __forceinline__ void tma3d(uint32_t dst, const CUtensorMap* m, int c0, int c1, int c2, uint32_t bar) {
    asm volatile("cp.async.bulk.tensor.3d.shared::cluster.global.mbarrier::complete_tx::bytes [%0], [%1, {%3, %4, %5}], [%2];"
                 ::"r"(dst), "l"(m), "r"(bar), "r"(c0), "r"(c1), "r"(c2) : "memory");
}
__device__ __forceinline__ void tma4d(uint32_t dst, const CUtensorMap* m, int c2, int c3, uint32_t bar) {
    asm volatile("cp.async.bulk.tensor.4d.shared::cluster.global.mbarrier::complete_tx::bytes [%0], [%1, {%5, %5, %3, %4}], [%2];"
                 ::"r"(dst), "l"(m), "r"(bar), "r"(c2), "r"(c3), "r"(0) : "memory");
}
__device__ __forceinline__ void bulk_g2s(uint32_t dst, const void* src, uint32_t bytes, uint32_t bar) {
    asm volatile("cp.async.bulk.shared::cluster.global.mbarrier::complete_tx::bytes [%0], [%1], %2, [%3];"
                 ::"r"(dst), "l"(src), "r"(bytes), "r"(bar) : "memory");
}
__device__ __forceinline__ void tma4d_prefetch(const CUtensorMap* m, int c2, int c3) {
    asm volatile("cp.async.bulk.prefetch.tensor.4d.L2.global [%0, {%3, %3, %1, %2}];" ::"l"(m), "r"(c2), "r"(c3), "r"(0) : "memory");
}
__device__ __forceinline__ void tma2d_prefetch(const CUtensorMap* m, int c0, int c1) {
    asm volatile("cp.async.bulk.prefetch.tensor.2d.L2.global [%0, {%1, %2}];" ::"l"(m), "r"(c0), "r"(c1) : "memory");
}
__device__ __forceinline__ void fence_async_smem() { asm volatile("fence.proxy.async.shared::cta;" ::: "memory"); }
__device__ __forceinline__ void fence_gpu() { asm volatile("fence.acq_rel.gpu;" ::: "memory"); }
__device__ __forceinline__ float rcp(float x) { float r; asm("rcp.approx.ftz.f32 %0, %1;" : "=f"(r) : "f"(x)); return r; }
__device__ __forceinline__ void bar_sync(int id, int n) { asm volatile("bar.sync %0, %1;" ::"r"(id), "r"(n) : "memory"); }

__device__ __forceinline__ bool bar_or(int id, int n, uint32_t x) {
    uint32_t r;
    asm volatile("{\n.reg .pred p, q;\n.reg .b32 t;\nand.b32 t, %3, 1;\nsetp.ne.u32 p, t, 0;\nbar.red.or.pred q, %1, %2, p;\nselp.u32 %0, 1, 0, q;\n}"
                 : "=r"(r) : "r"(id), "r"(n), "r"(x) : "memory");
    return __any_sync(~0u, r);
}
__device__ __forceinline__ uint32_t or3(uint32_t a, uint32_t b, uint32_t c) {
    uint32_t r; asm("lop3.b32 %0, %1, %2, %3, 0xFE;" : "=r"(r) : "r"(a), "r"(b), "r"(c)); return r;
}
__device__ __forceinline__ uint32_t pack_bf16(float lo, float hi) {
    uint32_t r; asm("cvt.rn.bf16x2.f32 %0, %1, %2;" : "=r"(r) : "f"(hi), "f"(lo)); return r;
}
__device__ __forceinline__ uint32_t add_bf16x2(uint32_t a, uint32_t b) {
    uint32_t r; asm volatile("add.rn.bf16x2 %0, %1, %2;" : "=r"(r) : "r"(a), "r"(b)); return r;
}
__device__ __forceinline__ uint32_t movm(uint32_t a) {
    uint32_t r; asm volatile("movmatrix.sync.aligned.m8n8.trans.b16 %0, %1;" : "=r"(r) : "r"(a)); return r;
}
__device__ __forceinline__ uint32_t orx(uint32_t acc, uint32_t a, uint32_t t) {
    uint32_t r; asm("lop3.b32 %0, %1, %2, %3, 0xF6;" : "=r"(r) : "r"(acc), "r"(a), "r"(t)); return r;
}
__device__ __forceinline__ uint32_t orx2(uint32_t a, uint32_t b, uint32_t t) {
    uint32_t r; asm("lop3.b32 %0, %1, %2, %3, 0x7E;" : "=r"(r) : "r"(a), "r"(b), "r"(t)); return r;
}
__device__ __forceinline__ float ex2(float x) { float r; asm("ex2.approx.ftz.f32 %0, %1;" : "=f"(r) : "f"(x)); return r; }
__device__ __forceinline__ void ldsm4t(uint32_t (&r)[4], uint32_t a) {
    asm volatile("ldmatrix.sync.aligned.m8n8.x4.trans.shared.b16 {%0,%1,%2,%3}, [%4];"
                 : "=r"(r[0]), "=r"(r[1]), "=r"(r[2]), "=r"(r[3]) : "r"(a) : "memory");
}
__device__ __forceinline__ void ldsm4(uint32_t (&r)[4], uint32_t a) {
    asm volatile("ldmatrix.sync.aligned.m8n8.x4.shared.b16 {%0,%1,%2,%3}, [%4];"
                 : "=r"(r[0]), "=r"(r[1]), "=r"(r[2]), "=r"(r[3]) : "r"(a) : "memory");
}
__device__ __forceinline__ void stsm4t(uint32_t a, uint32_t r0, uint32_t r1, uint32_t r2, uint32_t r3) {
    asm volatile("stmatrix.sync.aligned.m8n8.x4.trans.shared.b16 [%0], {%1,%2,%3,%4};"
                 ::"r"(a), "r"(r0), "r"(r1), "r"(r2), "r"(r3) : "memory");
}
__device__ __forceinline__ void stsm4(uint32_t a, uint32_t r0, uint32_t r1, uint32_t r2, uint32_t r3) {
    asm volatile("stmatrix.sync.aligned.m8n8.x4.shared.b16 [%0], {%1,%2,%3,%4};"
                 ::"r"(a), "r"(r0), "r"(r1), "r"(r2), "r"(r3) : "memory");
}
__device__ __forceinline__ void mma16816(float* c, uint32_t a0, uint32_t a1, uint32_t a2, uint32_t a3, uint32_t b0, uint32_t b1) {
    asm volatile("mma.sync.aligned.m16n8k16.row.col.f32.bf16.bf16.f32 {%0,%1,%2,%3}, {%4,%5,%6,%7}, {%8,%9}, {%0,%1,%2,%3};"
                 : "+f"(c[0]), "+f"(c[1]), "+f"(c[2]), "+f"(c[3]) : "r"(a0), "r"(a1), "r"(a2), "r"(a3), "r"(b0), "r"(b1));
}
__device__ __forceinline__ void mma1688(float* c, uint32_t a0, uint32_t a1, uint32_t b0) {
    asm volatile("mma.sync.aligned.m16n8k8.row.col.f32.bf16.bf16.f32 {%0,%1,%2,%3}, {%4,%5}, {%6}, {%0,%1,%2,%3};"
                 : "+f"(c[0]), "+f"(c[1]), "+f"(c[2]), "+f"(c[3]) : "r"(a0), "r"(a1), "r"(b0));
}
__device__ __forceinline__ void sts128(uint32_t a, float x, float y, float z, float w) {
    asm volatile("st.shared.v4.f32 [%0], {%1,%2,%3,%4};" ::"r"(a), "f"(x), "f"(y), "f"(z), "f"(w) : "memory");
}
__device__ __forceinline__ void sts64(uint32_t a, float x, float y) {
    asm volatile("st.shared.v2.f32 [%0], {%1,%2};" ::"r"(a), "f"(x), "f"(y) : "memory");
}
__device__ __forceinline__ void sts32(uint32_t a, uint32_t x) { asm volatile("st.shared.b32 [%0], %1;" ::"r"(a), "r"(x) : "memory"); }
__device__ __forceinline__ void sts128u(uint32_t a, uint4 v) {
    asm volatile("st.shared.v4.b32 [%0], {%1,%2,%3,%4};" ::"r"(a), "r"(v.x), "r"(v.y), "r"(v.z), "r"(v.w) : "memory");
}
__device__ __forceinline__ float4 lds128(uint32_t a) {
    float4 v; asm volatile("ld.shared.v4.f32 {%0,%1,%2,%3}, [%4];" : "=f"(v.x), "=f"(v.y), "=f"(v.z), "=f"(v.w) : "r"(a) : "memory"); return v;
}
__device__ __forceinline__ uint4 lds128u(uint32_t a) {
    uint4 v; asm volatile("ld.shared.v4.b32 {%0,%1,%2,%3}, [%4];" : "=r"(v.x), "=r"(v.y), "=r"(v.z), "=r"(v.w) : "r"(a) : "memory"); return v;
}
__device__ __forceinline__ uint4 lds128v(uint32_t a) {
    uint4 v; asm volatile("ld.volatile.shared.v4.b32 {%0,%1,%2,%3}, [%4];" : "=r"(v.x), "=r"(v.y), "=r"(v.z), "=r"(v.w) : "r"(a) : "memory"); return v;
}
__device__ __forceinline__ void sts64u(uint32_t a, uint2 v) { asm volatile("st.shared.v2.b32 [%0], {%1,%2};" ::"r"(a), "r"(v.x), "r"(v.y) : "memory"); }
__device__ __forceinline__ uint2 lds64u(uint32_t a) {
    uint2 v; asm volatile("ld.shared.v2.b32 {%0,%1}, [%2];" : "=r"(v.x), "=r"(v.y) : "r"(a) : "memory"); return v;
}
__device__ __forceinline__ float2 lds64(uint32_t a) {
    float2 v; asm volatile("ld.shared.v2.f32 {%0,%1}, [%2];" : "=f"(v.x), "=f"(v.y) : "r"(a) : "memory"); return v;
}
__device__ __forceinline__ uint2 ldg_rlx64(const void* p) {
    uint2 v; asm volatile("ld.relaxed.gpu.global.v2.b32 {%0,%1}, [%2];" : "=r"(v.x), "=r"(v.y) : "l"(p) : "memory"); return v;
}
__device__ __forceinline__ uint4 ldg_rlx128(const void* p) {
    uint4 v; asm volatile("ld.relaxed.gpu.global.v4.b32 {%0,%1,%2,%3}, [%4];" : "=r"(v.x), "=r"(v.y), "=r"(v.z), "=r"(v.w) : "l"(p) : "memory"); return v;
}
__device__ __forceinline__ void stg_rlx64(void* p, uint32_t x, uint32_t y) {
    asm volatile("st.relaxed.gpu.global.v2.b32 [%0], {%1,%2};" ::"l"(p), "r"(x), "r"(y) : "memory");
}
__device__ __forceinline__ void stg_rlx128(void* p, uint32_t x, uint32_t y, uint32_t z, uint32_t w) {
    asm volatile("st.relaxed.gpu.global.v4.b32 [%0], {%1,%2,%3,%4};" ::"l"(p), "r"(x), "r"(y), "r"(z), "r"(w) : "memory");
}
__device__ __forceinline__ uint32_t ldg_rlx32(const void* p) {
    uint32_t v; asm volatile("ld.relaxed.gpu.global.b32 %0, [%1];" : "=r"(v) : "l"(p) : "memory"); return v;
}
__device__ __forceinline__ void stg128(void* p, uint32_t x, uint32_t y, uint32_t z, uint32_t w) {
    asm volatile("st.global.v4.b32 [%0], {%1,%2,%3,%4};" ::"l"(p), "r"(x), "r"(y), "r"(z), "r"(w) : "memory");
}
__device__ __forceinline__ uint32_t ld_acquire(const unsigned* p) {
    uint32_t v; asm volatile("ld.acquire.gpu.global.u32 %0, [%1];" : "=r"(v) : "l"(p) : "memory"); return v;
}
__device__ __forceinline__ void red_add_u32(unsigned* p, uint32_t v) {
    asm volatile("red.relaxed.gpu.global.add.u32 [%0], %1;" ::"l"(p), "r"(v) : "memory");
}
__device__ __forceinline__ void wait_counter(const unsigned* p, uint32_t target) {
    uint32_t n = 0;
    while (ld_acquire(p) < target) { if (++n > SPIN_LIMIT) __trap(); }
}

__device__ __forceinline__ void wg_fence() { asm volatile("wgmma.fence.sync.aligned;" ::: "memory"); }
__device__ __forceinline__ void wg_commit() { asm volatile("wgmma.commit_group.sync.aligned;" ::: "memory"); }
template <int N> __device__ __forceinline__ void wg_wait() { asm volatile("wgmma.wait_group.sync.aligned %0;" ::"n"(N) : "memory"); }
__host__ __device__ constexpr uint64_t mkdesc(uint32_t addr, uint32_t lbo, uint32_t sbo, uint32_t swz) {
    return (uint64_t)((addr & 0x3FFFF) >> 4) | ((uint64_t)(lbo >> 4) << 16) | ((uint64_t)(sbo >> 4) << 32) | ((uint64_t)swz << 62);
}
#define F4(d, o) "+f"(d[o]), "+f"(d[o + 1]), "+f"(d[o + 2]), "+f"(d[o + 3])
template <int SC> __device__ __forceinline__ void wg_rs32(float (&d)[16], const uint32_t (&a)[4], uint64_t db) {
    asm volatile("wgmma.mma_async.sync.aligned.m64n32k16.f32.bf16.bf16 "
                 "{%0,%1,%2,%3,%4,%5,%6,%7,%8,%9,%10,%11,%12,%13,%14,%15}, {%16,%17,%18,%19}, %20, %21, 1, 1, 0;"
                 : F4(d, 0), F4(d, 4), F4(d, 8), F4(d, 12)
                 : "r"(a[0]), "r"(a[1]), "r"(a[2]), "r"(a[3]), "l"(db), "n"(SC));
}
template <int SC> __device__ __forceinline__ void wg_rs40(float (&d)[20], const uint32_t (&a)[4], uint64_t db) {
    asm volatile("wgmma.mma_async.sync.aligned.m64n40k16.f32.bf16.bf16 "
                 "{%0,%1,%2,%3,%4,%5,%6,%7,%8,%9,%10,%11,%12,%13,%14,%15,%16,%17,%18,%19}, {%20,%21,%22,%23}, %24, %25, 1, 1, 0;"
                 : F4(d, 0), F4(d, 4), F4(d, 8), F4(d, 12), F4(d, 16)
                 : "r"(a[0]), "r"(a[1]), "r"(a[2]), "r"(a[3]), "l"(db), "n"(SC));
}
template <int SC> __device__ __forceinline__ void wg_ss40(float (&d)[20], uint64_t da, uint64_t db) {
    asm volatile("wgmma.mma_async.sync.aligned.m64n40k16.f32.bf16.bf16 "
                 "{%0,%1,%2,%3,%4,%5,%6,%7,%8,%9,%10,%11,%12,%13,%14,%15,%16,%17,%18,%19}, %20, %21, %22, 1, 1, 1, 0;"
                 : F4(d, 0), F4(d, 4), F4(d, 8), F4(d, 12), F4(d, 16)
                 : "l"(da), "l"(db), "n"(SC));
}
template <int SC> __device__ __forceinline__ void wg_ss8(float (&d)[4], uint64_t da, uint64_t db) {
    asm volatile("wgmma.mma_async.sync.aligned.m64n8k16.f32.bf16.bf16 {%0,%1,%2,%3}, %4, %5, %6, 1, 1, 1, 1;"
                 : F4(d, 0) : "l"(da), "l"(db), "n"(SC));
}

constexpr int DBG_N = 11;
#define LT(st, k, v) do {} while (0)
#define TSI(st) do {} while (0)
#define TS(k) do {} while (0)
#define TSV(k, v) do {} while (0)
#define TSDUMP() do {} while (0)
#define GT(k) do {} while (0)

__device__ __align__(256) uint4 g_fy[2048 * 128];

constexpr uint32_t FG_SIZE = 2 * 32768 + 36864;
constexpr uint32_t FT_F16 = 2 * FG_SIZE, FT_B1F = FT_F16 + 2048, FT_B1I = FT_B1F + 2048, FT_C = FT_B1I + 2048, FT_A8 = FT_C + 2048,
                   FT_TWC = FT_A8 + 512, FT_TWB = FT_TWC + 8192, FT_BAR = FT_TWB + 8192, FFT_SMEM = FT_BAR + 256;
struct FftMaps { CUtensorMap x, y, o, y2, wr, wi; };

__device__ __forceinline__ float2 wroot(int e) {
    float s, c; sincospif((float)(e & 2047) * (-1.f / 1024.f), &s, &c); return make_float2(c, s);
}
__device__ __forceinline__ uint4 afrag(float2 a, float2 b) {
    return make_uint4(pack_bf16(a.x, -a.y), pack_bf16(a.y, a.x), pack_bf16(b.x, -b.y), pack_bf16(b.y, b.x));
}
__device__ __forceinline__ uint4 conjfrag(uint4 v) { return make_uint4(v.x ^ 0x80000000u, v.y ^ 0x8000u, v.z ^ 0x80000000u, v.w ^ 0x8000u); }
__device__ __forceinline__ uint4 negfrag(uint4 v) { return make_uint4(v.x ^ 0x80008000u, v.y ^ 0x80008000u, v.z ^ 0x80008000u, v.w ^ 0x80008000u); }
__device__ __forceinline__ uint32_t comp(const uint4& v, int i) { return i == 0 ? v.x : i == 1 ? v.y : i == 2 ? v.z : v.w; }
__device__ __forceinline__ void setcomp(uint4& v, int i, uint32_t x) { if (i == 0) v.x = x; else if (i == 1) v.y = x; else if (i == 2) v.z = x; else v.w = x; }
__device__ __forceinline__ float2 cmul(float2 a, float2 b) { return make_float2(a.x * b.x - a.y * b.y, a.x * b.y + a.y * b.x); }
__device__ __forceinline__ float2 cmulc(float2 a, float2 b) { return make_float2(a.x * b.x + a.y * b.y, a.y * b.x - a.x * b.y); }

__device__ __forceinline__ uint32_t pack_h2(float2 a) { uint32_t r; asm("cvt.rn.f16x2.f32 %0, %1, %2;" : "=r"(r) : "f"(a.y), "f"(a.x)); return r; }
__device__ __forceinline__ float2 unpack_h2(uint32_t v) {
    float2 r; asm("{\n.reg .b16 l, h;\nmov.b32 {l, h}, %2;\ncvt.f32.f16 %0, l;\ncvt.f32.f16 %1, h;\n}" : "=f"(r.x), "=f"(r.y) : "r"(v)); return r;
}
__device__ __forceinline__ void fft_tables(uint32_t tb, int tid, int nthr) {
    for (int i = tid; i < 128; i += nthr) {
        const int lane = i & 31, q = i >> 5, g = lane >> 2, t = lane & 3, o = 8 * (q >> 1) + g, in = 8 * (q & 1) + 2 * t;
        sts128u(tb + FT_F16 + i * 16, afrag(wroot(128 * o * in), wroot(128 * o * (in + 1))));
        sts128u(tb + FT_B1F + i * 16, afrag(wroot(64 * (1 + 2 * o) * in), wroot(64 * (1 + 2 * o) * (in + 1))));
        sts128u(tb + FT_B1I + i * 16, afrag(wroot(-64 * o * (1 + 2 * in)), wroot(-64 * o * (3 + 2 * in))));
        uint4 v;
        for (int r = 0; r < 4; r++) {
            const float2 a = wroot(128 * (4 * r + t) * (4 * q + (g >> 1)));
            setcomp(v, r, (g & 1) ? pack_bf16(a.y, a.x) : pack_bf16(a.x, -a.y));
        }
        sts128u(tb + FT_C + i * 16, v);
        if (q == 0) sts128u(tb + FT_A8 + lane * 16, afrag(wroot(256 * g * 2 * t), wroot(256 * g * (2 * t + 1))));
    }
    for (int i = tid; i < 512; i += nthr) {
        const int lane = i & 31, r = (i >> 5) & 3, phi = 8 * (i >> 7) + (lane >> 2), c = 4 * r + (lane & 3);
        const float2 a = wroot(4 * c * phi), b = wroot(2 * (phi + 32 * c));
        constexpr float SC = 1.f / (2.f * 2048.f * 512.f);
        sts128(tb + FT_TWC + i * 16, a.x * SC, a.y * SC, b.x, b.y);
    }
    for (int i = tid; i < 512; i += nthr) {
        const int lane = i & 31, r = (i >> 5) & 3, fa = (i >> 7) & 1, hf = i >> 8, c = 8 * (lane & 1) + r;
        const int p0 = fa + 2 * (lane >> 2), p1 = p0 + 16, s0 = (hf && p0) ? 32 - p0 : p0, s1 = hf ? 32 - p1 : p1;
        sts128u(tb + FT_TWB + i * 16, make_uint4(pack_h2(wroot(4 * c * s0)), pack_h2(wroot(4 * (c + 4) * s0)),
                                                 pack_h2(wroot(4 * c * s1)), pack_h2(wroot(4 * (c + 4) * s1))));
    }
}

template <bool TW>
__device__ __forceinline__ void dft16(uint4 (&out)[4], const uint4 (&in)[4], const uint4 (&m)[4], const uint4 (&tw)[4]) {
#pragma unroll
    for (int i = 0; i < 4; i++)
#pragma unroll
        for (int mt = 0; mt < 2; mt++) {
            float c[4] = {0.f, 0.f, 0.f, 0.f};
            mma16816(c, m[2 * mt].x, m[2 * mt].y, m[2 * mt].z, m[2 * mt].w, comp(in[0], i), comp(in[1], i));
            mma16816(c, m[2 * mt + 1].x, m[2 * mt + 1].y, m[2 * mt + 1].z, m[2 * mt + 1].w, comp(in[2], i), comp(in[3], i));
            if (TW) {
                const float2 a = cmul(make_float2(c[0], c[2]), unpack_h2(comp(tw[i], 2 * mt))), b = cmul(make_float2(c[1], c[3]), unpack_h2(comp(tw[i], 2 * mt + 1)));
                setcomp(out[2 * mt], i, pack_bf16(a.x, a.y));
                setcomp(out[2 * mt + 1], i, pack_bf16(b.x, b.y));
            } else {
                setcomp(out[2 * mt], i, pack_bf16(c[0], c[2]));
                setcomp(out[2 * mt + 1], i, pack_bf16(c[1], c[3]));
            }
        }
}
__device__ __forceinline__ void tma_ld4(uint32_t dst, const CUtensorMap* m, int c0, int c1, uint32_t bar) {
    asm volatile("cp.async.bulk.tensor.4d.shared::cluster.global.mbarrier::complete_tx::bytes [%0], [%1, {%3, %4, %5, %5}], [%2];"
                 ::"r"(dst), "l"(m), "r"(bar), "r"(c0), "r"(c1), "r"(0) : "memory");
}
__device__ __forceinline__ void tma_st4(uint32_t src, const CUtensorMap* m, int c0, int c1) {
    asm volatile("cp.async.bulk.tensor.4d.global.shared::cta.bulk_group [%1, {%2, %3, %4, %4}], [%0];" ::"r"(src), "l"(m), "r"(c0), "r"(c1), "r"(0) : "memory");
}
__device__ __forceinline__ void tma_ld3(uint32_t dst, const CUtensorMap* m, int c0, int c1, uint32_t bar) {
    asm volatile("cp.async.bulk.tensor.3d.shared::cluster.global.mbarrier::complete_tx::bytes [%0], [%1, {%3, %4, %5}], [%2];"
                 ::"r"(dst), "l"(m), "r"(bar), "r"(c0), "r"(c1), "r"(0) : "memory");
}
__device__ __forceinline__ void tma_st3(uint32_t src, const CUtensorMap* m, int c0, int c1) {
    asm volatile("cp.async.bulk.tensor.3d.global.shared::cta.bulk_group [%1, {%2, %3, %4}], [%0];" ::"r"(src), "l"(m), "r"(c0), "r"(c1), "r"(0) : "memory");
}
__device__ __forceinline__ void bulk_commit() { asm volatile("cp.async.bulk.commit_group;" ::: "memory"); }
__device__ __forceinline__ void bulk_wait_read() { asm volatile("cp.async.bulk.wait_group.read 0;" ::: "memory"); }
__device__ __forceinline__ void bulk_wait_all() { asm volatile("cp.async.bulk.wait_group 0;" ::: "memory"); }

__device__ __forceinline__ float2 wroot_fast(int e) {
    float s, c; __sincosf((float)(((e + 1024) & 2047) - 1024) * (-3.14159265358979f / 1024.f), &s, &c); return make_float2(c, s);
}
template <bool INV, int NT>
__device__ __forceinline__ void fft_col(int s2, int t0, const CUtensorMap* src, const CUtensorMap* dst, uint32_t gb, uint32_t mb,
                                        int w, int lane, int bar) {
    const int g = lane >> 2, t = lane & 3;
    const bool lead = w == 4 && lane == 0;
    if (NT > 1 && lead)
        for (int i = 0; i < 2; i++) { mbar_expect_tx(mb + 8 * i, 32768); tma_ld4(gb + i * 32768, src, (t0 + i) * 64, s2, mb + 8 * i); }
    uint4 f[4], m[2][4];
#pragma unroll
    for (int i = 0; i < 4; i++) {
        const int o = 8 * (i >> 1) + g, in = 8 * (i & 1) + 2 * t, sg = INV ? -128 : 128;
        f[i] = afrag(wroot_fast(sg * o * in), wroot_fast(sg * o * (in + 1)));
#pragma unroll
        for (int q = 0; q < 2; q++) {
            const int z = 2 * w + q;
            m[q][i] = INV ? afrag(wroot_fast(-(8 * o + s2) * (z + 16 * in)), wroot_fast(-(8 * o + s2) * (z + 16 * in + 16)))
                          : afrag(wroot_fast((z + 16 * o) * (8 * in + s2)), wroot_fast((z + 16 * o) * (8 * in + 8 + s2)));
        }
    }
    const uint32_t r1 = (32 * w + 2 * t) * 128 + ((g ^ (2 * t)) << 4);
    const uint32_t w1 = (32 * w + g) * 128 + (((2 * t) ^ (((w & 3) << 1) | (g & 1))) << 4);
    const uint32_t r2 = (32 * t + 2 * w) * 128 + ((g ^ (2 * t)) << 4);
    const uint32_t w2 = (32 * w + g) * 128 + (((2 * t) ^ g) << 4);
    int bi = 0, ph = 0;
#pragma unroll 1
    for (int it = 0; it < NT; it++) {
        const uint32_t buf = gb + bi * 32768;
        mbar_wait(mb + 8 * bi, ph);
        uint4 in[2][4], out[4];
#pragma unroll
        for (int q = 0; q < 2; q++)
#pragma unroll
            for (int i = 0; i < 4; i++) in[q][i] = lds128u(buf + (r1 ^ ((i & 1) * 0x90)) + (i >> 1) * 1024 + q * 2048);
        __syncwarp();
#pragma unroll
        for (int q = 0; q < 2; q++) {
            if (INV) dft16<false>(out, in[q], m[q], f); else dft16<false>(out, in[q], f, f);
#pragma unroll
            for (int i = 0; i < 4; i++) sts128u(buf + (w1 ^ ((i & 1) << 4)) + (i >> 1) * 1024 + q * 2048, out[i]);
        }
        bar_sync(bar, 256);
#pragma unroll
        for (int q = 0; q < 2; q++)
#pragma unroll
            for (int i = 0; i < 4; i++) in[q][i] = lds128u(buf + (r2 ^ (q * 0x90)) + (i & 1) * 2048 + (i >> 1) * 16384);
        const int bn = bi == 0 ? 2 : bi - 1;
        if (lead && it < NT - 2) { bulk_wait_read(); mbar_expect_tx(mb + 8 * bn, 32768); tma_ld4(gb + bn * 32768, src, (t0 + it + 2) * 64, s2, mb + 8 * bn); }
        bar_sync(bar, 256);
#pragma unroll
        for (int q = 0; q < 2; q++) {
            if (INV) dft16<false>(out, in[q], f, f); else dft16<false>(out, in[q], m[q], f);
#pragma unroll
            for (int i = 0; i < 4; i++) sts128u(buf + (w2 ^ ((i & 1) << 4)) + (i >> 1) * 1024 + q * 2048, out[i]);
        }
        fence_async_smem();
        bar_sync(bar, 256);
        if (NT > 1 && lead) { tma_st4(buf, dst, (t0 + it) * 64, s2); bulk_commit(); }
        if (++bi == 3) { bi = 0; ph ^= 1; }
    }
    if (NT > 1 && lead) bulk_wait_read();
}

__device__ __forceinline__ float ldw(uint32_t a) {
    uint16_t v; asm volatile("ld.shared.u16 %0, [%1];" : "=h"(v) : "r"(a) : "memory");
    return __uint_as_float((uint32_t)v << 16);
}
__device__ __forceinline__ void fft_mid(int grp, const FftMaps& fm, uint32_t tb,
                                        uint32_t gb, uint32_t mb, uint32_t& cnt, int w, int lane, int bar) {
    const int g = lane >> 2, t = lane & 3;
    const bool lead = w == 4 && lane == 0;
    const uint32_t wb = gb + 65536;
#define MID_LOAD(k, c)                                                                                                  \
    { mbar_expect_tx(mb + 8 * ((c) & 1), 32768);                                                                        \
      tma_ld3(gb + ((c) & 1) * 32768, &fm.y2, 0, (k) * 8, mb + 8 * ((c) & 1));                                          \
      tma_ld3(gb + ((c) & 1) * 32768 + 16384, &fm.y2, 0, ((256 - (k)) & 255) * 8, mb + 8 * ((c) & 1)); }
#define MID_LOADW(k)                                                                                                    \
    { mbar_expect_tx(mb + 16, 36864);                                                                                   \
      tma_ld3(wb, &fm.wr, (k) * 513 & ~7, 0, mb + 16); tma_ld3(wb + 9216, &fm.wi, (k) * 513 & ~7, 0, mb + 16);          \
      tma_ld3(wb + 18432, &fm.wr, ((256 - (k)) & 255) * 513 & ~7, 0, mb + 16); tma_ld3(wb + 27648, &fm.wi, ((256 - (k)) & 255) * 513 & ~7, 0, mb + 16); }
    if (lead) { MID_LOAD(grp, cnt); MID_LOADW(grp); }
    const int hB = w >> 2, faB = (w >> 1) & 1, xB = faB;
    const int phi = 8 * (w & 3) + g;
    const uint32_t rA = (8 * w + 2 * t) * 128 + ((g ^ (2 * t)) << 4);
    const uint32_t wA = (8 * w + g) * 128 + (((2 * t) ^ ((g & 1) | ((w & 3) << 1))) << 4);
    const uint32_t oB = (w >> 1) * 8192 + (w & 1) * 512;
    const uint32_t rB = oB + (8 * t + (g >> 2)) * 128 + (((g & 3) ^ ((g >> 2) | (t << 1)) ^ xB) << 4);
    const uint32_t wB = oB + (8 * (g >> 1) + (t >> 1)) * 128 + (((((g & 1) << 2) | (2 * (t & 1))) ^ ((t >> 1) | ((g >> 1) << 1)) ^ xB) << 4);
    const uint32_t wBi = oB + (8 * (g >> 1) + (t >> 1)) * 128 + (((((g & 1) << 2) | (2 * (t & 1))) ^ ((t >> 1) | ((w & 1) << 2))) << 4);
    const int hC = (lane >> 3) & 1, pr = 8 * (w & 3) + (lane & 7), pc = hC ? (32 - pr) & 31 : pr;
    const uint32_t aC = hC * 16384 + (pc & 1) * 8192 + (pc >> 2) * 1024 + (((((pc & 2) << 1) | (lane >> 4)) ^ (((pc >> 2) & 3) << 1) ^ (pc & 1)) << 4);
    const uint32_t g0 = wb + (t >> 1) * 144 + (32 * (t & 1) + phi) * 2, g1 = wb + 18432 + (7 - (t >> 1)) * 144 + (64 - 32 * (t & 1) - phi) * 2;
    const uint32_t wAo = (8 * w + g) * 128 + (((2 * t) ^ g) << 4);
    uint32_t wph = 0;
#pragma unroll 1
    for (int k1 = grp; k1 < 129; k1 += 8, cnt++, wph ^= 1) {
        const uint32_t buf = gb + (cnt & 1) * 32768;
        uint4 in[2][4], m[4], out[4];
        m[0] = m[1] = m[2] = lds128u(tb + FT_A8 + lane * 16);
        m[3] = negfrag(m[0]);
        mbar_wait(mb + 8 * (cnt & 1), (cnt >> 1) & 1);
#pragma unroll
        for (int q = 0; q < 2; q++)
#pragma unroll
            for (int i = 0; i < 4; i++) in[q][i] = lds128u(buf + (rA ^ ((i & 1) * 0x90)) + (i >> 1) * 8192 + q * 16384);
        __syncwarp();
#pragma unroll
        for (int q = 0; q < 2; q++) {
            dft16<false>(out, in[q], m, m);
#pragma unroll
            for (int i = 0; i < 4; i++) sts128u(buf + (wA ^ (((i ^ (i >> 1)) & 1) << 4)) + (i >> 1) * 8192 + q * 16384, out[i]);
        }
        {
            uint4 tw[4];
#pragma unroll
            for (int i = 0; i < 4; i++) {
                m[i] = lds128u(tb + (faB ? FT_B1F : FT_F16) + i * 512 + lane * 16);
                if (hB) { m[i].y ^= 0x80008000u; m[i].w ^= 0x80008000u; }
                tw[i] = lds128u(tb + FT_TWB + (w >> 1) * 2048 + i * 512 + lane * 16);
            }
            bar_sync(bar, 256);
#pragma unroll
            for (int q = 0; q < 2; q++)
#pragma unroll
                for (int i = 0; i < 4; i++) in[q][i] = lds128u(buf + (rB ^ ((i & 1) << 6)) + (i >> 1) * 4096 + q * 256);
            __syncwarp();
#pragma unroll
            for (int q = 0; q < 2; q++) {
                dft16<true>(out, in[q], m, tw);
#pragma unroll
                for (int i = 0; i < 4; i++) sts128u(buf + (wB ^ ((i & 1) << 4)) + (i >> 1) * 4096 + q * 256, out[i]);
            }
        }
        {
            const uint32_t cjm = (g & 1) ? 0x8000u : 0x80000000u;
            float4 tw[4];
#pragma unroll
            for (int i = 0; i < 4; i++) { m[i] = lds128u(tb + FT_C + i * 512 + lane * 16); tw[i] = lds128(tb + FT_TWC + ((w & 3) * 4 + i) * 512 + lane * 16); }
            if (lead && k1 + 8 < 129) { bulk_wait_read(); MID_LOAD(k1 + 8, cnt + 1); }
            __syncwarp();
            mbar_wait(mb + 16, wph);
            const uint32_t o0 = (k1 & 7) * 2, o1 = (-k1 & 7) * 2;
            if (w == 1 && lane < 16) {
                const int k2 = lane & 7, k2p = k1 ? 7 - k2 : (8 - k2) & 7;
                const uint32_t p0 = wb + (lane >> 3) * 9216 + k2 * 1152 + o0, p1 = wb + 18432 + (lane >> 3) * 9216 + k2p * 1152 + o1;
                const float sg = lane < 8 ? 0.5f : -0.5f;
                const uint32_t v = pack_bf16(0.5f * ldw(p0) + sg * ldw(p1), 0.5f * ldw(p1 + 1136) + sg * ldw(p0 + 1136));
                asm volatile("st.shared.u16 [%0], %1;" ::"r"(p0), "h"((uint16_t)v) : "memory");
                asm volatile("st.shared.u16 [%0], %1;" ::"r"(p1 + 1136), "h"((uint16_t)(v >> 16)) : "memory");
                fence_async_smem();
            }
            bar_sync(bar, 256);
#define FFT_CU 1
            constexpr int CU = FFT_CU;
#pragma unroll CU
            for (int q = 0; q < 4; q++) {
                const int k2 = 4 * (w >> 2) + q, k2p = k1 ? 7 - k2 : (8 - k2) & 7, kr = hC ? k2p : k2;
                const uint32_t a0 = buf + (aC ^ ((kr & 1) << 4)) + kr * 128;
                const uint32_t r0 = g0 + k2 * 1152 + o0, r1 = g1 + k2p * 1152 + o1;
                uint32_t x[4], y[4];
                ldsm4(x, a0); ldsm4(y, a0 ^ 32);
                float c[4][4];
#pragma unroll
                for (int i = 0; i < 4; i++) { c[i][0] = c[i][1] = c[i][2] = c[i][3] = 0.f; mma16816(c[i], x[0], x[1], x[2], x[3], m[i].x, m[i].y); }
#pragma unroll
                for (int i = 0; i < 4; i++) mma16816(c[i], y[0], y[1], y[2], y[3], m[i].z, m[i].w);
#pragma unroll
                for (int i = 0; i < 4; i++) {
                    const float2 ga = make_float2(ldw(r0 + i * 288), ldw(r0 + 9216 + i * 288));
                    const float2 gc = make_float2(ldw(r1 - i * 288), ldw(r1 + 9216 - i * 288));
                    const float tc = tw[i].z, ts = tw[i].w;
                    const float* z = c[i];
                    const float2 S = make_float2(ga.x + gc.x, ga.y - gc.y), D = make_float2(ga.x - gc.x, ga.y + gc.y);
                    const float2 u = make_float2(ts * z[0] - tc * z[3], ts * z[1] + tc * z[2]), v = make_float2(ts * z[2] - tc * z[1], ts * z[3] + tc * z[0]);
                    uint32_t* o = (i < 2 ? x : y) + 2 * (i & 1);
                    o[0] = pack_bf16(fmaf(S.x, z[0], fmaf(-S.y, z[1], fmaf(D.x, u.x, -D.y * u.y))), fmaf(S.x, z[1], fmaf(S.y, z[0], fmaf(D.x, u.y, D.y * u.x))));
                    o[1] = pack_bf16(fmaf(S.x, z[2], fmaf(-S.y, z[3], fmaf(-D.x, v.x, D.y * v.y))), fmaf(S.x, z[3], fmaf(S.y, z[2], fmaf(-D.x, v.y, -D.y * v.x))));
                }
#pragma unroll
                for (int i = 0; i < 4; i++) { c[i][0] = c[i][1] = c[i][2] = c[i][3] = 0.f; mma16816(c[i], x[0], x[1], x[2], x[3], m[i].x ^ cjm, m[i].y ^ cjm); }
#pragma unroll
                for (int i = 0; i < 4; i++) mma16816(c[i], y[0], y[1], y[2], y[3], m[i].z ^ cjm, m[i].w ^ cjm);
#pragma unroll
                for (int i = 0; i < 4; i++) {
                    uint32_t* o = (i < 2 ? x : y) + 2 * (i & 1);
                    o[0] = pack_bf16(c[i][0] * tw[i].x + c[i][1] * tw[i].y, c[i][1] * tw[i].x - c[i][0] * tw[i].y);
                    o[1] = pack_bf16(c[i][2] * tw[i].x + c[i][3] * tw[i].y, c[i][2] * tw[i].y - c[i][3] * tw[i].x);
                }
                stsm4(a0, x[0], x[1], x[2], x[3]);
                stsm4(a0 ^ 32, y[0], y[1], y[2], y[3]);
            }
        }
#pragma unroll
        for (int i = 0; i < 4; i++) { m[i] = lds128u(tb + (faB ? FT_B1I : FT_F16) + i * 512 + lane * 16); if (!faB) m[i] = conjfrag(m[i]); }
        bar_sync(bar, 256);
        if (lead && k1 + 8 < 129) MID_LOADW(k1 + 8);
        __syncwarp();
#pragma unroll
        for (int q = 0; q < 2; q++)
#pragma unroll
            for (int i = 0; i < 4; i++) in[q][i] = lds128u(buf + (rB ^ ((i & 1) << 6)) + (i >> 1) * 4096 + q * 256);
        __syncwarp();
#pragma unroll
        for (int q = 0; q < 2; q++) {
            dft16<false>(out, in[q], m, m);
#pragma unroll
            for (int i = 0; i < 4; i++) sts128u(buf + (wBi ^ ((i & 1) << 4) ^ (q << 5)) + (i >> 1) * 4096 + q * 256, out[i]);
        }
        m[0] = m[1] = m[2] = conjfrag(lds128u(tb + FT_A8 + lane * 16));
        m[3] = negfrag(m[0]);
        bar_sync(bar, 256);
#pragma unroll
        for (int q = 0; q < 2; q++)
#pragma unroll
            for (int i = 0; i < 4; i++) in[q][i] = lds128u(buf + (rA ^ ((i & 1) * 0x90)) + (i >> 1) * 8192 + q * 16384);
        __syncwarp();
#pragma unroll
        for (int q = 0; q < 2; q++) {
            dft16<false>(out, in[q], m, m);
#pragma unroll
            for (int i = 0; i < 4; i++) sts128u(buf + (wAo ^ ((i & 1) << 4)) + (i >> 1) * 8192 + q * 16384, out[i]);
        }
        fence_async_smem();
        bar_sync(bar, 256);
        if (lead) {
            tma_st3(buf, &fm.y2, 0, k1 * 8);
            if (k1 & 127) tma_st3(buf + 16384, &fm.y2, 0, (256 - k1) * 8);
            bulk_commit();
        }
    }
    if (lead) bulk_wait_all();
}

__device__ __align__(128) unsigned g_start;
__device__ __align__(128) unsigned g_fbar;
__device__ __align__(128) unsigned g_end;
__device__ __forceinline__ unsigned gbar_arrive(unsigned* c, unsigned inc, unsigned total, int lane) {
    unsigned v = 0;
    if (lane == 0) { asm volatile("fence.proxy.async;" ::: "memory"); fence_gpu(); v = atomicAdd(c, inc); }
    return (__shfl_sync(~0u, v, 0) & ~(total - 1)) + total;
}
__device__ __forceinline__ void gbar_wait(unsigned* c, unsigned target, unsigned ns) {
    uint32_t n = 0;
    while (__any_sync(~0u, (int)(ld_acquire(c) - target) < 0)) { if (ns) __nanosleep(ns); if (++n > SPIN_LIMIT) __trap(); }
    asm volatile("fence.proxy.async;" ::: "memory");
}
__device__ __forceinline__ void fft_rest(int cta, const FftMaps& fm, uint32_t sb, bool skip) {
    const int hi = __shfl_sync(~0u, threadIdx.x >> 8, 0), w = __shfl_sync(~0u, (threadIdx.x >> 5) & 7, 0), lane = threadIdx.x & 31;
    unsigned target = 0;
    if (w == 4) target = gbar_arrive(&g_start, 16, 256, lane);
    if (threadIdx.x < 32) mbar_init(sb + FT_BAR + 8 * threadIdx.x, 1);
    fft_tables(sb, threadIdx.x, 512);
    fence_async_smem();
    __syncthreads();
    const int grp = cta * 2 + hi, bar = 1 + hi;
    const uint32_t gb = sb + hi * FG_SIZE, mb = sb + FT_BAR + hi * 128;
    uint32_t cnt = 0;
    if (w == 4) gbar_wait(&g_start, target, 200);
    GT(1);
    fft_mid(grp, fm, sb, gb, mb, cnt, w, lane, bar);
    if (w == 4) gbar_wait(&g_fbar, gbar_arrive(&g_fbar, 1, 8, lane), 200);
    GT(2);
    fft_col<true, 16>(grp, 0, &fm.y, &fm.o, gb, mb + 64, w, lane, bar);
}

__device__ __align__(256) uint4 g_kvq[4 * 32 * 3 * 8 * 2 * 32];
__device__ __align__(256) uint2 g_alpha[2 * 32 * 3 * 8 * 2 * 32];
__device__ __align__(256) uint4 g_red[5 * 32768 / 16];
__device__ __align__(256) uint4 g_stamp[32];
__device__ __align__(256) uint4 g_qst[128 * 2];
__device__ __align__(256) bf16 g_ox[2048 * 4096];
struct Tune { uint32_t d_alpha, d_r, opt, d_q, d_v, spread, extra; };
#define OP_SPLIT 1
#define X_SEQ 24
#define OPD_EARLY 0
constexpr int RA = 2;

constexpr uint32_t SM_BASE = 1024;
constexpr uint32_t O_WO = 0;
constexpr uint32_t O_WV = 65536;
constexpr uint32_t O_XB = 131072;
constexpr uint32_t O_MEM = O_XB + 32768;
constexpr uint32_t O_RECV = O_MEM + 8192;
constexpr uint32_t O_KVQ = O_RECV + 12288;
constexpr uint32_t O_STG = O_KVQ + 18432;
constexpr uint32_t O_S = O_STG + 8192;
constexpr uint32_t O_XO = O_STG + 16384;
constexpr uint32_t O_P = O_S + 10240;
constexpr uint32_t O_O = O_P + 1536;
constexpr uint32_t O_DBG = O_O + 2048;
constexpr uint32_t O_F1 = 196608;
constexpr uint32_t O_VM = O_F1 + 32768;
constexpr uint32_t O_BAR = 232448 - 512;
constexpr uint32_t MAIN_SMEM = 232448;
static_assert(O_DBG + (DBG_TIMING ? 4 * DBG_N * 24 * 4 : 0) <= O_VM && FFT_SMEM <= MAIN_SMEM && O_VM + 2048 <= O_BAR, "smem");
constexpr int G_ST = 6;
enum { B_WK0 = 0, B_WK1, B_WQ0, B_WQ1, B_WV, B_WO, B_F1, B_XP, B_XFULL, B_RFULL, B_AFULL, B_KVFULL, B_QST, B_RECV, B_GF = B_RECV + 6,
       B_QDONE = B_GF + G_ST, B_KDONE, B_XEMPTY, B_SDONE, B_SRDY, B_OPDONE, B_QX, B_GE, B_XPE = B_GE + G_ST, B_QKW, B_MEM, B_COUNT };

constexpr float SM_SCALE_LOG2 = 0.08838834764831845f * 1.4426950408889634f;
constexpr float MASK_VAL = -1.0e9f / 0.08838834764831845f;

__device__ __forceinline__ uint32_t red_grp(int grp) { return (uint32_t)((grp >> 1) * 1024 + (grp & 1) * 256); }
__host__ __device__ constexpr uint64_t xdesc(int ks) { return mkdesc(SM_BASE + O_XB + (ks >> 2) * 1024 + (ks & 3) * 32, 16, 8192, 1); }

__device__ __forceinline__ void x_split(const float* d, uint32_t (&sn)[4], uint32_t (&kp)[4], int kh) {
#pragma unroll
    for (int i = 0; i < 4; i++) {
        const uint32_t lo = pack_bf16(d[2 * i], d[2 * i + 1]), hi = pack_bf16(d[8 + 2 * i], d[8 + 2 * i + 1]);
        sn[i] = kh ? lo : hi; kp[i] = kh ? hi : lo;
    }
}
__device__ __forceinline__ void x_send(int R, const uint32_t (&sn)[4], int sg, int tid, uint32_t sb, uint32_t mate) {
    const uint32_t par = sg & 1;
    const uint32_t bar = O_BAR + 8 * (B_RECV + R * 2) + 8 * par;
    if (tid == 0) mbar_expect_tx(sb + bar, 2048);
    asm volatile("st.async.shared::cluster.mbarrier::complete_tx::bytes.v4.b32 [%0], {%1,%2,%3,%4}, [%5];"
                 ::"r"(mate + O_RECV + (par * 3 + R) * 2048 + tid * 16), "r"(sn[0]), "r"(sn[1]), "r"(sn[2]), "r"(sn[3]), "r"(mate + bar) : "memory");
}
__device__ __forceinline__ void x_wait(int R, int sg, uint32_t sb) {
    mbar_wait_cluster(sb + O_BAR + 8 * (B_RECV + R * 2) + 8 * (sg & 1), (sg >> 1) & 1);
}
template <int R>
__device__ __forceinline__ void x_finish(const uint32_t (&kp)[4], int sg, int h, int mt, int kh, int tid, uint32_t sb) {
    const uint4 r = lds128u(sb + O_RECV + ((sg & 1) * 3 + R) * 2048 + tid * 16);
    uint32_t u0 = add_bf16x2(kp[0], r.x), u1 = add_bf16x2(kp[1], r.y), u2 = add_bf16x2(kp[2], r.z), u3 = add_bf16x2(kp[3], r.w);
    if (R < 2) { u0 = movm(u0); u1 = movm(u1); u2 = movm(u2); u3 = movm(u3); }
    const uint32_t tag = ((sg >> 2) & 1) ^ 1;
    u0 = (u0 & ~1u) | tag;
    uint4* const hb = &g_kvq[((sg & 3) * 32 + h) * (3 * 512)];
    if (R == 0) {
        uint2* p = (uint2*)hb + (kh * 16 + mt) * 32 + (tid & 31);
        asm volatile("{\n.reg .pred p;\nsetp.lt.s32 p, %5, 64;\n@p st.relaxed.gpu.global.v2.b32 [%0], {%1,%2};\n@p st.relaxed.gpu.global.v2.b32 [%0+2048], {%3,%4};\n}"
                     ::"l"(p), "r"(u0), "r"(u1), "r"((u2 & ~1u) | tag), "r"(u3), "r"(sg) : "memory");
    } else {
        asm volatile("{\n.reg .pred p;\nsetp.lt.s32 p, %5, 64;\n@p st.relaxed.gpu.global.v4.b32 [%0], {%1,%2,%3,%4};\n}"
                     ::"l"(hb + R * 512 + (mt * 2 + kh) * 32 + (tid & 31)), "r"(u0), "r"(u1), "r"(u2), "r"(u3), "r"(sg) : "memory");
    }
}

__device__ __forceinline__ uint32_t convert_mem(const unsigned char* redp, int s, int kh, int jj, int w, int lane, uint32_t sb, uint32_t& sf) {
    const uint32_t off = red_grp(jj * 16 + w * 4 + (lane >> 3)), o16 = off + (lane & 7) * 16, o8 = off + 512 + ((lane >> 3) & 1) * 64 + (lane & 7) * 8;
    uint32_t ma = sb + O_MEM + (jj * 4 + (lane >> 4)) * 1024 + (lane & 7) * 128 + (((2 * w + ((lane >> 3) & 1)) ^ (lane & 7)) << 4);
    uint32_t a16 = sb + O_STG + o16, a8 = sb + O_STG + o8;
    const uint32_t target = (s & 4) ? 0x42C00000u : 0x42000000u;
    uint32_t n = 0;
    bool redo;
    KEEP2(ma, a16); KEEP2(a8, target);
#pragma unroll 1
    do {
        asm volatile("" : "+r"(n));
        if (n) {
            const unsigned char* pg = redp + (s & 3) * 32768 + kh * 16384;
            const uint4 x = ldg_rlx128(pg + o16), y = ldg_rlx128(pg + o16 + 128);
            const uint2 z = ldg_rlx64(pg + o8);
            sts128u(a16, x); sts128u(a16 + 128, y); sts64u(a8, z);
            if (n > SPIN_LIMIT) __trap();
        }
        n++;
        mbar_wait(sb + O_BAR + 8 * B_RFULL, s & 1);
        const uint4 ra = lds128u(a16), rb = lds128u(a16 + 128);
        const uint2 rc = lds64u(a8);
        stsm4t(ma, ra.x, ra.y, ra.z, __byte_perm(ra.w, rc.x, 0x5410));
        stsm4t(ma + 2048, rb.x, rb.y, rb.z, __byte_perm(rb.w, rc.x, 0x7610));
        redo = __any_sync(~0u, orx(orx2(ra.w, rb.w, target), rc.y, target) > 0xffffu);
    } while (redo);
    if (lane == 0) mbar_arrive(sb + O_BAR + 8 * B_MEM);
    fence_async_smem();
    __syncwarp();
    if (lane == 0) mbar_arrive(sb + O_BAR + 8 * B_QKW);
    return n - 1;
}

#define F16(d, o) F4(d, o), F4(d, o + 4), F4(d, o + 8), F4(d, o + 12)
__device__ __forceinline__ void wg_ss128(float (&d)[64], uint64_t da, uint64_t db, int sc) {
    asm volatile("{\n.reg .pred p;\nsetp.ne.b32 p, %66, 0;\nwgmma.mma_async.sync.aligned.m64n128k16.f32.bf16.bf16 "
                 "{%0,%1,%2,%3,%4,%5,%6,%7,%8,%9,%10,%11,%12,%13,%14,%15,%16,%17,%18,%19,%20,%21,%22,%23,%24,%25,%26,%27,%28,%29,%30,%31,"
                 "%32,%33,%34,%35,%36,%37,%38,%39,%40,%41,%42,%43,%44,%45,%46,%47,%48,%49,%50,%51,%52,%53,%54,%55,%56,%57,%58,%59,%60,%61,%62,%63}, "
                 "%64, %65, p, 1, 1, 0, 1;\n}"
                 : F16(d, 0), F16(d, 16), F16(d, 32), F16(d, 48) : "l"(da), "l"(db), "r"(sc));
}
__device__ __forceinline__ void stg_rlx32(void* p, uint32_t v) { asm volatile("st.relaxed.gpu.global.u32 [%0], %1;" ::"l"(p), "r"(v) : "memory"); }

__global__ void __cluster_dims__(2, 1, 1) __launch_bounds__(512, 1)
rmt_main(const __grid_constant__ CUtensorMap tm_x, const __grid_constant__ CUtensorMap tm_wq, const __grid_constant__ CUtensorMap tm_wk,
         const __grid_constant__ CUtensorMap tm_wv, const __grid_constant__ CUtensorMap tm_wo, const bf16* __restrict__ mem0,
         const Tune tn, const __grid_constant__ FftMaps fm, const __grid_constant__ CUtensorMap tm_o,
         const __grid_constant__ CUtensorMap tm_w2, bf16* __restrict__ out) {
    extern __shared__ __align__(1024) unsigned char smem_raw[];
    const uint32_t sb = smem_u32(smem_raw);
    if ((sb & 0x3FFFF) != SM_BASE) __trap();
    GT(6);
    const int cid = blockIdx.x >> 1, kh = blockIdx.x & 1;
    const int tpc = cid < 4 ? 62 + cid : cid - 4;
    int h, nh;
    if (tpc < 32) { h = (tpc >> 4) * 8 + (tpc & 7); nh = (tpc >> 3) & 1; }
    else if (tpc < 60) { int u = tpc - 32, r = u % 14; h = 16 + (u / 14) * 7 + r % 7; nh = r / 7; }
    else if (tpc < 62) { GT(0); fft_rest((tpc - 60) * 2 + kh, fm, sb, tn.opt & 8); GT(3); return; }
    else { h = 30 + ((tpc - 62) >> 1); nh = tpc & 1; }
    const int j = nh * 2 + kh, role = h * 4 + j;
    const int wgi = __shfl_sync(~0u, threadIdx.x >> 7, 0);
    const int w = __shfl_sync(~0u, (threadIdx.x >> 5) & 3, 0);
    const int tid = threadIdx.x & 127, lane = tid & 31;
#define PIN_IDS() const int tid = __shfl_sync(~0u, threadIdx.x & 127, threadIdx.x & 31), lane = tid & 31
#define OPAQUE_IDS() int tid_ = tid; asm volatile("" : "+r"(tid_)); const int tid = tid_, lane = tid_ & 31; (void)lane
    unsigned char* const redp = (unsigned char*)(((uintptr_t)g_red + 32767) & ~(uintptr_t)32767);
    const uint32_t bars = sb + O_BAR;

    if (threadIdx.x < B_COUNT) {
        const int i = threadIdx.x;
        mbar_init(bars + 8 * i, i < B_QDONE ? 1 : i < B_GE ? 4 : i < B_XPE ? 8 : i < B_QKW ? 12 : 16);
        asm volatile("fence.mbarrier_init.release.cluster;" ::: "memory");
        fence_async_smem();
    } else if (threadIdx.x >= 64 && threadIdx.x < 71) {
        const int i = threadIdx.x - 64;
        const CUtensorMap* m = i == 0 ? &tm_wk : i == 1 ? &tm_wq : i == 2 ? &fm.x : i == 3 ? &tm_x : i == 4 ? &tm_wv : i == 5 ? &tm_wo : &fm.y;
        asm volatile("prefetch.tensormap [%0];" ::"l"(m) : "memory");
    }
    __syncthreads();
    const int wc0 = h * 128 + nh * 64;
    if (wgi < 2 && lane == 0) {
        if (w < 2) {
            const uint32_t bar = bars + 8 * (B_WK0 + 2 * (wgi ^ 1) + w);
            mbar_expect_tx(bar, 32768);
            tma2d(sb + (wgi ? O_XB : O_WO) + w * 32768, wgi ? &tm_wk : &tm_wq, wc0, kh * 512 + w * 256, bar);
        } else if (wgi == 0 && w == 2) {
            mbar_expect_tx(bars + 8 * B_F1, 32768);
            tma_ld4(sb + O_F1, &fm.x, (role & 15) * 64, role >> 4, bars + 8 * B_F1);
        } else if (wgi == 1 && w == 2 && role < 2 * (RA + 3)) tma4d_prefetch(&tm_x, kh * 8, (role >> 1) * 4);
    }
    GT(7);
    uint32_t mate;
    asm volatile("mapa.shared::cluster.u32 %0, %1, %2;" : "=r"(mate) : "r"(sb), "r"(kh ^ 1));
    if (wgi >= 2) fft_col<false, 1>(role >> 4, role & 15, &fm.x, &fm.y, sb + O_F1, bars + 8 * B_F1, (wgi - 2) * 4 + w, lane, 6);

    if (wgi < 2) {
        asm volatile("setmaxnreg.inc.sync.aligned.u32 176;");
        PIN_IDS();
        uint32_t a[32][4], sf = 0;
        {
            const uint32_t stage = sb + (wgi == 0 ? O_WO : O_XB);
            const uint32_t ad = stage + (((lane >> 4) & 1) * 8 + (lane & 7)) * 128 + (((2 * w + ((lane >> 3) & 1)) ^ (lane & 7)) << 4);
#pragma unroll
            for (int i = 0; i < 2; i++) {
                mbar_wait(bars + 8 * (B_WK0 + 2 * (wgi ^ 1) + i), 0);
#pragma unroll
                for (int ks = 0; ks < 16; ks++) ldsm4t(a[i * 16 + ks], ad + (i * 16 + ks) * 2048);
            }
#pragma unroll
            for (int ks = 0; ks < 32; ks += 2) KEEP2(a[ks][0], a[ks + 1][0]);
            SCHED_FENCE();
            if (lane == 0) mbar_arrive(bars + 8 * (B_QDONE + wgi));
            if (wgi == 0) GT(10); else GT(11);
        }
        asm volatile("barrier.cluster.arrive.relaxed.aligned;" ::: "memory");
        asm volatile("barrier.cluster.wait.acquire.aligned;" ::: "memory");
        uint32_t kp[4];
#define X_PASS(d, dofs)                                                                                    \
        wg_fence();                                                                                        \
        _Pragma("unroll") for (int ks = 0; ks < 32; ks++) { if (ks == 0) wg_rs32<0>(d, a[ks], xdesc(ks) + (dofs)); else wg_rs32<1>(d, a[ks], xdesc(ks) + (dofs)); } \
        wg_commit();                                                                                       \
        wg_wait<0>();
#define X_FINISH(sg) { if (wgi == 0) x_finish<0>(kp, sg, h, nh * 4 + w, kh, tid, sb); else x_finish<1>(kp, sg, h, nh * 4 + w, kh, tid, sb); }
        mbar_wait(bars + 8 * B_XP, 0);
        if (wgi == 0) GT(8);
#pragma unroll 1
        for (int sg = 0; sg < RA; sg++) {
            float d[16]; uint32_t sn[4];
            X_PASS(d, sg * 2048 - (int)((O_XB - O_WO) >> 4));
            if (sg > 0) {
                if (lane == 0) mbar_arrive(bars + 8 * B_XPE);
                x_wait(wgi, sg - 1, sb); X_FINISH(sg - 1);
            }
            x_split(d, sn, kp, kh);
            x_send(wgi, sn, sg, tid, sb, mate);
        }
        const int lq = wgi == 0 ? 4 : 0;
#pragma unroll 1
        for (int s = 0; s < 64; s++) {
            TSI(s);
            {
                float d[16]; uint32_t sn[4], kc[4];
                x_wait(wgi, s + RA - 1, sb);
                mbar_wait(bars + 8 * B_XFULL, s & 1);
                if (wgi == 1) {
                    mbar_wait(bars + 8 * B_OPDONE, s & 1);
                    x_finish<1>(kp, s + RA - 1, h, nh * 4 + w, kh, tid, sb);
                    TS(5);
                    mbar_wait(bars + 8 * B_QX, s & 1);
                } else mbar_wait(bars + 8 * B_OPDONE, s & 1);
                TS(6);
                wg_fence();
#pragma unroll
                for (int ks = 0; ks < 32; ks++) {
                    if (ks == 0) wg_rs32<0>(d, a[ks], xdesc(ks)); else wg_rs32<1>(d, a[ks], xdesc(ks));
                    if (ks == X_SEQ - 1) wg_commit();
                }
                wg_commit();
                wg_wait<1>();
                if (tid < lq) mbar_arrive(bars + 8 * B_QX);
                wg_wait<0>();
                TS(7);
                x_split(d, sn, kc, kh);
                x_send(wgi, sn, s + RA, tid, sb, mate);
                TS(4);
                if (wgi == 0) { x_finish<0>(kp, s + RA - 1, h, nh * 4 + w, kh, tid, sb); TS(5); }
#pragma unroll
                for (int i = 0; i < 4; i++) kp[i] = kc[i];
            }
            uint2* ap = &g_alpha[((s & 1) * 32 + h) * (3 * 512) + wgi * 512 + ((nh * 4 + w) * 2 + kh) * 32 + lane];
            uint32_t mb0 = sb + O_MEM + (lane & 7) * 128 + (((lane >> 3) ^ (lane & 7)) << 4), mb1 = mb0 ^ 64;
            const uint32_t tag = ((s >> 1) & 1) ^ 1;
            KEEP2(mb0, mb1); KEEPP(ap);
            float e[2][4];
#pragma unroll
            for (int i = 0; i < 4; i++) e[0][i] = e[1][i] = 0.f;
            if (lane == 0) mbar_arrive(bars + 8 * B_MEM);
            mbar_wait(bars + 8 * B_MEM, s & 1);
            TS(0);
#pragma unroll
            for (int ks = 0; ks < 32; ks += 2) {
                uint32_t b[4];
                ldsm4(b, ((ks & 2) ? mb1 : mb0) + (ks >> 2) * 1024);
                mma16816(e[0], a[ks][0], a[ks][1], a[ks][2], a[ks][3], b[0], b[1]);
                mma16816(e[1], a[ks + 1][0], a[ks + 1][1], a[ks + 1][2], a[ks + 1][3], b[2], b[3]);
            }
            TS(2);
            uint32_t u0 = pack_bf16(e[0][0] + e[1][0], e[0][1] + e[1][1]), u1 = pack_bf16(e[0][2] + e[1][2], e[0][3] + e[1][3]);
            u0 = movm(u0); u1 = movm(u1);
            SCHED_FENCE();
            if (lane == 0) mbar_arrive(bars + 8 * B_QKW);
            stg_rlx64(ap, (u0 & ~1u) | tag, u1);
            TS(3);
            if (wgi == 1) {
                const uint2* vp = &g_alpha[((s & 1) * 32 + h) * (3 * 512) + 1024 + w * 128 + lane];
                const uint32_t vs = sb + O_VM + tid * 16;
                KEEPP(vp); KEEP2(vs, 0);
                mbar_wait(bars + 8 * B_QST, s & 1);
                uint32_t n, bad;
                asm volatile("ld.shared.u32 %0, [%1];" : "=r"(n) : "r"(bars + 504) : "memory");
                wait_gtime(n + tn.d_v);
                TS(8);
                n = 0;
                do {
                    uint2 va[4];
#pragma unroll
                    for (int i = 0; i < 4; i++) va[i] = ldg_rlx64(vp + i * 32);
                    if (++n > SPIN_LIMIT) __trap();
                    bad = (orx2(va[0].x, va[1].x, tag) | orx2(va[2].x, va[3].x, tag)) & 1;
                    sts128u(vs, make_uint4((add_bf16x2(va[0].x, va[1].x) & ~1u) | ((~s ^ bad) & 1), add_bf16x2(va[0].y, va[1].y),
                                                             add_bf16x2(va[2].x, va[3].x), add_bf16x2(va[2].y, va[3].y)));
                } while (__any_sync(~0u, bad));
                TS(9);
                TSV(16 + w, n - 1);
                LT(s, 4 + w, n - 1);
            }
        }
        x_wait(wgi, 63 + RA, sb);
        sts32(bars + 508, sf);
        TSDUMP();
        asm volatile("bar.arrive 7, 512;" ::: "memory");
        float d[64];
        int st = 0, ph = 0;
#pragma unroll 1
        for (int kt = 0; kt < 64; kt++) {
            mbar_wait(bars + 8 * (B_GF + st), ph);
            if (kt == 0) GT(4);
            const uint64_t da = mkdesc(SM_BASE + st * 32768 + wgi * 8192, 16, 1024, 1), db = mkdesc(SM_BASE + st * 32768 + 16384, 8192, 1024, 1);
            wg_fence();
#pragma unroll
            for (int k = 0; k < 4; k++) wg_ss128(d, da + k * 2, db + k * 128, kt | k);
            wg_commit();
            if (kt > 0) {
                wg_wait<1>();
                if (lane == 0) mbar_arrive(bars + 8 * (B_GE + (st == 0 ? G_ST - 1 : st - 1)));
            }
            if (++st == G_ST) { st = 0; ph ^= 1; }
        }
        wg_wait<0>();
        {
            const uint32_t sl = sb + O_F1 + (wgi * 4 + w) * 4096;
#pragma unroll
            for (int i = 0; i < 8; i++)
                stsm4(sl + (lane & 15) * 256 + (((2 * i + (lane >> 4)) ^ (lane & 7)) << 4), pack_bf16(d[8 * i], d[8 * i + 1]),
                      pack_bf16(d[8 * i + 2], d[8 * i + 3]), pack_bf16(d[8 * i + 4], d[8 * i + 5]), pack_bf16(d[8 * i + 6], d[8 * i + 7]));
            __syncwarp();
            bf16* op = out + (size_t)((role >> 3) * 128 + wgi * 64 + w * 16 + (lane >> 4)) * 2048 + 1024 + (role & 7) * 128 + (lane & 15) * 8;
#pragma unroll
            for (int i = 0; i < 8; i++) {
                const int r = 2 * i + (lane >> 4);
                const uint4 v = lds128u(sl + r * 256 + (((lane & 15) ^ (r & 7)) << 4));
                stg128(op + (size_t)i * 4096, v.x, v.y, v.z, v.w);
            }
        }
        GT(5);
    } else if (wgi == 2) {
        asm volatile("setmaxnreg.dec.sync.aligned.u32 64;");
        PIN_IDS();
        asm volatile("barrier.cluster.arrive.relaxed.aligned;" ::: "memory");
#define X_LOAD(dst, sg, bar) tma4d(sb + (dst), &tm_x, kh * 8, ((sg) & 63) * 4, bars + 8 * (bar))
        if (w == 0) {
#define WV_LOAD(i) tma2d(sb + O_WV + (i) * 32768, &tm_wv, wc0, kh * 512 + (i) * 256, bars + 8 * B_WV)
            const int nearly = (tn.opt >> 5) & 3;
            mbar_wait(bars + 8 * B_WK0, 0);
            if (lane == 0) { mbar_expect_tx(bars + 8 * B_WV, 65536); for (int i = 0; i < nearly; i++) WV_LOAD(i); }
            mbar_wait(bars + 8 * B_QDONE, 0);
            if (lane == 0) { mbar_expect_tx(bars + 8 * B_XP, 65536); X_LOAD(O_WO, 0, B_XP); X_LOAD(O_WO + 32768, 1, B_XP); }
            mbar_wait(bars + 8 * B_KDONE, 0);
            if (lane == 0) {
                mbar_expect_tx(bars + 8 * B_XFULL, 32768); X_LOAD(O_XB, RA, B_XFULL);
                for (int i = nearly; i < 2; i++) WV_LOAD(i);
            }
        }
        asm volatile("barrier.cluster.wait.acquire.aligned;" ::: "memory");
        mbar_wait(bars + 8 * B_WV, 0);
        GT(12);
        uint32_t sf = 0, tref = gtime() - 4000;
#define V_PASS(d, dofs)                                                                                    \
        wg_fence();                                                                                        \
        _Pragma("unroll") for (int ks = 0; ks < 32; ks++) {                                                \
            constexpr uint64_t da0 = mkdesc(SM_BASE + O_WV, 16, 1024, 1);                                  \
            if (ks == 0) wg_ss40<0>(d, da0 + ks * 128, xdesc(ks) + (dofs)); else wg_ss40<1>(d, da0 + ks * 128, xdesc(ks) + (dofs)); \
        }                                                                                                  \
        wg_commit();                                                                                       \
        wg_wait<0>();
        mbar_wait(bars + 8 * B_XP, 0);
        {
            uint32_t kp[4];
#pragma unroll 1
            for (int sg = 0; sg <= RA; sg++) {
                float d[20]; uint32_t sn[4];
                if (sg < RA) { V_PASS(d, sg * 2048 - (int)((O_XB - O_WO) >> 4)); }
                if (sg == RA - 1) {
                    if (lane == 0) mbar_arrive(bars + 8 * B_XPE);
                    if (w == 0) {
                        mbar_wait(bars + 8 * B_XPE, 0);
                        GT(9);
                        if (lane == 0) {
                            mbar_expect_tx(bars + 8 * B_WO, 65536);
#pragma unroll
                            for (int i = 0; i < 4; i++) tma2d(sb + O_WO + i * 16384, &tm_wo, j * 256 + i * 64, h * 128, bars + 8 * B_WO);
                        }
                    }
                }
                if (sg > 0) { x_wait(2, sg - 1, sb); x_finish<2>(kp, sg - 1, h, nh * 4 + w, kh, tid, sb); }
                if (sg < RA) { x_split(d, sn, kp, kh); x_send(2, sn, sg, tid, sb, mate); }
            }
        }
#pragma unroll 1
        for (int s = 0; s < 64; s++) {
            TSI(s);
            OPAQUE_IDS();
            uint2* ap = &g_alpha[((s & 1) * 32 + h) * (3 * 512) + 1024 + ((nh * 4 + w) * 2 + kh) * 32 + lane];
            KEEPP(ap);
            float d[20];
            mbar_wait(bars + 8 * B_QKW, s & 1);
            TS(0);
            if (s == 0) GT(14);
            V_PASS(d, 0);
            TS(1);
            stg_rlx64(ap, (pack_bf16(d[16], d[17]) & ~1u) | (((s >> 1) & 1) ^ 1), pack_bf16(d[18], d[19]));
            if (lane == 0) mbar_arrive(bars + 8 * B_XEMPTY);
            if (s == 63) break;
            uint32_t sn[4], kp[4];
            x_split(d, sn, kp, kh);
            if (w == 3) {
                uint32_t n = 0, mx, mn;
                do {
                    const uint4 st = ldg_rlx128(&g_stamp[lane]);
                    mx = __reduce_max_sync(~0u, max(max(st.x - tref, st.y - tref), max(st.z - tref, st.w - tref)));
                    mn = __reduce_min_sync(~0u, min(min(st.x - tref, st.y - tref), min(st.z - tref, st.w - tref)));
                } while (mx >= 200000u && ++n < 64);
                tref = mx < 200000u ? tref + mx + (mx - mn > tn.spread ? tn.extra : 1) : gtime();
                TSV(12, clk()); TSV(13, n); TSV(14, mx - mn);
            }
            if (tn.opt & 1) { mbar_wait(bars + 8 * B_SDONE, s & 1); x_send(2, sn, s + RA, tid, sb, mate); }
            if (w == 0) {
                mbar_wait(bars + 8 * B_XEMPTY, s & 1);
                mbar_wait(bars + 8 * ((tn.opt & 2) ? B_SRDY : B_SDONE), s & 1);
                if (lane == 0) {
                    mbar_expect_tx(bars + 8 * B_XFULL, 32768);
                    X_LOAD(O_XB, s + RA + 1, B_XFULL);
                }
                mbar_wait(bars + 8 * B_SRDY, s & 1);
                if (lane == 0) {
                    const uint4* hb = &g_kvq[(((s + 1) & 3) * 32 + h) * (3 * 512)];
                    mbar_expect_tx(bars + 8 * B_KVFULL, 18432);
                    bulk_g2s(sb + O_KVQ, hb + 512, 16384, bars + 8 * B_KVFULL);
                    bulk_g2s(sb + O_KVQ + 16384, hb + j * 128, 2048, bars + 8 * B_KVFULL);
                    if (nh == 0 && ((h ^ s) & 7) == 0 && s < 61 - RA) tma4d_prefetch(&tm_x, kh * 8, (s + RA + 3) * 4);
                }
            }
            mbar_wait(bars + 8 * B_OPDONE, (s + 1) & 1);
            if (!(tn.opt & 1)) x_send(2, sn, s + RA, tid, sb, mate);
            if (w == 3) {
                wait_gtime(tref + tn.d_r);
                if (lane == 0) {
                    mbar_expect_tx(bars + 8 * B_RFULL, 16384);
                    bulk_g2s(sb + O_STG, redp + (s & 3) * 32768 + kh * 16384, 16384, bars + 8 * B_RFULL);
                }
                TSV(3, clk());
            }
            x_wait(2, s + RA, sb);
            const bool late = w == 3 || (tn.opt & 4);
            if (!late) { x_finish<2>(kp, s + RA, h, nh * 4 + w, kh, tid, sb); TS(6); }
            if (DBG_TIMING && w == 0) { mbar_wait(bars + 8 * B_RFULL, s & 1); TS(4); }
            const uint32_t n = convert_mem(redp, s, kh, 0, w, lane, sb, sf); (void)n;
            TS(5);
            TSV(8 + w, n);
            LT(s, 8 + w, n);
            if (late) x_finish<2>(kp, s + RA, h, nh * 4 + w, kh, tid, sb);
        }
        sts32(bars + 508, sf);
        TSDUMP();
        asm volatile("bar.arrive 7, 512;" ::: "memory");
    } else {
        asm volatile("setmaxnreg.dec.sync.aligned.u32 96;");
        PIN_IDS();
        GT(0);
        asm volatile("barrier.cluster.arrive.relaxed.aligned;" ::: "memory");
#define RED_CLEAR(st)                                                                                           \
        if (lane < 16) {                                                                                        \
            const uint32_t cb = ((st) & 4) ? 0x42800000u : 0u;                                                  \
            stg128(redp + ((st) & 3) * 32768 + role * 256 + lane * 16, 0, (role & 2) ? cb : 0u, 0, cb);        \
        }
        if (w == 0) { RED_CLEAR(0); RED_CLEAR(1); RED_CLEAR(2); }
        sts128u(sb + O_VM + tid * 16, make_uint4(0, 0, 0, 0));
        {
            uint4 v[4];
#pragma unroll
            for (int q = 0; q < 4; q++) v[q] = *(const uint4*)(mem0 + ((lane >> 3) + (q & 1) * 4) * 1024 + kh * 512 + (2 * w + (q >> 1)) * 64 + (lane & 7) * 8);
            mbar_wait(bars + 8 * B_KDONE, 0);
#pragma unroll
            for (int q = 0; q < 4; q++) {
                const int row = (lane >> 3) + (q & 1) * 4;
                sts128u(sb + O_MEM + (2 * w + (q >> 1)) * 1024 + row * 128 + (((lane & 7) ^ row) << 4), v[q]);
            }
            fence_async_smem();
            __syncwarp();
            if (lane < 2) { mbar_arrive(bars + 8 * B_MEM); mbar_arrive(bars + 8 * B_QKW); }
            if (lane == 0) mbar_arrive(bars + 8 * B_OPDONE);
            if (tid == 0) mbar_arrive(bars + 8 * B_KVFULL);
        }
        asm volatile("barrier.cluster.wait.acquire.aligned;" ::: "memory");
        if (w == 0) {
            mbar_wait(bars + 8 * B_XP, 0);
            if (lane == 0) { tma_st4(sb + O_F1, &fm.y, (role & 15) * 64, role >> 4); bulk_commit(); }
            if (lane < 4) tma2d_prefetch(&tm_wo, j * 256 + lane * 64, h * 128);
            if (lane == 0) bulk_wait_all();
            __syncwarp();
            gbar_wait(&g_start, gbar_arrive(&g_start, 1, 256, lane), 0);
            GT(13);
        }
        bar_sync(1, 128);
        uint32_t sf = 0;
#pragma unroll 1
        for (int s = 0; s < 64; s++) {
            TSI(s);
            OPAQUE_IDS();
            uint4 kf[4]; uint2 qf[2];
            const uint32_t tg = ((s >> 2) & 1) ^ 1;
            {
                const uint32_t ka = sb + O_KVQ + w * 2048 + lane * 16, qa = sb + O_KVQ + 16384 + w * 512 + lane * 8;
                uint32_t n = s == 0;
                bool redo;
#pragma unroll 1
                do {
                    asm volatile("" : "+r"(n));
                    if (n) {
                        const uint4* hb = &g_kvq[((s & 3) * 32 + h) * (3 * 512)];
                        uint4 y[4];
                        do {
#pragma unroll
                            for (int i = 0; i < 4; i++) { kf[i] = ldg_rlx128(hb + 512 + w * 128 + i * 32 + lane); y[i] = ldg_rlx128(hb + 1024 + w * 128 + i * 32 + lane); }
#pragma unroll
                            for (int u = 0; u < 2; u++) qf[u] = ldg_rlx64((const uint2*)hb + j * 256 + (2 * w + u) * 32 + lane);
                            if (++n > SPIN_LIMIT) __trap();
                        } while (__any_sync(~0u, (orx2(y[0].x, y[1].x, tg) | orx2(y[2].x, y[3].x, tg)) & 1));
#pragma unroll
                        for (int i = 0; i < 4; i++) { sts128u(ka + i * 512, kf[i]); sts128u(ka + 8192 + i * 512, y[i]); }
#pragma unroll
                        for (int u = 0; u < 2; u++) sts64u(qa + u * 256, qf[u]);
                        fence_async_smem();
                    }
                    n++;
                    mbar_wait(bars + 8 * B_KVFULL, s & 1);
#pragma unroll
                    for (int i = 0; i < 4; i++) kf[i] = lds128u(ka + i * 512);
#pragma unroll
                    for (int u = 0; u < 2; u++) qf[u] = lds64u(qa + u * 256);
                    redo = __any_sync(~0u, or3(orx2(kf[0].x, kf[1].x, tg), orx2(kf[2].x, kf[3].x, tg), orx2(qf[0].x, qf[1].x, tg)) & 1);
                } while (redo);
                if (w == 0) TSV(22, n - 1);
            }
            TS(9);
            if (s == 0) GT(15);
            if (s > 0) {
                const uint32_t n = convert_mem(redp, s - 1, kh, 1, w, lane, sb, sf); (void)n;
                TS(11);
                TSV(16 + w, n);
                LT(s - 1, 12 + w, n);
                if (w == 1 && s < 62) RED_CLEAR(s + 2);
            }
            const uint32_t tag = ((s >> 1) & 1) ^ 1;
            const uint2* ap = &g_alpha[((s & 1) * 32 + h) * (3 * 512) + w * 128 + lane];
            const uint32_t l16 = sb + lane * 16, l4 = sb + lane * 4;
            const uint32_t sw = l16 + O_S + w * 2560, sr = l4 + O_S + w * 128;
            uint32_t pw = sb + O_P + ((lane >> 1) & 1) * 704 + (2 * w + (lane >> 4)) * 16 + ((lane >> 2) & 3) * 4 + (lane & 1) * 2;
            int lim = (lane & 2) ? 8 * j + 2 * w + (lane >> 4) - 2 * ((lane >> 2) & 3) - (lane & 1) : 64;
            uint32_t aa = sb + O_STG + w * 1024 + lane * 8;
            KEEP2(l16, l4); KEEP2(pw, lim); KEEP2(aa, tag);
            TS(0);
            if (w == 0) {
                mbar_wait(bars + 8 * B_MEM, s & 1);
                uint32_t tq = gtime();
                if (lane < 9) stg_rlx32(lane < 8 ? (uint32_t*)g_qst + role * 8 + lane : (uint32_t*)g_stamp + role, tq);
                wait_clk(clk(), tn.d_q);
                uint32_t n = 0, mx;
                do { mx = __reduce_max_sync(~0u, ldg_rlx32((const uint32_t*)g_qst + h * 32 + lane) - (tq - 1024)); } while (mx > 100000u && ++n < 16);
                TSV(13, n);
                LT(s, 2, n);
                if (mx <= 100000u) tq += mx - 1024;
                if (lane == 0) { sts32(bars + 504, tq); mbar_arrive(bars + 8 * B_QST); }
                TS(14);
                mbar_wait(bars + 8 * B_QKW, s & 1);
                TS(1);
                wait_gtime(tq + tn.d_alpha);
                if (lane == 0) {
                    mbar_expect_tx(bars + 8 * B_AFULL, 8192);
                    bulk_g2s(sb + O_STG, ap, 8192, bars + 8 * B_AFULL);
                }
                if (s == 0) { mbar_wait(bars + 8 * B_WO, 0); GT(1); }
            }
            {
                uint32_t n = 0;
                bool redo;
#pragma unroll 1
                do {
                    asm volatile("" : "+r"(n));
                    if (n) {
                        uint2 x[8];
#pragma unroll
                        for (int q = 0; q < 8; q++) x[q] = ldg_rlx64(ap + (q >> 2) * 512 + (q & 3) * 32);
#pragma unroll
                        for (int q = 0; q < 8; q++) sts64u(aa + (q >> 2) * 4096 + (q & 3) * 256, x[q]);
                        if (n > SPIN_LIMIT) __trap();
                    }
                    n++;
                    mbar_wait(bars + 8 * B_AFULL, s & 1);
                    TS(12);
                    uint2 qa[4], ka[4];
#pragma unroll
                    for (int i = 0; i < 4; i++) qa[i] = lds64u(aa + i * 256);
#pragma unroll
                    for (int i = 0; i < 4; i++) ka[i] = lds64u(aa + 4096 + i * 256);
                    float sa[5][4];
#pragma unroll
                    for (int i = 0; i < 5; i++) sa[i][0] = sa[i][1] = sa[i][2] = sa[i][3] = 0.f;
#pragma unroll
                    for (int u = 0; u < 2; u++) {
                        const uint32_t q0 = add_bf16x2(qa[2 * u].x, qa[2 * u + 1].x), q1 = add_bf16x2(qa[2 * u].y, qa[2 * u + 1].y);
                        mma16816(sa[1], q0, qf[u].x, q1, qf[u].y, kf[2 * u].x, kf[2 * u].y);
                        mma16816(sa[2], q0, qf[u].x, q1, qf[u].y, kf[2 * u].z, kf[2 * u].w);
                        mma16816(sa[3], q0, qf[u].x, q1, qf[u].y, kf[2 * u + 1].x, kf[2 * u + 1].y);
                        mma16816(sa[4], q0, qf[u].x, q1, qf[u].y, kf[2 * u + 1].z, kf[2 * u + 1].w);
                        const uint32_t k0 = add_bf16x2(ka[2 * u].x, ka[2 * u + 1].x), k1 = add_bf16x2(ka[2 * u].y, ka[2 * u + 1].y);
                        mma16816(sa[0], q0, qf[u].x, q1, qf[u].y, k0, k1);
                        if (u == 0) SCHED_FENCE();
                    }
                    redo = __any_sync(~0u, or3(orx2(qa[0].x, ka[0].x, tag), orx2(qa[1].x, ka[1].x, tag),
                                               orx(orx(orx2(qa[2].x, ka[2].x, tag), qa[3].x, tag), ka[3].x, tag)) & 1);
#pragma unroll
                    for (int i = 1; i <= 5; i++) sts128(sw + (i % 5) * 512, sa[i % 5][0], sa[i % 5][1], sa[i % 5][2], sa[i % 5][3]);
                } while (redo);
                if (w == 0) TSV(20, n - 1);
            }
            TS(2);
            bar_sync(1, 128);
            float sc[5];
            {
                float x[4][5];
#pragma unroll
                for (int q = 0; q < 4; q++)
#pragma unroll
                    for (int n = 0; n < 5; n++) asm volatile("ld.shared.f32 %0, [%1];" : "=f"(x[q][n]) : "r"(sr + q * 2560 + n * 512) : "memory");
                if (lane == 0) mbar_arrive(bars + 8 * B_SDONE);
#pragma unroll
                for (int n = 0; n < 5; n++) sc[n] = (x[0][n] + x[1][n]) + (x[2][n] + x[3][n]);
            }
            TS(15);
#pragma unroll
            for (int n = 1; n < 5; n++) if (8 * (n - 1) > lim) sc[n] = MASK_VAL;
            float m = fmaxf(fmaxf(fmaxf(sc[0], sc[1]), fmaxf(sc[2], sc[3])), sc[4]);
            m = fmaxf(m, __shfl_xor_sync(~0u, m, 1));
            m = fmaxf(m, __shfl_xor_sync(~0u, m, 4));
            m = fmaxf(m, __shfl_xor_sync(~0u, m, 8));
            SCHED_FENCE();
            uint4 vf[4];
#pragma unroll
            for (int i = 0; i < 4; i++) vf[i] = lds128u(l16 + O_KVQ + 8192 + w * 2048 + i * 512);
            m *= -SM_SCALE_LOG2;
#pragma unroll
            for (int n = 0; n < 5; n++) {
                const uint32_t pv = pack_bf16(ex2(fmaf(sc[n], SM_SCALE_LOG2, m)), 0.f);
                asm volatile("st.shared.u16 [%0], %1;" ::"r"(pw + n * 128), "h"((uint16_t)pv) : "memory");
            }
            KEEP2(vf[0].x, vf[1].x); KEEP2(vf[2].x, vf[3].x);
            SCHED_FENCE();
            bar_sync(1, 128);
            TS(3);
            if (lane == 0) mbar_arrive(bars + 8 * B_SRDY);
            float ox[2][4], sm[4], sx[4], cc[4][4];
            unsigned char *pa, *pb;
#pragma unroll 1
            for (uint32_t nv = 0;; nv++) {
                uint32_t pf[4], p0, px[4], px0;
                ldsm4(pf, l16 + O_P + 128);
                ldsm4(px, l16 + O_P + 128 + 704);
                asm volatile("ld.shared.u32 %0, [%1];" : "=r"(p0) : "r"(l4 + O_P) : "memory");
                asm volatile("ld.shared.u32 %0, [%1];" : "=r"(px0) : "r"(l4 + O_P + 704) : "memory");
                float o[2][4];
#pragma unroll
                for (int i = 0; i < 4; i++) o[0][i] = o[1][i] = ox[0][i] = ox[1][i] = sm[i] = sx[i] = 0.f;
                constexpr uint32_t ONE2 = 0x3f803f80u;
                mma1688(sm, ONE2, ONE2, p0);
                mma1688(sx, ONE2, ONE2, px0);
#pragma unroll
                for (int c = 0; c < 2; c++) {
#pragma unroll
                    for (int u = 0; u < 2; u++) mma16816(o[u], vf[2 * u + c].x, vf[2 * u + c].y, vf[2 * u + c].z, vf[2 * u + c].w, pf[2 * c], pf[2 * c + 1]);
#pragma unroll
                    for (int u = 0; u < 2; u++) mma16816(ox[u], vf[2 * u + c].x, vf[2 * u + c].y, vf[2 * u + c].z, vf[2 * u + c].w, px[2 * c], px[2 * c + 1]);
                    mma16816(sm, ONE2, ONE2, ONE2, ONE2, pf[2 * c], pf[2 * c + 1]);
                    mma16816(sx, ONE2, ONE2, ONE2, ONE2, px[2 * c], px[2 * c + 1]);
                }
                const uint32_t vbad = orx(orx(orx2(vf[0].x, vf[1].x, tg), vf[2].x, tg), vf[3].x, tg);
                uint4 vm;
                {
                    uint32_t n = 0;
                    bool redo;
#pragma unroll 1
                    do {
                        vm = lds128v(l16 + O_VM + w * 512);
                        float o2[2][4];
#pragma unroll
                        for (int i = 0; i < 4; i++) { o2[0][i] = o[0][i]; o2[1][i] = o[1][i]; }
                        mma1688(o2[0], vm.x, vm.y, p0);
                        mma1688(o2[1], vm.z, vm.w, p0);
                        redo = __any_sync(~0u, ((vm.x ^ ~s) & 1) && ++n < SPIN_LIMIT);
                        const uint32_t oa = l4 + O_O + w * 512;
                        sts32(oa, pack_bf16(o2[0][0], o2[0][1]));
                        sts32(oa + 128, pack_bf16(o2[0][2], o2[0][3]));
                        sts32(oa + 256, pack_bf16(o2[1][0], o2[1][1]));
                        sts32(oa + 384, pack_bf16(o2[1][2], o2[1][3]));
                    } while (redo);
                    if (w == 0) TSV(21, n);
                }
                TS(4);
                fence_async_smem();
                mma1688(ox[0], vm.x, vm.y, px0);
                mma1688(ox[1], vm.z, vm.w, px0);
                sm[0] = rcp(sm[0]); sm[1] = rcp(sm[1]);
                bar_sync(1, 128);
                TS(5);
#define OP_ISSUE(t0, t1)                                                                                       \
                wg_fence();                                                                                    \
                _Pragma("unroll") for (int ks = 0; ks < 8; ks++)                                               \
                    _Pragma("unroll") for (int t = t0; t < t1; t++) {                                          \
                        constexpr uint64_t da0 = mkdesc(SM_BASE + O_WO, 16, 1024, 1), db0 = mkdesc(SM_BASE + O_O, 128, 128, 0); \
                        if (ks == 0) wg_ss8<0>(cc[t], da0 + t * 1024, db0); else wg_ss8<1>(cc[t], da0 + t * 1024 + ks * 128, db0 + ks * 16); \
                    }                                                                                          \
                wg_commit();
                OP_ISSUE(0, (OP_SPLIT ? 2 : 4));
                pa = redp + (s & 3) * 32768 + red_grp(j * 16 + (tid >> 3));
                pb = pa + 512 + ((lane >> 3) & 1) * 64 + (lane & 7) * 8;
                pa += (lane & 7) * 16;
                KEEPP(pa); KEEPP(pb);
                SCHED_FENCE();
                if (!bar_or(1, 128, vbad)) break;
                wg_wait<0>();
                const uint4* vp = &g_kvq[((s & 3) * 32 + h) * (3 * 512) + 1024 + w * 128 + lane];
#pragma unroll
                for (int i = 0; i < 4; i++) vf[i] = ldg_rlx128(vp + i * 32);
                if (nv > SPIN_LIMIT) __trap();
                bar_sync(1, 128);
            }
            {
                const float i0 = sm[0], i1 = sm[1];
#pragma unroll
                for (int hf = 0; hf < 2; hf++) {
                    if (hf == 0 || OP_SPLIT) wg_wait<0>();
                    if (hf == 0) TS(6);
                    if (OPD_EARLY && hf == OP_SPLIT && lane == 0) mbar_arrive(bars + 8 * B_OPDONE);
                    asm volatile("red.relaxed.gpu.global.add.noftz.v4.bf16x2 [%0], {%1,%2,%3,%4};" ::"l"(pa + hf * 128),
                                 "r"(pack_bf16(cc[2 * hf][0] * i0, cc[2 * hf][1] * i1)), "r"(pack_bf16(cc[2 * hf][2] * i0, cc[2 * hf][3] * i1)),
                                 "r"(pack_bf16(cc[2 * hf + 1][0] * i0, cc[2 * hf + 1][1] * i1)), "r"(pack_bf16(cc[2 * hf + 1][2] * i0, 1.f)) : "memory");
                    if (OP_SPLIT && hf == 0) { SCHED_FENCE(); OP_ISSUE(2, 4); }
                }
                asm volatile("red.relaxed.gpu.global.add.noftz.v2.bf16x2 [%0], {%1,%2};" ::"l"(pb), "r"(pack_bf16(cc[1][3] * i1, cc[3][3] * i1)), "r"(0x3f800000u) : "memory");
                if (!OPD_EARLY && lane == 0) mbar_arrive(bars + 8 * B_OPDONE);
                SCHED_FENCE();
                TS(7);
            }
            {
                const float ix0 = rcp(sx[0]), ix1 = rcp(sx[1]);
                const uint32_t xo = sb + O_XO + w * 512;
                stsm4t(xo + (lane & 7) * 64 + (((lane >> 3) ^ ((lane >> 1) & 3)) << 4), pack_bf16(ox[0][0] * ix0, ox[0][1] * ix1),
                       pack_bf16(ox[0][2] * ix0, ox[0][3] * ix1), pack_bf16(ox[1][0] * ix0, ox[1][1] * ix1), pack_bf16(ox[1][2] * ix0, ox[1][3] * ix1));
                __syncwarp();
                const uint4 ov = lds128u(xo + (lane >> 2) * 64 + (((lane & 3) ^ ((lane >> 3) & 3)) << 4));
                stg128(&g_ox[(size_t)(s * 32 + j * 8 + (lane >> 2)) * 4096 + h * 128 + w * 32 + (lane & 3) * 8], ov.x, ov.y, ov.z, ov.w);
            }
            TS(8);
            if (w == 2) { LT(s, 0, gtime()); LT(s, 1, clk()); }
            if (s == 0) GT(2);
        }
        GT(3);
        sts32(bars + 508, sf);
        TSDUMP();
        bar_sync(7, 512);
        const int m0 = (role >> 3) * 128, nb = (role & 7) * 2;
#define W2_LOAD(st, kt) { mbar_expect_tx(bars + 8 * (B_GF + (st)), 32768); tma3d(sb + (st) * 32768 + 16384, &tm_w2, 0, (kt) * 64, nb, bars + 8 * (B_GF + (st))); }
        if (w == 1 && lane == 0) {
            fence_async_smem();
#pragma unroll 1
            for (int kt = 0; kt < G_ST; kt++) W2_LOAD(kt, kt);
        }
        if (w == 0) {
            gbar_wait(&g_end, gbar_arrive(&g_end, 1, 128, lane), 0);
            int st = 0, ph = 1;
#pragma unroll 1
            for (int kt = 0; kt < 64; kt++) {
                if (kt >= G_ST) mbar_wait(bars + 8 * (B_GE + st), ph);
                if (lane == 0) {
                    if (kt >= G_ST) W2_LOAD(st, kt);
                    tma2d(sb + st * 32768, &tm_o, kt * 64, m0, bars + 8 * (B_GF + st));
                }
                if (++st == G_ST) { st = 0; ph ^= 1; }
            }
        }
    }
}

typedef CUresult (*EncodeFn)(CUtensorMap*, CUtensorMapDataType, cuuint32_t, void*, const cuuint64_t*, const cuuint64_t*,
                             const cuuint32_t*, const cuuint32_t*, CUtensorMapInterleave, CUtensorMapSwizzle,
                             CUtensorMapL2promotion, CUtensorMapFloatOOBfill);

static void make_map(EncodeFn fn, CUtensorMap* m, const void* p, uint64_t cols, uint64_t rows, uint32_t bc, uint32_t br) {
    cuuint64_t dims[2] = {cols, rows}, strides[1] = {cols * 2};
    cuuint32_t box[2] = {bc, br}, es[2] = {1, 1};
    fn(m, CU_TENSOR_MAP_DATA_TYPE_BFLOAT16, 2, (void*)p, dims, strides, box, es, CU_TENSOR_MAP_INTERLEAVE_NONE,
       CU_TENSOR_MAP_SWIZZLE_128B, CU_TENSOR_MAP_L2_PROMOTION_L2_128B, CU_TENSOR_MAP_FLOAT_OOB_FILL_NONE);
}

static Tune h_tune = {480, 1888, 38, 200, 960, 4000, 300};

extern "C" void kernel_launch(void* const* d_in, const int* in_sizes, int n_in, void* d_out, int out_size) {
    static bool init = false;
    static FftMaps fm;
    static CUtensorMap tm_x, tm_wq, tm_wk, tm_wv, tm_wo, tm_o, tm_wo2;
    if (!init) {
        void* fp = nullptr; cudaDriverEntryPointQueryResult qr;
        cudaGetDriverEntryPoint("cuTensorMapEncodeTiled", &fp, cudaEnableDefault, &qr);
        EncodeFn fn = (EncodeFn)fp;
        void* ox = nullptr; cudaGetSymbolAddress(&ox, g_ox);
        {
            cuuint64_t dims[4] = {64, 8, 16, 256}, strides[3] = {2048, 128, 16384};
            cuuint32_t box[4] = {64, 8, 8, 4}, es[4] = {1, 1, 1, 1};
            fn(&tm_x, CU_TENSOR_MAP_DATA_TYPE_BFLOAT16, 4, d_in[3], dims, strides, box, es, CU_TENSOR_MAP_INTERLEAVE_NONE,
               CU_TENSOR_MAP_SWIZZLE_128B, CU_TENSOR_MAP_L2_PROMOTION_L2_128B, CU_TENSOR_MAP_FLOAT_OOB_FILL_NONE);
        }
        void* fy = nullptr; cudaGetSymbolAddress(&fy, g_fy);
        for (int i = 0; i < 3; i++) {
            const cuuint64_t pitch = i == 2 ? 4096 : 2048;
            cuuint64_t dims[4] = {1024, 8, 16, 16}, strides[3] = {pitch, 128 * pitch, 8 * pitch};
            cuuint32_t box[4] = {64, 1, 16, 16}, es[4] = {1, 1, 1, 1};
            fn(i == 0 ? &fm.x : i == 1 ? &fm.y : &fm.o, CU_TENSOR_MAP_DATA_TYPE_BFLOAT16, 4, i == 0 ? d_in[0] : i == 1 ? fy : d_out, dims, strides, box, es,
               CU_TENSOR_MAP_INTERLEAVE_NONE, CU_TENSOR_MAP_SWIZZLE_128B, CU_TENSOR_MAP_L2_PROMOTION_L2_256B, CU_TENSOR_MAP_FLOAT_OOB_FILL_NONE);
        }
        {
            cuuint64_t dims[3] = {64, 2048, 16}, strides[2] = {2048, 128};
            cuuint32_t box[3] = {64, 8, 16}, es[3] = {1, 1, 1};
            fn(&fm.y2, CU_TENSOR_MAP_DATA_TYPE_BFLOAT16, 3, fy, dims, strides, box, es, CU_TENSOR_MAP_INTERLEAVE_NONE,
               CU_TENSOR_MAP_SWIZZLE_128B, CU_TENSOR_MAP_L2_PROMOTION_L2_128B, CU_TENSOR_MAP_FLOAT_OOB_FILL_NONE);
        }
        for (int i = 0; i < 2; i++) {
            cuuint64_t dims[3] = {256 * 513 - 448, 8, 8}, strides[2] = {128, 256 * 1026};
            cuuint32_t box[3] = {72, 8, 8}, es[3] = {1, 1, 1};
            fn(i ? &fm.wi : &fm.wr, CU_TENSOR_MAP_DATA_TYPE_BFLOAT16, 3, d_in[1 + i], dims, strides, box, es, CU_TENSOR_MAP_INTERLEAVE_NONE,
               CU_TENSOR_MAP_SWIZZLE_NONE, CU_TENSOR_MAP_L2_PROMOTION_L2_128B, CU_TENSOR_MAP_FLOAT_OOB_FILL_NONE);
        }
        make_map(fn, &tm_wq, d_in[5], 4096, 1024, 64, 256);
        make_map(fn, &tm_wk, d_in[6], 4096, 1024, 64, 256);
        make_map(fn, &tm_wv, d_in[7], 4096, 1024, 64, 256);
        make_map(fn, &tm_wo, d_in[8], 1024, 4096, 64, 128);
        make_map(fn, &tm_o, ox, 4096, 2048, 64, 128);
        {
            cuuint64_t dims[3] = {64, 4096, 16}, strides[2] = {2048, 128};
            cuuint32_t box[3] = {64, 64, 2}, es[3] = {1, 1, 1};
            fn(&tm_wo2, CU_TENSOR_MAP_DATA_TYPE_BFLOAT16, 3, d_in[8], dims, strides, box, es, CU_TENSOR_MAP_INTERLEAVE_NONE,
               CU_TENSOR_MAP_SWIZZLE_128B, CU_TENSOR_MAP_L2_PROMOTION_L2_128B, CU_TENSOR_MAP_FLOAT_OOB_FILL_NONE);
        }
        cudaFuncSetAttribute(rmt_main, cudaFuncAttributeMaxDynamicSharedMemorySize, MAIN_SMEM);
        init = true;
    }
    rmt_main<<<132, 512, MAIN_SMEM>>>(tm_x, tm_wq, tm_wk, tm_wv, tm_wo, (const bf16*)d_in[4], h_tune, fm, tm_o, tm_wo2, (bf16*)d_out);
}
```

```cpp
#include <cuda_runtime.h>
#include <cuda_bf16.h>
#include <cuda.h>
#include <stdint.h>

typedef __nv_bfloat16 bf16;

#define DBG_TIMING 0

#define SPIN_LIMIT (1u << 22)

__device__ __forceinline__ uint32_t smem_u32(const void* p) { return (uint32_t)__cvta_generic_to_shared(p); }
__device__ __forceinline__ uint32_t clk() { uint32_t c; asm volatile("mov.u32 %0, %%clock;" : "=r"(c)::"memory"); return c; }
#define SCHED_FENCE() sf ^= (uint32_t)clock64()
#define KEEP2(a, b) asm volatile("lop3.b32 %0, %0, %1, %2, 0x96;" : "+r"(sf) : "r"((uint32_t)(a)), "r"((uint32_t)(b)))
#define KEEPP(p) KEEP2((uintptr_t)(p), (uintptr_t)(p) >> 32)
__device__ __forceinline__ uint32_t gtime() { uint32_t c; asm volatile("mov.u32 %0, %%globaltimer_lo;" : "=r"(c)::"memory"); return c; }
__device__ __forceinline__ void wait_clk(uint32_t t0, uint32_t d) {
    asm volatile("{\n.reg .pred p;\n.reg .s32 t;\n.reg .b64 c;\nWL:\nmov.u64 c, %%clock64;\ncvt.u32.u64 t, c;\nsub.s32 t, t, %0;\nsetp.lt.s32 p, t, 0;\n@p bra.uni WL;\n}" ::"r"(t0 + d) : "memory");
}
__device__ __forceinline__ void wait_gtime(uint32_t t1) {
    asm volatile("{\n.reg .pred p;\n.reg .s32 t;\n.reg .b64 c;\nWL:\nmov.u64 c, %%globaltimer;\ncvt.u32.u64 t, c;\nsub.s32 t, t, %0;\nsetp.lt.s32 p, t, 0;\n@p bra.uni WL;\n}" ::"r"(t1) : "memory");
}

__device__ __forceinline__ void mbar_init(uint32_t bar, uint32_t cnt) {
    asm volatile("mbarrier.init.shared::cta.b64 [%0], %1;" ::"r"(bar), "r"(cnt) : "memory");
}
__device__ __forceinline__ void mbar_arrive(uint32_t bar) {
    asm volatile("mbarrier.arrive.shared::cta.b64 _, [%0];" ::"r"(bar) : "memory");
}
__device__ __forceinline__ void mbar_expect_tx(uint32_t bar, uint32_t bytes) {
    asm volatile("mbarrier.arrive.expect_tx.shared::cta.b64 _, [%0], %1;" ::"r"(bar), "r"(bytes) : "memory");
}
__device__ __forceinline__ void mbar_wait(uint32_t bar, uint32_t parity) {
    asm volatile(
        "{\n.reg .pred p, q;\n.reg .u32 n;\nmov.u32 n, 0;\n"
        "WL:\nmbarrier.try_wait.parity.shared::cta.b64 p, [%0], %1;\n"
        "add.u32 n, n, 1;\nsetp.gt.u32 q, n, %2;\n@q trap;\n@!p bra.uni WL;\n}" ::"r"(bar), "r"(parity), "n"(SPIN_LIMIT) : "memory");
}
__device__ __forceinline__ void mbar_wait_cluster(uint32_t bar, uint32_t parity) {
    asm volatile(
        "{\n.reg .pred p, q;\n.reg .u32 n;\nmov.u32 n, 0;\n"
        "WL:\nmbarrier.try_wait.parity.acquire.cluster.shared::cta.b64 p, [%0], %1;\n"
        "add.u32 n, n, 1;\nsetp.gt.u32 q, n, %2;\n@q trap;\n@!p bra.uni WL;\n}" ::"r"(bar), "r"(parity), "n"(SPIN_LIMIT) : "memory");
}
__device__ __forceinline__ void tma2d(uint32_t dst, const CUtensorMap* m, int c0, int c1, uint32_t bar) {
    asm volatile("cp.async.bulk.tensor.2d.shared::cluster.global.mbarrier::complete_tx::bytes [%0], [%1, {%3, %4}], [%2];"
                 ::"r"(dst), "l"(m), "r"(bar), "r"(c0), "r"(c1) : "memory");
}
__device__ __forceinline__ void tma3d(uint32_t dst, const CUtensorMap* m, int c0, int c1, int c2, uint32_t bar) {
    asm volatile("cp.async.bulk.tensor.3d.shared::cluster.global.mbarrier::complete_tx::bytes [%0], [%1, {%3, %4, %5}], [%2];"
                 ::"r"(dst), "l"(m), "r"(bar), "r"(c0), "r"(c1), "r"(c2) : "memory");
}
__device__ __forceinline__ void tma4d(uint32_t dst, const CUtensorMap* m, int c2, int c3, uint32_t bar) {
    asm volatile("cp.async.bulk.tensor.4d.shared::cluster.global.mbarrier::complete_tx::bytes [%0], [%1, {%5, %5, %3, %4}], [%2];"
                 ::"r"(dst), "l"(m), "r"(bar), "r"(c2), "r"(c3), "r"(0) : "memory");
}
__device__ __forceinline__ void bulk_g2s(uint32_t dst, const void* src, uint32_t bytes, uint32_t bar) {
    asm volatile("cp.async.bulk.shared::cluster.global.mbarrier::complete_tx::bytes [%0], [%1], %2, [%3];"
                 ::"r"(dst), "l"(src), "r"(bytes), "r"(bar) : "memory");
}
__device__ __forceinline__ void tma4d_prefetch(const CUtensorMap* m, int c2, int c3) {
    asm volatile("cp.async.bulk.prefetch.tensor.4d.L2.global [%0, {%3, %3, %1, %2}];" ::"l"(m), "r"(c2), "r"(c3), "r"(0) : "memory");
}
__device__ __forceinline__ void tma2d_prefetch(const CUtensorMap* m, int c0, int c1) {
    asm volatile("cp.async.bulk.prefetch.tensor.2d.L2.global [%0, {%1, %2}];" ::"l"(m), "r"(c0), "r"(c1) : "memory");
}
__device__ __forceinline__ void fence_async_smem() { asm volatile("fence.proxy.async.shared::cta;" ::: "memory"); }
__device__ __forceinline__ void fence_gpu() { asm volatile("fence.acq_rel.gpu;" ::: "memory"); }
__device__ __forceinline__ float rcp(float x) { float r; asm("rcp.approx.ftz.f32 %0, %1;" : "=f"(r) : "f"(x)); return r; }
__device__ __forceinline__ void bar_sync(int id, int n) { asm volatile("bar.sync %0, %1;" ::"r"(id), "r"(n) : "memory"); }

__device__ __forceinline__ bool bar_or(int id, int n, uint32_t x) {
    uint32_t r;
    asm volatile("{\n.reg .pred p, q;\n.reg .b32 t;\nand.b32 t, %3, 1;\nsetp.ne.u32 p, t, 0;\nbar.red.or.pred q, %1, %2, p;\nselp.u32 %0, 1, 0, q;\n}"
                 : "=r"(r) : "r"(id), "r"(n), "r"(x) : "memory");
    return __any_sync(~0u, r);
}
__device__ __forceinline__ uint32_t or3(uint32_t a, uint32_t b, uint32_t c) {
    uint32_t r; asm("lop3.b32 %0, %1, %2, %3, 0xFE;" : "=r"(r) : "r"(a), "r"(b), "r"(c)); return r;
}
__device__ __forceinline__ uint32_t pack_bf16(float lo, float hi) {
    uint32_t r; asm("cvt.rn.bf16x2.f32 %0, %1, %2;" : "=r"(r) : "f"(hi), "f"(lo)); return r;
}
__device__ __forceinline__ uint32_t add_bf16x2(uint32_t a, uint32_t b) {
    uint32_t r; asm volatile("add.rn.bf16x2 %0, %1, %2;" : "=r"(r) : "r"(a), "r"(b)); return r;
}
__device__ __forceinline__ uint32_t movm(uint32_t a) {
    uint32_t r; asm volatile("movmatrix.sync.aligned.m8n8.trans.b16 %0, %1;" : "=r"(r) : "r"(a)); return r;
}
__device__ __forceinline__ uint32_t orx(uint32_t acc, uint32_t a, uint32_t t) {
    uint32_t r; asm("lop3.b32 %0, %1, %2, %3, 0xF6;" : "=r"(r) : "r"(acc), "r"(a), "r"(t)); return r;
}
__device__ __forceinline__ uint32_t orx2(uint32_t a, uint32_t b, uint32_t t) {
    uint32_t r; asm("lop3.b32 %0, %1, %2, %3, 0x7E;" : "=r"(r) : "r"(a), "r"(b), "r"(t)); return r;
}
__device__ __forceinline__ float ex2(float x) { float r; asm("ex2.approx.ftz.f32 %0, %1;" : "=f"(r) : "f"(x)); return r; }
__device__ __forceinline__ void ldsm4t(uint32_t (&r)[4], uint32_t a) {
    asm volatile("ldmatrix.sync.aligned.m8n8.x4.trans.shared.b16 {%0,%1,%2,%3}, [%4];"
                 : "=r"(r[0]), "=r"(r[1]), "=r"(r[2]), "=r"(r[3]) : "r"(a) : "memory");
}
__device__ __forceinline__ void ldsm4(uint32_t (&r)[4], uint32_t a) {
    asm volatile("ldmatrix.sync.aligned.m8n8.x4.shared.b16 {%0,%1,%2,%3}, [%4];"
                 : "=r"(r[0]), "=r"(r[1]), "=r"(r[2]), "=r"(r[3]) : "r"(a) : "memory");
}
__device__ __forceinline__ void stsm4t(uint32_t a, uint32_t r0, uint32_t r1, uint32_t r2, uint32_t r3) {
    asm volatile("stmatrix.sync.aligned.m8n8.x4.trans.shared.b16 [%0], {%1,%2,%3,%4};"
                 ::"r"(a), "r"(r0), "r"(r1), "r"(r2), "r"(r3) : "memory");
}
__device__ __forceinline__ void stsm4(uint32_t a, uint32_t r0, uint32_t r1, uint32_t r2, uint32_t r3) {
    asm volatile("stmatrix.sync.aligned.m8n8.x4.shared.b16 [%0], {%1,%2,%3,%4};"
                 ::"r"(a), "r"(r0), "r"(r1), "r"(r2), "r"(r3) : "memory");
}
__device__ __forceinline__ void mma16816(float* c, uint32_t a0, uint32_t a1, uint32_t a2, uint32_t a3, uint32_t b0, uint32_t b1) {
    asm volatile("mma.sync.aligned.m16n8k16.row.col.f32.bf16.bf16.f32 {%0,%1,%2,%3}, {%4,%5,%6,%7}, {%8,%9}, {%0,%1,%2,%3};"
                 : "+f"(c[0]), "+f"(c[1]), "+f"(c[2]), "+f"(c[3]) : "r"(a0), "r"(a1), "r"(a2), "r"(a3), "r"(b0), "r"(b1));
}
__device__ __forceinline__ void mma1688(float* c, uint32_t a0, uint32_t a1, uint32_t b0) {
    asm volatile("mma.sync.aligned.m16n8k8.row.col.f32.bf16.bf16.f32 {%0,%1,%2,%3}, {%4,%5}, {%6}, {%0,%1,%2,%3};"
                 : "+f"(c[0]), "+f"(c[1]), "+f"(c[2]), "+f"(c[3]) : "r"(a0), "r"(a1), "r"(b0));
}
__device__ __forceinline__ void sts128(uint32_t a, float x, float y, float z, float w) {
    asm volatile("st.shared.v4.f32 [%0], {%1,%2,%3,%4};" ::"r"(a), "f"(x), "f"(y), "f"(z), "f"(w) : "memory");
}
__device__ __forceinline__ void sts64(uint32_t a, float x, float y) {
    asm volatile("st.shared.v2.f32 [%0], {%1,%2};" ::"r"(a), "f"(x), "f"(y) : "memory");
}
__device__ __forceinline__ void sts32(uint32_t a, uint32_t x) { asm volatile("st.shared.b32 [%0], %1;" ::"r"(a), "r"(x) : "memory"); }
__device__ __forceinline__ void sts128u(uint32_t a, uint4 v) {
    asm volatile("st.shared.v4.b32 [%0], {%1,%2,%3,%4};" ::"r"(a), "r"(v.x), "r"(v.y), "r"(v.z), "r"(v.w) : "memory");
}
__device__ __forceinline__ float4 lds128(uint32_t a) {
    float4 v; asm volatile("ld.shared.v4.f32 {%0,%1,%2,%3}, [%4];" : "=f"(v.x), "=f"(v.y), "=f"(v.z), "=f"(v.w) : "r"(a) : "memory"); return v;
}
__device__ __forceinline__ uint4 lds128u(uint32_t a) {
    uint4 v; asm volatile("ld.shared.v4.b32 {%0,%1,%2,%3}, [%4];" : "=r"(v.x), "=r"(v.y), "=r"(v.z), "=r"(v.w) : "r"(a) : "memory"); return v;
}
__device__ __forceinline__ uint4 lds128v(uint32_t a) {
    uint4 v; asm volatile("ld.volatile.shared.v4.b32 {%0,%1,%2,%3}, [%4];" : "=r"(v.x), "=r"(v.y), "=r"(v.z), "=r"(v.w) : "r"(a) : "memory"); return v;
}
__device__ __forceinline__ void sts64u(uint32_t a, uint2 v) { asm volatile("st.shared.v2.b32 [%0], {%1,%2};" ::"r"(a), "r"(v.x), "r"(v.y) : "memory"); }
__device__ __forceinline__ uint2 lds64u(uint32_t a) {
    uint2 v; asm volatile("ld.shared.v2.b32 {%0,%1}, [%2];" : "=r"(v.x), "=r"(v.y) : "r"(a) : "memory"); return v;
}
__device__ __forceinline__ float2 lds64(uint32_t a) {
    float2 v; asm volatile("ld.shared.v2.f32 {%0,%1}, [%2];" : "=f"(v.x), "=f"(v.y) : "r"(a) : "memory"); return v;
}
__device__ __forceinline__ uint2 ldg_rlx64(const void* p) {
    uint2 v; asm volatile("ld.relaxed.gpu.global.v2.b32 {%0,%1}, [%2];" : "=r"(v.x), "=r"(v.y) : "l"(p) : "memory"); return v;
}
__device__ __forceinline__ uint4 ldg_rlx128(const void* p) {
    uint4 v; asm volatile("ld.relaxed.gpu.global.v4.b32 {%0,%1,%2,%3}, [%4];" : "=r"(v.x), "=r"(v.y), "=r"(v.z), "=r"(v.w) : "l"(p) : "memory"); return v;
}
__device__ __forceinline__ void stg_rlx64(void* p, uint32_t x, uint32_t y) {
    asm volatile("st.relaxed.gpu.global.v2.b32 [%0], {%1,%2};" ::"l"(p), "r"(x), "r"(y) : "memory");
}
__device__ __forceinline__ void stg_rlx128(void* p, uint32_t x, uint32_t y, uint32_t z, uint32_t w) {
    asm volatile("st.relaxed.gpu.global.v4.b32 [%0], {%1,%2,%3,%4};" ::"l"(p), "r"(x), "r"(y), "r"(z), "r"(w) : "memory");
}
__device__ __forceinline__ uint32_t ldg_rlx32(const void* p) {
    uint32_t v; asm volatile("ld.relaxed.gpu.global.b32 %0, [%1];" : "=r"(v) : "l"(p) : "memory"); return v;
}
__device__ __forceinline__ void stg128(void* p, uint32_t x, uint32_t y, uint32_t z, uint32_t w) {
    asm volatile("st.global.v4.b32 [%0], {%1,%2,%3,%4};" ::"l"(p), "r"(x), "r"(y), "r"(z), "r"(w) : "memory");
}
__device__ __forceinline__ uint32_t ld_acquire(const unsigned* p) {
    uint32_t v; asm volatile("ld.acquire.gpu.global.u32 %0, [%1];" : "=r"(v) : "l"(p) : "memory"); return v;
}
__device__ __forceinline__ void red_add_u32(unsigned* p, uint32_t v) {
    asm volatile("red.relaxed.gpu.global.add.u32 [%0], %1;" ::"l"(p), "r"(v) : "memory");
}
__device__ __forceinline__ void wait_counter(const unsigned* p, uint32_t target) {
    uint32_t n = 0;
    while (ld_acquire(p) < target) { if (++n > SPIN_LIMIT) __trap(); }
}

__device__ __forceinline__ void wg_fence() { asm volatile("wgmma.fence.sync.aligned;" ::: "memory"); }
__device__ __forceinline__ void wg_commit() { asm volatile("wgmma.commit_group.sync.aligned;" ::: "memory"); }
template <int N> __device__ __forceinline__ void wg_wait() { asm volatile("wgmma.wait_group.sync.aligned %0;" ::"n"(N) : "memory"); }
__host__ __device__ constexpr uint64_t mkdesc(uint32_t addr, uint32_t lbo, uint32_t sbo, uint32_t swz) {
    return (uint64_t)((addr & 0x3FFFF) >> 4) | ((uint64_t)(lbo >> 4) << 16) | ((uint64_t)(sbo >> 4) << 32) | ((uint64_t)swz << 62);
}
#define F4(d, o) "+f"(d[o]), "+f"(d[o + 1]), "+f"(d[o + 2]), "+f"(d[o + 3])
template <int SC> __device__ __forceinline__ void wg_rs32(float (&d)[16], const uint32_t (&a)[4], uint64_t db) {
    asm volatile("wgmma.mma_async.sync.aligned.m64n32k16.f32.bf16.bf16 "
                 "{%0,%1,%2,%3,%4,%5,%6,%7,%8,%9,%10,%11,%12,%13,%14,%15}, {%16,%17,%18,%19}, %20, %21, 1, 1, 0;"
                 : F4(d, 0), F4(d, 4), F4(d, 8), F4(d, 12)
                 : "r"(a[0]), "r"(a[1]), "r"(a[2]), "r"(a[3]), "l"(db), "n"(SC));
}
template <int SC> __device__ __forceinline__ void wg_rs40(float (&d)[20], const uint32_t (&a)[4], uint64_t db) {
    asm volatile("wgmma.mma_async.sync.aligned.m64n40k16.f32.bf16.bf16 "
                 "{%0,%1,%2,%3,%4,%5,%6,%7,%8,%9,%10,%11,%12,%13,%14,%15,%16,%17,%18,%19}, {%20,%21,%22,%23}, %24, %25, 1, 1, 0;"
                 : F4(d, 0), F4(d, 4), F4(d, 8), F4(d, 12), F4(d, 16)
                 : "r"(a[0]), "r"(a[1]), "r"(a[2]), "r"(a[3]), "l"(db), "n"(SC));
}
template <int SC> __device__ __forceinline__ void wg_ss40(float (&d)[20], uint64_t da, uint64_t db) {
    asm volatile("wgmma.mma_async.sync.aligned.m64n40k16.f32.bf16.bf16 "
                 "{%0,%1,%2,%3,%4,%5,%6,%7,%8,%9,%10,%11,%12,%13,%14,%15,%16,%17,%18,%19}, %20, %21, %22, 1, 1, 1, 0;"
                 : F4(d, 0), F4(d, 4), F4(d, 8), F4(d, 12), F4(d, 16)
                 : "l"(da), "l"(db), "n"(SC));
}
template <int SC> __device__ __forceinline__ void wg_ss8(float (&d)[4], uint64_t da, uint64_t db) {
    asm volatile("wgmma.mma_async.sync.aligned.m64n8k16.f32.bf16.bf16 {%0,%1,%2,%3}, %4, %5, %6, 1, 1, 1, 1;"
                 : F4(d, 0) : "l"(da), "l"(db), "n"(SC));
}

constexpr int DBG_N = 11;
#define LT(st, k, v) do {} while (0)
#define TSI(st) do {} while (0)
#define TS(k) do {} while (0)
#define TSV(k, v) do {} while (0)
#define TSDUMP() do {} while (0)
#define GT(k) do {} while (0)

__device__ __align__(256) uint4 g_fy[2048 * 128];

constexpr uint32_t FG_SIZE = 2 * 32768 + 36864;
constexpr uint32_t FT_F16 = 2 * FG_SIZE, FT_B1F = FT_F16 + 2048, FT_B1I = FT_B1F + 2048, FT_C = FT_B1I + 2048, FT_A8 = FT_C + 2048,
                   FT_TWC = FT_A8 + 512, FT_TWB = FT_TWC + 8192, FT_BAR = FT_TWB + 8192, FFT_SMEM = FT_BAR + 256;
struct FftMaps { CUtensorMap x, y, o, y2, wr, wi; };

__device__ __forceinline__ float2 wroot(int e) {
    float s, c; sincospif((float)(e & 2047) * (-1.f / 1024.f), &s, &c); return make_float2(c, s);
}
__device__ __forceinline__ uint4 afrag(float2 a, float2 b) {
    return make_uint4(pack_bf16(a.x, -a.y), pack_bf16(a.y, a.x), pack_bf16(b.x, -b.y), pack_bf16(b.y, b.x));
}
__device__ __forceinline__ uint4 conjfrag(uint4 v) { return make_uint4(v.x ^ 0x80000000u, v.y ^ 0x8000u, v.z ^ 0x80000000u, v.w ^ 0x8000u); }
__device__ __forceinline__ uint4 negfrag(uint4 v) { return make_uint4(v.x ^ 0x80008000u, v.y ^ 0x80008000u, v.z ^ 0x80008000u, v.w ^ 0x80008000u); }
__device__ __forceinline__ uint32_t comp(const uint4& v, int i) { return i == 0 ? v.x : i == 1 ? v.y : i == 2 ? v.z : v.w; }
__device__ __forceinline__ void setcomp(uint4& v, int i, uint32_t x) { if (i == 0) v.x = x; else if (i == 1) v.y = x; else if (i == 2) v.z = x; else v.w = x; }
__device__ __forceinline__ float2 cmul(float2 a, float2 b) { return make_float2(a.x * b.x - a.y * b.y, a.x * b.y + a.y * b.x); }
__device__ __forceinline__ float2 cmulc(float2 a, float2 b) { return make_float2(a.x * b.x + a.y * b.y, a.y * b.x - a.x * b.y); }

__device__ __forceinline__ uint32_t pack_h2(float2 a) { uint32_t r; asm("cvt.rn.f16x2.f32 %0, %1, %2;" : "=r"(r) : "f"(a.y), "f"(a.x)); return r; }
__device__ __forceinline__ float2 unpack_h2(uint32_t v) {
    float2 r; asm("{\n.reg .b16 l, h;\nmov.b32 {l, h}, %2;\ncvt.f32.f16 %0, l;\ncvt.f32.f16 %1, h;\n}" : "=f"(r.x), "=f"(r.y) : "r"(v)); return r;
}
__device__ __forceinline__ void fft_tables(uint32_t tb, int tid, int nthr) {
    for (int i = tid; i < 128; i += nthr) {
        const int lane = i & 31, q = i >> 5, g = lane >> 2, t = lane & 3, o = 8 * (q >> 1) + g, in = 8 * (q & 1) + 2 * t;
        sts128u(tb + FT_F16 + i * 16, afrag(wroot(128 * o * in), wroot(128 * o * (in + 1))));
        sts128u(tb + FT_B1F + i * 16, afrag(wroot(64 * (1 + 2 * o) * in), wroot(64 * (1 + 2 * o) * (in + 1))));
        sts128u(tb + FT_B1I + i * 16, afrag(wroot(-64 * o * (1 + 2 * in)), wroot(-64 * o * (3 + 2 * in))));
        uint4 v;
        for (int r = 0; r < 4; r++) {
            const float2 a = wroot(128 * (4 * r + t) * (4 * q + (g >> 1)));
            setcomp(v, r, (g & 1) ? pack_bf16(a.y, a.x) : pack_bf16(a.x, -a.y));
        }
        sts128u(tb + FT_C + i * 16, v);
        if (q == 0) sts128u(tb + FT_A8 + lane * 16, afrag(wroot(256 * g * 2 * t), wroot(256 * g * (2 * t + 1))));
    }
    for (int i = tid; i < 512; i += nthr) {
        const int lane = i & 31, r = (i >> 5) & 3, phi = 8 * (i >> 7) + (lane >> 2), c = 4 * r + (lane & 3);
        const float2 a = wroot(4 * c * phi), b = wroot(2 * (phi + 32 * c));
        constexpr float SC = 1.f / (2.f * 2048.f * 512.f);
        sts128(tb + FT_TWC + i * 16, a.x * SC, a.y * SC, b.x, b.y);
    }
    for (int i = tid; i < 512; i += nthr) {
        const int lane = i & 31, r = (i >> 5) & 3, fa = (i >> 7) & 1, hf = i >> 8, c = 8 * (lane & 1) + r;
        const int p0 = fa + 2 * (lane >> 2), p1 = p0 + 16, s0 = (hf && p0) ? 32 - p0 : p0, s1 = hf ? 32 - p1 : p1;
        sts128u(tb + FT_TWB + i * 16, make_uint4(pack_h2(wroot(4 * c * s0)), pack_h2(wroot(4 * (c + 4) * s0)),
                                                 pack_h2(wroot(4 * c * s1)), pack_h2(wroot(4 * (c + 4) * s1))));
    }
}

template <bool TW>
__device__ __forceinline__ void dft16(uint4 (&out)[4], const uint4 (&in)[4], const uint4 (&m)[4], const uint4 (&tw)[4]) {
#pragma unroll
    for (int i = 0; i < 4; i++)
#pragma unroll
        for (int mt = 0; mt < 2; mt++) {
            float c[4] = {0.f, 0.f, 0.f, 0.f};
            mma16816(c, m[2 * mt].x, m[2 * mt].y, m[2 * mt].z, m[2 * mt].w, comp(in[0], i), comp(in[1], i));
            mma16816(c, m[2 * mt + 1].x, m[2 * mt + 1].y, m[2 * mt + 1].z, m[2 * mt + 1].w, comp(in[2], i), comp(in[3], i));
            if (TW) {
                const float2 a = cmul(make_float2(c[0], c[2]), unpack_h2(comp(tw[i], 2 * mt))), b = cmul(make_float2(c[1], c[3]), unpack_h2(comp(tw[i], 2 * mt + 1)));
                setcomp(out[2 * mt], i, pack_bf16(a.x, a.y));
                setcomp(out[2 * mt + 1], i, pack_bf16(b.x, b.y));
            } else {
                setcomp(out[2 * mt], i, pack_bf16(c[0], c[2]));
                setcomp(out[2 * mt + 1], i, pack_bf16(c[1], c[3]));
            }
        }
}
__device__ __forceinline__ void tma_ld4(uint32_t dst, const CUtensorMap* m, int c0, int c1, uint32_t bar) {
    asm volatile("cp.async.bulk.tensor.4d.shared::cluster.global.mbarrier::complete_tx::bytes [%0], [%1, {%3, %4, %5, %5}], [%2];"
                 ::"r"(dst), "l"(m), "r"(bar), "r"(c0), "r"(c1), "r"(0) : "memory");
}
__device__ __forceinline__ void tma_st4(uint32_t src, const CUtensorMap* m, int c0, int c1) {
    asm volatile("cp.async.bulk.tensor.4d.global.shared::cta.bulk_group [%1, {%2, %3, %4, %4}], [%0];" ::"r"(src), "l"(m), "r"(c0), "r"(c1), "r"(0) : "memory");
}
__device__ __forceinline__ void tma_ld3(uint32_t dst, const CUtensorMap* m, int c0, int c1, uint32_t bar) {
    asm volatile("cp.async.bulk.tensor.3d.shared::cluster.global.mbarrier::complete_tx::bytes [%0], [%1, {%3, %4, %5}], [%2];"
                 ::"r"(dst), "l"(m), "r"(bar), "r"(c0), "r"(c1), "r"(0) : "memory");
}
__device__ __forceinline__ void tma_st3(uint32_t src, const CUtensorMap* m, int c0, int c1) {
    asm volatile("cp.async.bulk.tensor.3d.global.shared::cta.bulk_group [%1, {%2, %3, %4}], [%0];" ::"r"(src), "l"(m), "r"(c0), "r"(c1), "r"(0) : "memory");
}
__device__ __forceinline__ void bulk_commit() { asm volatile("cp.async.bulk.commit_group;" ::: "memory"); }
__device__ __forceinline__ void bulk_wait_read() { asm volatile("cp.async.bulk.wait_group.read 0;" ::: "memory"); }
__device__ __forceinline__ void bulk_wait_all() { asm volatile("cp.async.bulk.wait_group 0;" ::: "memory"); }

__device__ __forceinline__ float2 wroot_fast(int e) {
    float s, c; __sincosf((float)(((e + 1024) & 2047) - 1024) * (-3.14159265358979f / 1024.f), &s, &c); return make_float2(c, s);
}
template <bool INV, int NT>
__device__ __forceinline__ void fft_col(int s2, int t0, const CUtensorMap* src, const CUtensorMap* dst, uint32_t gb, uint32_t mb,
                                        int w, int lane, int bar) {
    const int g = lane >> 2, t = lane & 3;
    const bool lead = w == 4 && lane == 0;
    if (NT > 1 && lead)
        for (int i = 0; i < 2; i++) { mbar_expect_tx(mb + 8 * i, 32768); tma_ld4(gb + i * 32768, src, (t0 + i) * 64, s2, mb + 8 * i); }
    uint4 f[4], m[2][4];
#pragma unroll
    for (int i = 0; i < 4; i++) {
        const int o = 8 * (i >> 1) + g, in = 8 * (i & 1) + 2 * t, sg = INV ? -128 : 128;
        f[i] = afrag(wroot_fast(sg * o * in), wroot_fast(sg * o * (in + 1)));
#pragma unroll
        for (int q = 0; q < 2; q++) {
            const int z = 2 * w + q;
            m[q][i] = INV ? afrag(wroot_fast(-(8 * o + s2) * (z + 16 * in)), wroot_fast(-(8 * o + s2) * (z + 16 * in + 16)))
                          : afrag(wroot_fast((z + 16 * o) * (8 * in + s2)), wroot_fast((z + 16 * o) * (8 * in + 8 + s2)));
        }
    }
    const uint32_t r1 = (32 * w + 2 * t) * 128 + ((g ^ (2 * t)) << 4);
    const uint32_t w1 = (32 * w + g) * 128 + (((2 * t) ^ (((w & 3) << 1) | (g & 1))) << 4);
    const uint32_t r2 = (32 * t + 2 * w) * 128 + ((g ^ (2 * t)) << 4);
    const uint32_t w2 = (32 * w + g) * 128 + (((2 * t) ^ g) << 4);
    int bi = 0, ph = 0;
#pragma unroll 1
    for (int it = 0; it < NT; it++) {
        const uint32_t buf = gb + bi * 32768;
        mbar_wait(mb + 8 * bi, ph);
        uint4 in[2][4], out[4];
#pragma unroll
        for (int q = 0; q < 2; q++)
#pragma unroll
            for (int i = 0; i < 4; i++) in[q][i] = lds128u(buf + (r1 ^ ((i & 1) * 0x90)) + (i >> 1) * 1024 + q * 2048);
        __syncwarp();
#pragma unroll
        for (int q = 0; q < 2; q++) {
            if (INV) dft16<false>(out, in[q], m[q], f); else dft16<false>(out, in[q], f, f);
#pragma unroll
            for (int i = 0; i < 4; i++) sts128u(buf + (w1 ^ ((i & 1) << 4)) + (i >> 1) * 1024 + q * 2048, out[i]);
        }
        bar_sync(bar, 256);
#pragma unroll
        for (int q = 0; q < 2; q++)
#pragma unroll
            for (int i = 0; i < 4; i++) in[q][i] = lds128u(buf + (r2 ^ (q * 0x90)) + (i & 1) * 2048 + (i >> 1) * 16384);
        const int bn = bi == 0 ? 2 : bi - 1;
        if (lead && it < NT - 2) { bulk_wait_read(); mbar_expect_tx(mb + 8 * bn, 32768); tma_ld4(gb + bn * 32768, src, (t0 + it + 2) * 64, s2, mb + 8 * bn); }
        bar_sync(bar, 256);
#pragma unroll
        for (int q = 0; q < 2; q++) {
            if (INV) dft16<false>(out, in[q], f, f); else dft16<false>(out, in[q], m[q], f);
#pragma unroll
            for (int i = 0; i < 4; i++) sts128u(buf + (w2 ^ ((i & 1) << 4)) + (i >> 1) * 1024 + q * 2048, out[i]);
        }
        fence_async_smem();
        bar_sync(bar, 256);
        if (NT > 1 && lead) { tma_st4(buf, dst, (t0 + it) * 64, s2); bulk_commit(); }
        if (++bi == 3) { bi = 0; ph ^= 1; }
    }
    if (NT > 1 && lead) bulk_wait_read();
}

__device__ __forceinline__ float ldw(uint32_t a) {
    uint16_t v; asm volatile("ld.shared.u16 %0, [%1];" : "=h"(v) : "r"(a) : "memory");
    return __uint_as_float((uint32_t)v << 16);
}
__device__ __forceinline__ void fft_mid(int grp, const FftMaps& fm, uint32_t tb,
                                        uint32_t gb, uint32_t mb, uint32_t& cnt, int w, int lane, int bar) {
    const int g = lane >> 2, t = lane & 3;
    const bool lead = w == 4 && lane == 0;
    const uint32_t wb = gb + 65536;
#define MID_LOAD(k, c)                                                                                                  \
    { mbar_expect_tx(mb + 8 * ((c) & 1), 32768);                                                                        \
      tma_ld3(gb + ((c) & 1) * 32768, &fm.y2, 0, (k) * 8, mb + 8 * ((c) & 1));                                          \
      tma_ld3(gb + ((c) & 1) * 32768 + 16384, &fm.y2, 0, ((256 - (k)) & 255) * 8, mb + 8 * ((c) & 1)); }
#define MID_LOADW(k)                                                                                                    \
    { mbar_expect_tx(mb + 16, 36864);                                                                                   \
      tma_ld3(wb, &fm.wr, (k) * 513 & ~7, 0, mb + 16); tma_ld3(wb + 9216, &fm.wi, (k) * 513 & ~7, 0, mb + 16);          \
      tma_ld3(wb + 18432, &fm.wr, ((256 - (k)) & 255) * 513 & ~7, 0, mb + 16); tma_ld3(wb + 27648, &fm.wi, ((256 - (k)) & 255) * 513 & ~7, 0, mb + 16); }
    if (lead) { MID_LOAD(grp, cnt); MID_LOADW(grp); }
    const int hB = w >> 2, faB = (w >> 1) & 1, xB = faB;
    const int phi = 8 * (w & 3) + g;
    const uint32_t rA = (8 * w + 2 * t) * 128 + ((g ^ (2 * t)) << 4);
    const uint32_t wA = (8 * w + g) * 128 + (((2 * t) ^ ((g & 1) | ((w & 3) << 1))) << 4);
    const uint32_t oB = (w >> 1) * 8192 + (w & 1) * 512;
    const uint32_t rB = oB + (8 * t + (g >> 2)) * 128 + (((g & 3) ^ ((g >> 2) | (t << 1)) ^ xB) << 4);
    const uint32_t wB = oB + (8 * (g >> 1) + (t >> 1)) * 128 + (((((g & 1) << 2) | (2 * (t & 1))) ^ ((t >> 1) | ((g >> 1) << 1)) ^ xB) << 4);
    const uint32_t wBi = oB + (8 * (g >> 1) + (t >> 1)) * 128 + (((((g & 1) << 2) | (2 * (t & 1))) ^ ((t >> 1) | ((w & 1) << 2))) << 4);
    const int hC = (lane >> 3) & 1, pr = 8 * (w & 3) + (lane & 7), pc = hC ? (32 - pr) & 31 : pr;
    const uint32_t aC = hC * 16384 + (pc & 1) * 8192 + (pc >> 2) * 1024 + (((((pc & 2) << 1) | (lane >> 4)) ^ (((pc >> 2) & 3) << 1) ^ (pc & 1)) << 4);
    const uint32_t g0 = wb + (t >> 1) * 144 + (32 * (t & 1) + phi) * 2, g1 = wb + 18432 + (7 - (t >> 1)) * 144 + (64 - 32 * (t & 1) - phi) * 2;
    const uint32_t wAo = (8 * w + g) * 128 + (((2 * t) ^ g) << 4);
    uint32_t wph = 0;
#pragma unroll 1
    for (int k1 = grp; k1 < 129; k1 += 8, cnt++, wph ^= 1) {
        const uint32_t buf = gb + (cnt & 1) * 32768;
        uint4 in[2][4], m[4], out[4];
        m[0] = m[1] = m[2] = lds128u(tb + FT_A8 + lane * 16);
        m[3] = negfrag(m[0]);
        mbar_wait(mb + 8 * (cnt & 1), (cnt >> 1) & 1);
#pragma unroll
        for (int q = 0; q < 2; q++)
#pragma unroll
            for (int i = 0; i < 4; i++) in[q][i] = lds128u(buf + (rA ^ ((i & 1) * 0x90)) + (i >> 1) * 8192 + q * 16384);
        __syncwarp();
#pragma unroll
        for (int q = 0; q < 2; q++) {
            dft16<false>(out, in[q], m, m);
#pragma unroll
            for (int i = 0; i < 4; i++) sts128u(buf + (wA ^ (((i ^ (i >> 1)) & 1) << 4)) + (i >> 1) * 8192 + q * 16384, out[i]);
        }
        {
            uint4 tw[4];
#pragma unroll
            for (int i = 0; i < 4; i++) {
                m[i] = lds128u(tb + (faB ? FT_B1F : FT_F16) + i * 512 + lane * 16);
                if (hB) { m[i].y ^= 0x80008000u; m[i].w ^= 0x80008000u; }
                tw[i] = lds128u(tb + FT_TWB + (w >> 1) * 2048 + i * 512 + lane * 16);
            }
            bar_sync(bar, 256);
#pragma unroll
            for (int q = 0; q < 2; q++)
#pragma unroll
                for (int i = 0; i < 4; i++) in[q][i] = lds128u(buf + (rB ^ ((i & 1) << 6)) + (i >> 1) * 4096 + q * 256);
            __syncwarp();
#pragma unroll
            for (int q = 0; q < 2; q++) {
                dft16<true>(out, in[q], m, tw);
#pragma unroll
                for (int i = 0; i < 4; i++) sts128u(buf + (wB ^ ((i & 1) << 4)) + (i >> 1) * 4096 + q * 256, out[i]);
            }
        }
        {
            const uint32_t cjm = (g & 1) ? 0x8000u : 0x80000000u;
            float4 tw[4];
#pragma unroll
            for (int i = 0; i < 4; i++) { m[i] = lds128u(tb + FT_C + i * 512 + lane * 16); tw[i] = lds128(tb + FT_TWC + ((w & 3) * 4 + i) * 512 + lane * 16); }
            if (lead && k1 + 8 < 129) { bulk_wait_read(); MID_LOAD(k1 + 8, cnt + 1); }
            __syncwarp();
            mbar_wait(mb + 16, wph);
            const uint32_t o0 = (k1 & 7) * 2, o1 = (-k1 & 7) * 2;
            if (w == 1 && lane < 16) {
                const int k2 = lane & 7, k2p = k1 ? 7 - k2 : (8 - k2) & 7;
                const uint32_t p0 = wb + (lane >> 3) * 9216 + k2 * 1152 + o0, p1 = wb + 18432 + (lane >> 3) * 9216 + k2p * 1152 + o1;
                const float sg = lane < 8 ? 0.5f : -0.5f;
                const uint32_t v = pack_bf16(0.5f * ldw(p0) + sg * ldw(p1), 0.5f * ldw(p1 + 1136) + sg * ldw(p0 + 1136));
                asm volatile("st.shared.u16 [%0], %1;" ::"r"(p0), "h"((uint16_t)v) : "memory");
                asm volatile("st.shared.u16 [%0], %1;" ::"r"(p1 + 1136), "h"((uint16_t)(v >> 16)) : "memory");
                fence_async_smem();
            }
            bar_sync(bar, 256);
#define FFT_CU 1
            constexpr int CU = FFT_CU;
#pragma unroll CU
            for (int q = 0; q < 4; q++) {
                const int k2 = 4 * (w >> 2) + q, k2p = k1 ? 7 - k2 : (8 - k2) & 7, kr = hC ? k2p : k2;
                const uint32_t a0 = buf + (aC ^ ((kr & 1) << 4)) + kr * 128;
                const uint32_t r0 = g0 + k2 * 1152 + o0, r1 = g1 + k2p * 1152 + o1;
                uint32_t x[4], y[4];
                ldsm4(x, a0); ldsm4(y, a0 ^ 32);
                float c[4][4];
#pragma unroll
                for (int i = 0; i < 4; i++) { c[i][0] = c[i][1] = c[i][2] = c[i][3] = 0.f; mma16816(c[i], x[0], x[1], x[2], x[3], m[i].x, m[i].y); }
#pragma unroll
                for (int i = 0; i < 4; i++) mma16816(c[i], y[0], y[1], y[2], y[3], m[i].z, m[i].w);
#pragma unroll
                for (int i = 0; i < 4; i++) {
                    const float2 ga = make_float2(ldw(r0 + i * 288), ldw(r0 + 9216 + i * 288));
                    const float2 gc = make_float2(ldw(r1 - i * 288), ldw(r1 + 9216 - i * 288));
                    const float tc = tw[i].z, ts = tw[i].w;
                    const float* z = c[i];
                    const float2 S = make_float2(ga.x + gc.x, ga.y - gc.y), D = make_float2(ga.x - gc.x, ga.y + gc.y);
                    const float2 u = make_float2(ts * z[0] - tc * z[3], ts * z[1] + tc * z[2]), v = make_float2(ts * z[2] - tc * z[1], ts * z[3] + tc * z[0]);
                    uint32_t* o = (i < 2 ? x : y) + 2 * (i & 1);
                    o[0] = pack_bf16(fmaf(S.x, z[0], fmaf(-S.y, z[1], fmaf(D.x, u.x, -D.y * u.y))), fmaf(S.x, z[1], fmaf(S.y, z[0], fmaf(D.x, u.y, D.y * u.x))));
                    o[1] = pack_bf16(fmaf(S.x, z[2], fmaf(-S.y, z[3], fmaf(-D.x, v.x, D.y * v.y))), fmaf(S.x, z[3], fmaf(S.y, z[2], fmaf(-D.x, v.y, -D.y * v.x))));
                }
#pragma unroll
                for (int i = 0; i < 4; i++) { c[i][0] = c[i][1] = c[i][2] = c[i][3] = 0.f; mma16816(c[i], x[0], x[1], x[2], x[3], m[i].x ^ cjm, m[i].y ^ cjm); }
#pragma unroll
                for (int i = 0; i < 4; i++) mma16816(c[i], y[0], y[1], y[2], y[3], m[i].z ^ cjm, m[i].w ^ cjm);
#pragma unroll
                for (int i = 0; i < 4; i++) {
                    uint32_t* o = (i < 2 ? x : y) + 2 * (i & 1);
                    o[0] = pack_bf16(c[i][0] * tw[i].x + c[i][1] * tw[i].y, c[i][1] * tw[i].x - c[i][0] * tw[i].y);
                    o[1] = pack_bf16(c[i][2] * tw[i].x + c[i][3] * tw[i].y, c[i][2] * tw[i].y - c[i][3] * tw[i].x);
                }
                stsm4(a0, x[0], x[1], x[2], x[3]);
                stsm4(a0 ^ 32, y[0], y[1], y[2], y[3]);
            }
        }
#pragma unroll
        for (int i = 0; i < 4; i++) { m[i] = lds128u(tb + (faB ? FT_B1I : FT_F16) + i * 512 + lane * 16); if (!faB) m[i] = conjfrag(m[i]); }
        bar_sync(bar, 256);
        if (lead && k1 + 8 < 129) MID_LOADW(k1 + 8);
        __syncwarp();
#pragma unroll
        for (int q = 0; q < 2; q++)
#pragma unroll
            for (int i = 0; i < 4; i++) in[q][i] = lds128u(buf + (rB ^ ((i & 1) << 6)) + (i >> 1) * 4096 + q * 256);
        __syncwarp();
#pragma unroll
        for (int q = 0; q < 2; q++) {
            dft16<false>(out, in[q], m, m);
#pragma unroll
            for (int i = 0; i < 4; i++) sts128u(buf + (wBi ^ ((i & 1) << 4) ^ (q << 5)) + (i >> 1) * 4096 + q * 256, out[i]);
        }
        m[0] = m[1] = m[2] = conjfrag(lds128u(tb + FT_A8 + lane * 16));
        m[3] = negfrag(m[0]);
        bar_sync(bar, 256);
#pragma unroll
        for (int q = 0; q < 2; q++)
#pragma unroll
            for (int i = 0; i < 4; i++) in[q][i] = lds128u(buf + (rA ^ ((i & 1) * 0x90)) + (i >> 1) * 8192 + q * 16384);
        __syncwarp();
#pragma unroll
        for (int q = 0; q < 2; q++) {
            dft16<false>(out, in[q], m, m);
#pragma unroll
            for (int i = 0; i < 4; i++) sts128u(buf + (wAo ^ ((i & 1) << 4)) + (i >> 1) * 8192 + q * 16384, out[i]);
        }
        fence_async_smem();
        bar_sync(bar, 256);
        if (lead) {
            tma_st3(buf, &fm.y2, 0, k1 * 8);
            if (k1 & 127) tma_st3(buf + 16384, &fm.y2, 0, (256 - k1) * 8);
            bulk_commit();
        }
    }
    if (lead) bulk_wait_all();
}

__device__ __align__(128) unsigned g_start;
__device__ __align__(128) unsigned g_fbar;
__device__ __align__(128) unsigned g_end;
__device__ __forceinline__ unsigned gbar_arrive(unsigned* c, unsigned inc, unsigned total, int lane) {
    unsigned v = 0;
    if (lane == 0) { asm volatile("fence.proxy.async;" ::: "memory"); fence_gpu(); v = atomicAdd(c, inc); }
    return (__shfl_sync(~0u, v, 0) & ~(total - 1)) + total;
}
__device__ __forceinline__ void gbar_wait(unsigned* c, unsigned target, unsigned ns) {
    uint32_t n = 0;
    while (__any_sync(~0u, (int)(ld_acquire(c) - target) < 0)) { if (ns) __nanosleep(ns); if (++n > SPIN_LIMIT) __trap(); }
    asm volatile("fence.proxy.async;" ::: "memory");
}
__device__ __forceinline__ void fft_rest(int cta, const FftMaps& fm, uint32_t sb, bool skip) {
    const int hi = __shfl_sync(~0u, threadIdx.x >> 8, 0), w = __shfl_sync(~0u, (threadIdx.x >> 5) & 7, 0), lane = threadIdx.x & 31;
    unsigned target = 0;
    if (w == 4) target = gbar_arrive(&g_start, 16, 256, lane);
    if (threadIdx.x < 32) mbar_init(sb + FT_BAR + 8 * threadIdx.x, 1);
    fft_tables(sb, threadIdx.x, 512);
    fence_async_smem();
    __syncthreads();
    const int grp = cta * 2 + hi, bar = 1 + hi;
    const uint32_t gb = sb + hi * FG_SIZE, mb = sb + FT_BAR + hi * 128;
    uint32_t cnt = 0;
    if (w == 4) gbar_wait(&g_start, target, 200);
    GT(1);
    fft_mid(grp, fm, sb, gb, mb, cnt, w, lane, bar);
    if (w == 4) gbar_wait(&g_fbar, gbar_arrive(&g_fbar, 1, 8, lane), 200);
    GT(2);
    fft_col<true, 16>(grp, 0, &fm.y, &fm.o, gb, mb + 64, w, lane, bar);
}

__device__ __align__(256) uint4 g_kvq[4 * 32 * 3 * 8 * 2 * 32];
__device__ __align__(256) uint2 g_alpha[2 * 32 * 3 * 8 * 2 * 32];
__device__ __align__(256) uint4 g_red[5 * 32768 / 16];
__device__ __align__(256) uint4 g_stamp[32];
__device__ __align__(256) uint4 g_qst[128 * 2];
__device__ __align__(256) bf16 g_ox[2048 * 4096];
struct Tune { uint32_t d_alpha, d_r, opt, d_q, d_v, spread, extra; };
#define OP_SPLIT 1
#define X_SEQ 24
#define OPD_EARLY 0
constexpr int RA = 2;

constexpr uint32_t SM_BASE = 1024;
constexpr uint32_t O_WO = 0;
constexpr uint32_t O_WV = 65536;
constexpr uint32_t O_XB = 131072;
constexpr uint32_t O_MEM = O_XB + 32768;
constexpr uint32_t O_RECV = O_MEM + 8192;
constexpr uint32_t O_KVQ = O_RECV + 12288;
constexpr uint32_t O_STG = O_KVQ + 18432;
constexpr uint32_t O_S = O_STG + 8192;
constexpr uint32_t O_XO = O_STG + 16384;
constexpr uint32_t O_P = O_S + 10240;
constexpr uint32_t O_O = O_P + 1536;
constexpr uint32_t O_DBG = O_O + 2048;
constexpr uint32_t O_F1 = 196608;
constexpr uint32_t O_VM = O_F1 + 32768;
constexpr uint32_t O_BAR = 232448 - 512;
constexpr uint32_t MAIN_SMEM = 232448;
static_assert(O_DBG + (DBG_TIMING ? (4 * DBG_N + 1) * 96 : 0) <= O_VM && FFT_SMEM <= MAIN_SMEM && O_VM + 2048 <= O_BAR, "smem");
constexpr int G_ST = 6;
enum { B_W = 0, B_WO = B_W + 12, B_F1, B_XP, B_XFULL, B_RFULL, B_AFULL, B_KVFULL, B_QST, B_RECV, B_GF = B_RECV + 6,
       B_QDONE = B_GF + G_ST, B_KDONE, B_XEMPTY, B_SDONE, B_SRDY, B_OPDONE, B_QX, B_GE, B_XPE = B_GE + G_ST, B_QKW, B_MEM, B_COUNT };

constexpr float SM_SCALE_LOG2 = 0.08838834764831845f * 1.4426950408889634f;
constexpr float MASK_VAL = -1.0e9f / 0.08838834764831845f;

__device__ __forceinline__ uint32_t red_grp(int grp) { return (uint32_t)((grp >> 1) * 1024 + (grp & 1) * 256); }
__host__ __device__ constexpr uint64_t xdesc(int ks) { return mkdesc(SM_BASE + O_XB + (ks >> 2) * 1024 + (ks & 3) * 32, 16, 8192, 1); }

__device__ __forceinline__ void x_split(const float* d, uint32_t (&sn)[4], uint32_t (&kp)[4], int kh) {
#pragma unroll
    for (int i = 0; i < 4; i++) {
        const uint32_t lo = pack_bf16(d[2 * i], d[2 * i + 1]), hi = pack_bf16(d[8 + 2 * i], d[8 + 2 * i + 1]);
        sn[i] = kh ? lo : hi; kp[i] = kh ? hi : lo;
    }
}
__device__ __forceinline__ void x_send(int R, const uint32_t (&sn)[4], int sg, int tid, uint32_t sb, uint32_t mate) {
    const uint32_t par = sg & 1;
    const uint32_t bar = O_BAR + 8 * (B_RECV + R * 2) + 8 * par;
    if (tid == 0) mbar_expect_tx(sb + bar, 2048);
    asm volatile("st.async.shared::cluster.mbarrier::complete_tx::bytes.v4.b32 [%0], {%1,%2,%3,%4}, [%5];"
                 ::"r"(mate + O_RECV + (par * 3 + R) * 2048 + tid * 16), "r"(sn[0]), "r"(sn[1]), "r"(sn[2]), "r"(sn[3]), "r"(mate + bar) : "memory");
}
__device__ __forceinline__ void x_wait(int R, int sg, uint32_t sb) {
    mbar_wait_cluster(sb + O_BAR + 8 * (B_RECV + R * 2) + 8 * (sg & 1), (sg >> 1) & 1);
}
template <int R>
__device__ __forceinline__ void x_finish(const uint32_t (&kp)[4], int sg, int h, int mt, int kh, int tid, uint32_t sb) {
    const uint4 r = lds128u(sb + O_RECV + ((sg & 1) * 3 + R) * 2048 + tid * 16);
    uint32_t u0 = add_bf16x2(kp[0], r.x), u1 = add_bf16x2(kp[1], r.y), u2 = add_bf16x2(kp[2], r.z), u3 = add_bf16x2(kp[3], r.w);
    if (R < 2) { u0 = movm(u0); u1 = movm(u1); u2 = movm(u2); u3 = movm(u3); }
    const uint32_t tag = ((sg >> 2) & 1) ^ 1;
    u0 = (u0 & ~1u) | tag;
    uint4* const hb = &g_kvq[((sg & 3) * 32 + h) * (3 * 512)];
    if (R == 0) {
        uint2* p = (uint2*)hb + (kh * 16 + mt) * 32 + (tid & 31);
        asm volatile("{\n.reg .pred p;\nsetp.lt.s32 p, %5, 64;\n@p st.relaxed.gpu.global.v2.b32 [%0], {%1,%2};\n@p st.relaxed.gpu.global.v2.b32 [%0+2048], {%3,%4};\n}"
                     ::"l"(p), "r"(u0), "r"(u1), "r"((u2 & ~1u) | tag), "r"(u3), "r"(sg) : "memory");
    } else {
        asm volatile("{\n.reg .pred p;\nsetp.lt.s32 p, %5, 64;\n@p st.relaxed.gpu.global.v4.b32 [%0], {%1,%2,%3,%4};\n}"
                     ::"l"(hb + R * 512 + (mt * 2 + kh) * 32 + (tid & 31)), "r"(u0), "r"(u1), "r"(u2), "r"(u3), "r"(sg) : "memory");
    }
}

__device__ __forceinline__ uint32_t convert_mem(const unsigned char* redp, int s, int kh, int jj, int w, int lane, uint32_t sb, uint32_t& sf) {
    const uint32_t off = red_grp(jj * 16 + w * 4 + (lane >> 3)), o16 = off + (lane & 7) * 16, o8 = off + 512 + ((lane >> 3) & 1) * 64 + (lane & 7) * 8;
    uint32_t ma = sb + O_MEM + (jj * 4 + (lane >> 4)) * 1024 + (lane & 7) * 128 + (((2 * w + ((lane >> 3) & 1)) ^ (lane & 7)) << 4);
    uint32_t a16 = sb + O_STG + o16, a8 = sb + O_STG + o8;
    const uint32_t target = (s & 4) ? 0x42C00000u : 0x42000000u;
    uint32_t n = 0;
    bool redo;
    KEEP2(ma, a16); KEEP2(a8, target);
#pragma unroll 1
    do {
        asm volatile("" : "+r"(n));
        if (n) {
            const unsigned char* pg = redp + (s & 3) * 32768 + kh * 16384;
            const uint4 x = ldg_rlx128(pg + o16), y = ldg_rlx128(pg + o16 + 128);
            const uint2 z = ldg_rlx64(pg + o8);
            sts128u(a16, x); sts128u(a16 + 128, y); sts64u(a8, z);
            if (n > SPIN_LIMIT) __trap();
        }
        n++;
        mbar_wait(sb + O_BAR + 8 * B_RFULL, s & 1);
        const uint4 ra = lds128u(a16), rb = lds128u(a16 + 128);
        const uint2 rc = lds64u(a8);
        stsm4t(ma, ra.x, ra.y, ra.z, __byte_perm(ra.w, rc.x, 0x5410));
        stsm4t(ma + 2048, rb.x, rb.y, rb.z, __byte_perm(rb.w, rc.x, 0x7610));
        redo = __any_sync(~0u, orx(orx2(ra.w, rb.w, target), rc.y, target) > 0xffffu);
    } while (redo);
    if (lane == 0) mbar_arrive(sb + O_BAR + 8 * B_MEM);
    fence_async_smem();
    __syncwarp();
    if (lane == 0) mbar_arrive(sb + O_BAR + 8 * B_QKW);
    return n - 1;
}

#define F16(d, o) F4(d, o), F4(d, o + 4), F4(d, o + 8), F4(d, o + 12)
__device__ __forceinline__ void wg_ss128(float (&d)[64], uint64_t da, uint64_t db, int sc) {
    asm volatile("{\n.reg .pred p;\nsetp.ne.b32 p, %66, 0;\nwgmma.mma_async.sync.aligned.m64n128k16.f32.bf16.bf16 "
                 "{%0,%1,%2,%3,%4,%5,%6,%7,%8,%9,%10,%11,%12,%13,%14,%15,%16,%17,%18,%19,%20,%21,%22,%23,%24,%25,%26,%27,%28,%29,%30,%31,"
                 "%32,%33,%34,%35,%36,%37,%38,%39,%40,%41,%42,%43,%44,%45,%46,%47,%48,%49,%50,%51,%52,%53,%54,%55,%56,%57,%58,%59,%60,%61,%62,%63}, "
                 "%64, %65, p, 1, 1, 0, 1;\n}"
                 : F16(d, 0), F16(d, 16), F16(d, 32), F16(d, 48) : "l"(da), "l"(db), "r"(sc));
}
__device__ __forceinline__ void stg_rlx32(void* p, uint32_t v) { asm volatile("st.relaxed.gpu.global.u32 [%0], %1;" ::"l"(p), "r"(v) : "memory"); }

__global__ void __cluster_dims__(2, 1, 1) __launch_bounds__(512, 1)
rmt_main(const __grid_constant__ CUtensorMap tm_x, const __grid_constant__ CUtensorMap tm_wq, const __grid_constant__ CUtensorMap tm_wk,
         const __grid_constant__ CUtensorMap tm_wv, const __grid_constant__ CUtensorMap tm_wo, const bf16* __restrict__ mem0,
         const Tune tn, const __grid_constant__ FftMaps fm, const __grid_constant__ CUtensorMap tm_o,
         const __grid_constant__ CUtensorMap tm_w2, bf16* __restrict__ out) {
    extern __shared__ __align__(1024) unsigned char smem_raw[];
    const uint32_t sb = smem_u32(smem_raw);
    if ((sb & 0x3FFFF) != SM_BASE) __trap();
    GT(6);
    const int cid = blockIdx.x >> 1, kh = blockIdx.x & 1;
    const int tpc = cid < 4 ? 62 + cid : cid - 4;
    int h, nh;
    if (tpc < 32) { h = (tpc >> 4) * 8 + (tpc & 7); nh = (tpc >> 3) & 1; }
    else if (tpc < 60) { int u = tpc - 32, r = u % 14; h = 16 + (u / 14) * 7 + r % 7; nh = r / 7; }
    else if (tpc < 62) { GT(0); fft_rest((tpc - 60) * 2 + kh, fm, sb, tn.opt & 8); GT(3); return; }
    else { h = 30 + ((tpc - 62) >> 1); nh = tpc & 1; }
    const int j = nh * 2 + kh, role = h * 4 + j;
    const int wgi = __shfl_sync(~0u, threadIdx.x >> 7, 0);
    const int w = __shfl_sync(~0u, (threadIdx.x >> 5) & 3, 0);
    const int tid = threadIdx.x & 127, lane = tid & 31;
#define PIN_IDS() const int tid = __shfl_sync(~0u, threadIdx.x & 127, threadIdx.x & 31), lane = tid & 31
#define OPAQUE_IDS() int tid_ = tid; asm volatile("" : "+r"(tid_)); const int tid = tid_, lane = tid_ & 31; (void)lane
    unsigned char* const redp = (unsigned char*)(((uintptr_t)g_red + 32767) & ~(uintptr_t)32767);
    const uint32_t bars = sb + O_BAR;

    if (threadIdx.x < B_COUNT) {
        const int i = threadIdx.x;
        mbar_init(bars + 8 * i, i < B_QDONE ? 1 : i < B_GE ? 4 : i < B_XPE ? 8 : i < B_QKW ? 12 : 16);
        asm volatile("fence.mbarrier_init.release.cluster;" ::: "memory");
        fence_async_smem();
    } else if (threadIdx.x >= 64 && threadIdx.x < 71) {
        const int i = threadIdx.x - 64;
        const CUtensorMap* m = i == 0 ? &tm_wk : i == 1 ? &tm_wq : i == 2 ? &fm.x : i == 3 ? &tm_x : i == 4 ? &tm_wv : i == 5 ? &tm_wo : &fm.y;
        asm volatile("prefetch.tensormap [%0];" ::"l"(m) : "memory");
    }
    __syncthreads();
    const int wc0 = h * 128 + nh * 64;
#define W_LOAD(i)                                                                                                     \
    if (lane == 0) {                                                                                                  \
        mbar_expect_tx(bars + 8 * (B_W + (i)), 16384);                                                                \
        tma2d(sb + ((i) < 4 ? O_XB : (i) < 8 ? O_WO : O_WV) + ((i) & 3) * 16384, (i) < 4 ? &tm_wk : (i) < 8 ? &tm_wq : &tm_wv, \
              wc0, kh * 512 + ((i) & 3) * 128, bars + 8 * (B_W + (i)));                                               \
    }
    const int depth = (tn.opt >> 8) & 15, nearly = 8 + ((tn.opt >> 4) & 7);
    if (wgi == 0 && w == 3) {
        if (lane == 0) {
            mbar_expect_tx(bars + 8 * B_F1, 32768);
            tma_ld4(sb + O_F1, &fm.x, (role & 15) * 64, role >> 4, bars + 8 * B_F1);
        }
#pragma unroll 1
        for (int i = 0; i < nearly; i++) {
            if (i == depth - 2) mbar_wait(bars + 8 * B_F1, 0);
            if (i >= depth) mbar_wait(bars + 8 * (B_W + i - depth), 0);
            W_LOAD(i);
        }
    } else if (wgi == 1 && w == 2 && lane == 0 && role < 2 * (RA + 3)) tma4d_prefetch(&tm_x, kh * 8, (role >> 1) * 4);
    GT(7);
    uint32_t mate;
    asm volatile("mapa.shared::cluster.u32 %0, %1, %2;" : "=r"(mate) : "r"(sb), "r"(kh ^ 1));
    if (wgi >= 2) fft_col<false, 1>(role >> 4, role & 15, &fm.x, &fm.y, sb + O_F1, bars + 8 * B_F1, (wgi - 2) * 4 + w, lane, 6);

    if (wgi < 2) {
        asm volatile("setmaxnreg.inc.sync.aligned.u32 176;");
        PIN_IDS();
        uint32_t a[32][4], sf = 0;
        {
            const uint32_t stage = sb + (wgi == 0 ? O_WO : O_XB);
            const uint32_t ad = stage + (((lane >> 4) & 1) * 8 + (lane & 7)) * 128 + (((2 * w + ((lane >> 3) & 1)) ^ (lane & 7)) << 4);
#pragma unroll
            for (int i = 0; i < 4; i++) {
                mbar_wait(bars + 8 * (B_W + 4 * (wgi ^ 1) + i), 0);
#pragma unroll
                for (int ks = 0; ks < 8; ks++) ldsm4t(a[i * 8 + ks], ad + (i * 8 + ks) * 2048);
            }
#pragma unroll
            for (int ks = 0; ks < 32; ks += 2) KEEP2(a[ks][0], a[ks + 1][0]);
            SCHED_FENCE();
            if (lane == 0) mbar_arrive(bars + 8 * (B_QDONE + wgi));
            if (wgi == 0) GT(10); else GT(11);
        }
        asm volatile("barrier.cluster.arrive.relaxed.aligned;" ::: "memory");
        asm volatile("barrier.cluster.wait.acquire.aligned;" ::: "memory");
        uint32_t kp[4];
#define X_PASS(d, dofs)                                                                                    \
        wg_fence();                                                                                        \
        _Pragma("unroll") for (int ks = 0; ks < 32; ks++) { if (ks == 0) wg_rs32<0>(d, a[ks], xdesc(ks) + (dofs)); else wg_rs32<1>(d, a[ks], xdesc(ks) + (dofs)); } \
        wg_commit();                                                                                       \
        wg_wait<0>();
#define X_FINISH(sg) { if (wgi == 0) x_finish<0>(kp, sg, h, nh * 4 + w, kh, tid, sb); else x_finish<1>(kp, sg, h, nh * 4 + w, kh, tid, sb); }
        mbar_wait(bars + 8 * B_XP, 0);
        if (wgi == 0) GT(8);
#pragma unroll 1
        for (int sg = 0; sg < RA; sg++) {
            float d[16]; uint32_t sn[4];
            X_PASS(d, sg * 2048 - (int)((O_XB - O_WO) >> 4));
            if (sg > 0) {
                if (lane == 0) mbar_arrive(bars + 8 * B_XPE);
                x_wait(wgi, sg - 1, sb); X_FINISH(sg - 1);
            }
            x_split(d, sn, kp, kh);
            x_send(wgi, sn, sg, tid, sb, mate);
        }
        const int lq = wgi == 0 ? 4 : 0;
#pragma unroll 1
        for (int s = 0; s < 64; s++) {
            TSI(s);
            {
                float d[16]; uint32_t sn[4], kc[4];
                x_wait(wgi, s + RA - 1, sb);
                mbar_wait(bars + 8 * B_XFULL, s & 1);
                if (wgi == 1) {
                    mbar_wait(bars + 8 * B_OPDONE, s & 1);
                    x_finish<1>(kp, s + RA - 1, h, nh * 4 + w, kh, tid, sb);
                    TS(5);
                    mbar_wait(bars + 8 * B_QX, s & 1);
                } else mbar_wait(bars + 8 * B_OPDONE, s & 1);
                TS(6);
                wg_fence();
#pragma unroll
                for (int ks = 0; ks < 32; ks++) {
                    if (ks == 0) wg_rs32<0>(d, a[ks], xdesc(ks)); else wg_rs32<1>(d, a[ks], xdesc(ks));
                    if (ks == X_SEQ - 1) wg_commit();
                }
                wg_commit();
                wg_wait<1>();
                if (tid < lq) mbar_arrive(bars + 8 * B_QX);
                wg_wait<0>();
                TS(7);
                x_split(d, sn, kc, kh);
                x_send(wgi, sn, s + RA, tid, sb, mate);
                TS(4);
                if (wgi == 0) { x_finish<0>(kp, s + RA - 1, h, nh * 4 + w, kh, tid, sb); TS(5); }
#pragma unroll
                for (int i = 0; i < 4; i++) kp[i] = kc[i];
            }
            uint2* ap = &g_alpha[((s & 1) * 32 + h) * (3 * 512) + wgi * 512 + ((nh * 4 + w) * 2 + kh) * 32 + lane];
            uint32_t mb0 = sb + O_MEM + (lane & 7) * 128 + (((lane >> 3) ^ (lane & 7)) << 4), mb1 = mb0 ^ 64;
            const uint32_t tag = ((s >> 1) & 1) ^ 1;
            KEEP2(mb0, mb1); KEEPP(ap);
            float e[2][4];
#pragma unroll
            for (int i = 0; i < 4; i++) e[0][i] = e[1][i] = 0.f;
            if (lane == 0) mbar_arrive(bars + 8 * B_MEM);
            mbar_wait(bars + 8 * B_MEM, s & 1);
            TS(0);
#pragma unroll
            for (int ks = 0; ks < 32; ks += 2) {
                uint32_t b[4];
                ldsm4(b, ((ks & 2) ? mb1 : mb0) + (ks >> 2) * 1024);
                mma16816(e[0], a[ks][0], a[ks][1], a[ks][2], a[ks][3], b[0], b[1]);
                mma16816(e[1], a[ks + 1][0], a[ks + 1][1], a[ks + 1][2], a[ks + 1][3], b[2], b[3]);
            }
            TS(2);
            uint32_t u0 = pack_bf16(e[0][0] + e[1][0], e[0][1] + e[1][1]), u1 = pack_bf16(e[0][2] + e[1][2], e[0][3] + e[1][3]);
            u0 = movm(u0); u1 = movm(u1);
            SCHED_FENCE();
            if (lane == 0) mbar_arrive(bars + 8 * B_QKW);
            stg_rlx64(ap, (u0 & ~1u) | tag, u1);
            TS(3);
            if (wgi == 1) {
                const uint2* vp = &g_alpha[((s & 1) * 32 + h) * (3 * 512) + 1024 + w * 128 + lane];
                const uint32_t vs = sb + O_VM + tid * 16;
                KEEPP(vp); KEEP2(vs, 0);
                mbar_wait(bars + 8 * B_QST, s & 1);
                uint32_t n, bad;
                asm volatile("ld.shared.u32 %0, [%1];" : "=r"(n) : "r"(bars + 504) : "memory");
                wait_gtime(n + tn.d_v);
                TS(8);
                n = 0;
                do {
                    uint2 va[4];
#pragma unroll
                    for (int i = 0; i < 4; i++) va[i] = ldg_rlx64(vp + i * 32);
                    if (++n > SPIN_LIMIT) __trap();
                    bad = (orx2(va[0].x, va[1].x, tag) | orx2(va[2].x, va[3].x, tag)) & 1;
                    sts128u(vs, make_uint4((add_bf16x2(va[0].x, va[1].x) & ~1u) | ((~s ^ bad) & 1), add_bf16x2(va[0].y, va[1].y),
                                                             add_bf16x2(va[2].x, va[3].x), add_bf16x2(va[2].y, va[3].y)));
                } while (__any_sync(~0u, bad));
                TS(9);
                TSV(16 + w, n - 1);
                LT(s, 4 + w, n - 1);
            }
        }
        x_wait(wgi, 63 + RA, sb);
        sts32(bars + 508, sf);
        TSDUMP();
        asm volatile("bar.arrive 7, 512;" ::: "memory");
        float d[64];
        int st = 0, ph = 0;
#pragma unroll 1
        for (int kt = 0; kt < 64; kt++) {
            mbar_wait(bars + 8 * (B_GF + st), ph);
            if (kt == 0) GT(4);
            const uint64_t da = mkdesc(SM_BASE + st * 32768 + wgi * 8192, 16, 1024, 1), db = mkdesc(SM_BASE + st * 32768 + 16384, 8192, 1024, 1);
            wg_fence();
#pragma unroll
            for (int k = 0; k < 4; k++) wg_ss128(d, da + k * 2, db + k * 128, kt | k);
            wg_commit();
            if (kt > 0) {
                wg_wait<1>();
                if (lane == 0) mbar_arrive(bars + 8 * (B_GE + (st == 0 ? G_ST - 1 : st - 1)));
            }
            if (++st == G_ST) { st = 0; ph ^= 1; }
        }
        wg_wait<0>();
        {
            const uint32_t sl = sb + O_F1 + (wgi * 4 + w) * 4096;
#pragma unroll
            for (int i = 0; i < 8; i++)
                stsm4(sl + (lane & 15) * 256 + (((2 * i + (lane >> 4)) ^ (lane & 7)) << 4), pack_bf16(d[8 * i], d[8 * i + 1]),
                      pack_bf16(d[8 * i + 2], d[8 * i + 3]), pack_bf16(d[8 * i + 4], d[8 * i + 5]), pack_bf16(d[8 * i + 6], d[8 * i + 7]));
            __syncwarp();
            bf16* op = out + (size_t)((role >> 3) * 128 + wgi * 64 + w * 16 + (lane >> 4)) * 2048 + 1024 + (role & 7) * 128 + (lane & 15) * 8;
#pragma unroll
            for (int i = 0; i < 8; i++) {
                const int r = 2 * i + (lane >> 4);
                const uint4 v = lds128u(sl + r * 256 + (((lane & 15) ^ (r & 7)) << 4));
                stg128(op + (size_t)i * 4096, v.x, v.y, v.z, v.w);
            }
        }
        GT(5);
    } else if (wgi == 2) {
        asm volatile("setmaxnreg.dec.sync.aligned.u32 64;");
        PIN_IDS();
        asm volatile("barrier.cluster.arrive.relaxed.aligned;" ::: "memory");
#define X_LOAD(dst, sg, bar) tma4d(sb + (dst), &tm_x, kh * 8, ((sg) & 63) * 4, bars + 8 * (bar))
        if (w == 0) {
            mbar_wait(bars + 8 * B_KDONE, 0);
            if (lane == 0) { mbar_expect_tx(bars + 8 * B_XFULL, 32768); X_LOAD(O_XB, RA, B_XFULL); }
            mbar_wait(bars + 8 * B_QDONE, 0);
            if (lane == 0) { mbar_expect_tx(bars + 8 * B_XP, 65536); X_LOAD(O_WO, 0, B_XP); X_LOAD(O_WO + 32768, 1, B_XP); }
#pragma unroll 1
            for (int i = nearly; i < 12; i++) { mbar_wait(bars + 8 * (B_W + i - depth), 0); W_LOAD(i); }
        }
        asm volatile("barrier.cluster.wait.acquire.aligned;" ::: "memory");
#pragma unroll 1
        for (int i = 8; i < 12; i++) mbar_wait(bars + 8 * (B_W + i), 0);
        GT(12);
        uint32_t sf = 0, tref = gtime() - 4000;
#define V_PASS(d, dofs)                                                                                    \
        wg_fence();                                                                                        \
        _Pragma("unroll") for (int ks = 0; ks < 32; ks++) {                                                \
            constexpr uint64_t da0 = mkdesc(SM_BASE + O_WV, 16, 1024, 1);                                  \
            if (ks == 0) wg_ss40<0>(d, da0 + ks * 128, xdesc(ks) + (dofs)); else wg_ss40<1>(d, da0 + ks * 128, xdesc(ks) + (dofs)); \
        }                                                                                                  \
        wg_commit();                                                                                       \
        wg_wait<0>();
        mbar_wait(bars + 8 * B_XP, 0);
        {
            uint32_t kp[4];
#pragma unroll 1
            for (int sg = 0; sg <= RA; sg++) {
                float d[20]; uint32_t sn[4];
                if (sg < RA) {
#pragma unroll
                    for (int i = 0; i < 20; i++) d[i] = 0.f;
#pragma unroll 1
                    for (int kb = 0; kb < 8; kb++) {
                        const uint64_t da = mkdesc(SM_BASE + O_WV, 16, 1024, 1) + kb * 512, db = mkdesc(SM_BASE + O_WO, 16, 8192, 1) + sg * 2048 + kb * 64;
                        wg_fence();
#pragma unroll
                        for (int i = 0; i < 4; i++) wg_ss40<1>(d, da + i * 128, db + i * 2);
                        wg_commit();
                    }
                    wg_wait<0>();
                }
                if (sg == RA - 1) {
                    if (lane == 0) mbar_arrive(bars + 8 * B_XPE);
                    if (w == 0) {
                        mbar_wait(bars + 8 * B_XPE, 0);
                        GT(9);
                        if (lane == 0) {
                            mbar_expect_tx(bars + 8 * B_WO, 65536);
#pragma unroll
                            for (int i = 0; i < 4; i++) tma2d(sb + O_WO + i * 16384, &tm_wo, j * 256 + i * 64, h * 128, bars + 8 * B_WO);
                        }
                    }
                }
                if (sg > 0) { x_wait(2, sg - 1, sb); x_finish<2>(kp, sg - 1, h, nh * 4 + w, kh, tid, sb); }
                if (sg < RA) { x_split(d, sn, kp, kh); x_send(2, sn, sg, tid, sb, mate); }
            }
        }
#pragma unroll 1
        for (int s = 0; s < 64; s++) {
            TSI(s);
            OPAQUE_IDS();
            uint2* ap = &g_alpha[((s & 1) * 32 + h) * (3 * 512) + 1024 + ((nh * 4 + w) * 2 + kh) * 32 + lane];
            KEEPP(ap);
            float d[20];
            mbar_wait(bars + 8 * B_QKW, s & 1);
            TS(0);
            if (s == 0) GT(14);
            V_PASS(d, 0);
            TS(1);
            stg_rlx64(ap, (pack_bf16(d[16], d[17]) & ~1u) | (((s >> 1) & 1) ^ 1), pack_bf16(d[18], d[19]));
            if (lane == 0) mbar_arrive(bars + 8 * B_XEMPTY);
            if (s == 63) break;
            uint32_t sn[4], kp[4];
            x_split(d, sn, kp, kh);
            if (w == 3) {
                uint32_t n = 0, mx, mn;
                do {
                    const uint4 st = ldg_rlx128(&g_stamp[lane]);
                    mx = __reduce_max_sync(~0u, max(max(st.x - tref, st.y - tref), max(st.z - tref, st.w - tref)));
                    mn = __reduce_min_sync(~0u, min(min(st.x - tref, st.y - tref), min(st.z - tref, st.w - tref)));
                } while (mx >= 200000u && ++n < 64);
                tref = mx < 200000u ? tref + mx + (mx - mn > tn.spread ? tn.extra : 1) : gtime();
                TSV(12, clk()); TSV(13, n); TSV(14, mx - mn);
            }
            if (tn.opt & 1) { mbar_wait(bars + 8 * B_SDONE, s & 1); x_send(2, sn, s + RA, tid, sb, mate); }
            if (w == 0) {
                mbar_wait(bars + 8 * B_XEMPTY, s & 1);
                mbar_wait(bars + 8 * ((tn.opt & 2) ? B_SRDY : B_SDONE), s & 1);
                if (lane == 0) {
                    mbar_expect_tx(bars + 8 * B_XFULL, 32768);
                    X_LOAD(O_XB, s + RA + 1, B_XFULL);
                }
                mbar_wait(bars + 8 * B_SRDY, s & 1);
                if (lane == 0) {
                    const uint4* hb = &g_kvq[(((s + 1) & 3) * 32 + h) * (3 * 512)];
                    mbar_expect_tx(bars + 8 * B_KVFULL, 18432);
                    bulk_g2s(sb + O_KVQ, hb + 512, 16384, bars + 8 * B_KVFULL);
                    bulk_g2s(sb + O_KVQ + 16384, hb + j * 128, 2048, bars + 8 * B_KVFULL);
                    if (nh == 0 && ((h ^ s) & 7) == 0 && s < 61 - RA) tma4d_prefetch(&tm_x, kh * 8, (s + RA + 3) * 4);
                }
            }
            mbar_wait(bars + 8 * B_OPDONE, (s + 1) & 1);
            if (!(tn.opt & 1)) x_send(2, sn, s + RA, tid, sb, mate);
            if (w == 3) {
                wait_gtime(tref + tn.d_r);
                if (lane == 0) {
                    mbar_expect_tx(bars + 8 * B_RFULL, 16384);
                    bulk_g2s(sb + O_STG, redp + (s & 3) * 32768 + kh * 16384, 16384, bars + 8 * B_RFULL);
                }
                TSV(3, clk());
            }
            x_wait(2, s + RA, sb);
            const bool late = w == 3 || (tn.opt & 4);
            if (!late) { x_finish<2>(kp, s + RA, h, nh * 4 + w, kh, tid, sb); TS(6); }
            if (DBG_TIMING && w == 0) { mbar_wait(bars + 8 * B_RFULL, s & 1); TS(4); }
            const uint32_t n = convert_mem(redp, s, kh, 0, w, lane, sb, sf); (void)n;
            TS(5);
            TSV(8 + w, n);
            LT(s, 8 + w, n);
            if (late) x_finish<2>(kp, s + RA, h, nh * 4 + w, kh, tid, sb);
        }
        sts32(bars + 508, sf);
        TSDUMP();
        asm volatile("bar.arrive 7, 512;" ::: "memory");
    } else {
        asm volatile("setmaxnreg.dec.sync.aligned.u32 96;");
        PIN_IDS();
        GT(0);
        asm volatile("barrier.cluster.arrive.relaxed.aligned;" ::: "memory");
#define RED_CLEAR(st)                                                                                           \
        if (lane < 16) {                                                                                        \
            const uint32_t cb = ((st) & 4) ? 0x42800000u : 0u;                                                  \
            stg128(redp + ((st) & 3) * 32768 + role * 256 + lane * 16, 0, (role & 2) ? cb : 0u, 0, cb);        \
        }
        if (w == 0) {
            RED_CLEAR(0); RED_CLEAR(1); RED_CLEAR(2);
            if (lane == 0) { tma_st4(sb + O_F1, &fm.y, (role & 15) * 64, role >> 4); bulk_commit(); }
        }
        sts128u(sb + O_VM + tid * 16, make_uint4(0, 0, 0, 0));
        {
            uint4 v[4];
#pragma unroll
            for (int q = 0; q < 4; q++) v[q] = *(const uint4*)(mem0 + ((lane >> 3) + (q & 1) * 4) * 1024 + kh * 512 + (2 * w + (q >> 1)) * 64 + (lane & 7) * 8);
            mbar_wait(bars + 8 * B_KDONE, 0);
#pragma unroll
            for (int q = 0; q < 4; q++) {
                const int row = (lane >> 3) + (q & 1) * 4;
                sts128u(sb + O_MEM + (2 * w + (q >> 1)) * 1024 + row * 128 + (((lane & 7) ^ row) << 4), v[q]);
            }
            fence_async_smem();
            __syncwarp();
            if (lane < 2) { mbar_arrive(bars + 8 * B_MEM); mbar_arrive(bars + 8 * B_QKW); }
            if (lane == 0) mbar_arrive(bars + 8 * B_OPDONE);
            if (tid == 0) mbar_arrive(bars + 8 * B_KVFULL);
        }
        asm volatile("barrier.cluster.wait.acquire.aligned;" ::: "memory");
        if (w == 0) {
            if (lane == 0) bulk_wait_all();
            __syncwarp();
            gbar_wait(&g_start, gbar_arrive(&g_start, 1, 256, lane), 0);
            GT(13);
        }
        if (w == 1) {
            mbar_wait(bars + 8 * (B_W + 10), 0);
            uint32_t t = gtime();
#pragma unroll 1
            for (int i = 0; i < 4; i++) { if (lane == 0) tma2d_prefetch(&tm_wo, j * 256 + i * 64, h * 128); t += tn.extra; if (i < 3) wait_gtime(t); }
        }
        bar_sync(1, 128);
        uint32_t sf = 0;
#pragma unroll 1
        for (int s = 0; s < 64; s++) {
            TSI(s);
            OPAQUE_IDS();
            uint4 kf[4]; uint2 qf[2];
            const uint32_t tg = ((s >> 2) & 1) ^ 1;
            {
                const uint32_t ka = sb + O_KVQ + w * 2048 + lane * 16, qa = sb + O_KVQ + 16384 + w * 512 + lane * 8;
                uint32_t n = s == 0;
                bool redo;
#pragma unroll 1
                do {
                    asm volatile("" : "+r"(n));
                    if (n) {
                        const uint4* hb = &g_kvq[((s & 3) * 32 + h) * (3 * 512)];
                        uint4 y[4];
                        do {
#pragma unroll
                            for (int i = 0; i < 4; i++) { kf[i] = ldg_rlx128(hb + 512 + w * 128 + i * 32 + lane); y[i] = ldg_rlx128(hb + 1024 + w * 128 + i * 32 + lane); }
#pragma unroll
                            for (int u = 0; u < 2; u++) qf[u] = ldg_rlx64((const uint2*)hb + j * 256 + (2 * w + u) * 32 + lane);
                            if (++n > SPIN_LIMIT) __trap();
                        } while (__any_sync(~0u, (orx2(y[0].x, y[1].x, tg) | orx2(y[2].x, y[3].x, tg)) & 1));
#pragma unroll
                        for (int i = 0; i < 4; i++) { sts128u(ka + i * 512, kf[i]); sts128u(ka + 8192 + i * 512, y[i]); }
#pragma unroll
                        for (int u = 0; u < 2; u++) sts64u(qa + u * 256, qf[u]);
                        fence_async_smem();
                    }
                    n++;
                    mbar_wait(bars + 8 * B_KVFULL, s & 1);
#pragma unroll
                    for (int i = 0; i < 4; i++) kf[i] = lds128u(ka + i * 512);
#pragma unroll
                    for (int u = 0; u < 2; u++) qf[u] = lds64u(qa + u * 256);
                    redo = __any_sync(~0u, or3(orx2(kf[0].x, kf[1].x, tg), orx2(kf[2].x, kf[3].x, tg), orx2(qf[0].x, qf[1].x, tg)) & 1);
                } while (redo);
                if (w == 0) TSV(22, n - 1);
            }
            TS(9);
            if (s == 0) GT(15);
            if (s > 0) {
                const uint32_t n = convert_mem(redp, s - 1, kh, 1, w, lane, sb, sf); (void)n;
                TS(11);
                TSV(16 + w, n);
                LT(s - 1, 12 + w, n);
                if (w == 1 && s < 62) RED_CLEAR(s + 2);
            }
            const uint32_t tag = ((s >> 1) & 1) ^ 1;
            const uint2* ap = &g_alpha[((s & 1) * 32 + h) * (3 * 512) + w * 128 + lane];
            const uint32_t l16 = sb + lane * 16, l4 = sb + lane * 4;
            const uint32_t sw = l16 + O_S + w * 2560, sr = l4 + O_S + w * 128;
            uint32_t pw = sb + O_P + ((lane >> 1) & 1) * 704 + (2 * w + (lane >> 4)) * 16 + ((lane >> 2) & 3) * 4 + (lane & 1) * 2;
            int lim = (lane & 2) ? 8 * j + 2 * w + (lane >> 4) - 2 * ((lane >> 2) & 3) - (lane & 1) : 64;
            uint32_t aa = sb + O_STG + w * 1024 + lane * 8;
            KEEP2(l16, l4); KEEP2(pw, lim); KEEP2(aa, tag);
            TS(0);
            if (w == 0) {
                mbar_wait(bars + 8 * B_MEM, s & 1);
                uint32_t tq = gtime();
                if (lane < 9) stg_rlx32(lane < 8 ? (uint32_t*)g_qst + role * 8 + lane : (uint32_t*)g_stamp + role, tq);
                wait_clk(clk(), tn.d_q);
                uint32_t n = 0, mx;
                do { mx = __reduce_max_sync(~0u, ldg_rlx32((const uint32_t*)g_qst + h * 32 + lane) - (tq - 1024)); } while (mx > 100000u && ++n < 16);
                TSV(13, n);
                LT(s, 2, n);
                if (mx <= 100000u) tq += mx - 1024;
                if (lane == 0) { sts32(bars + 504, tq); mbar_arrive(bars + 8 * B_QST); }
                TS(14);
                mbar_wait(bars + 8 * B_QKW, s & 1);
                TS(1);
                wait_gtime(tq + tn.d_alpha);
                if (lane == 0) {
                    mbar_expect_tx(bars + 8 * B_AFULL, 8192);
                    bulk_g2s(sb + O_STG, ap, 8192, bars + 8 * B_AFULL);
                }
                if (s == 0) { mbar_wait(bars + 8 * B_WO, 0); GT(1); }
            }
            {
                uint32_t n = 0;
                bool redo;
#pragma unroll 1
                do {
                    asm volatile("" : "+r"(n));
                    if (n) {
                        uint2 x[8];
#pragma unroll
                        for (int q = 0; q < 8; q++) x[q] = ldg_rlx64(ap + (q >> 2) * 512 + (q & 3) * 32);
#pragma unroll
                        for (int q = 0; q < 8; q++) sts64u(aa + (q >> 2) * 4096 + (q & 3) * 256, x[q]);
                        if (n > SPIN_LIMIT) __trap();
                    }
                    n++;
                    mbar_wait(bars + 8 * B_AFULL, s & 1);
                    TS(12);
                    uint2 qa[4], ka[4];
#pragma unroll
                    for (int i = 0; i < 4; i++) qa[i] = lds64u(aa + i * 256);
#pragma unroll
                    for (int i = 0; i < 4; i++) ka[i] = lds64u(aa + 4096 + i * 256);
                    float sa[5][4];
#pragma unroll
                    for (int i = 0; i < 5; i++) sa[i][0] = sa[i][1] = sa[i][2] = sa[i][3] = 0.f;
#pragma unroll
                    for (int u = 0; u < 2; u++) {
                        const uint32_t q0 = add_bf16x2(qa[2 * u].x, qa[2 * u + 1].x), q1 = add_bf16x2(qa[2 * u].y, qa[2 * u + 1].y);
                        mma16816(sa[1], q0, qf[u].x, q1, qf[u].y, kf[2 * u].x, kf[2 * u].y);
                        mma16816(sa[2], q0, qf[u].x, q1, qf[u].y, kf[2 * u].z, kf[2 * u].w);
                        mma16816(sa[3], q0, qf[u].x, q1, qf[u].y, kf[2 * u + 1].x, kf[2 * u + 1].y);
                        mma16816(sa[4], q0, qf[u].x, q1, qf[u].y, kf[2 * u + 1].z, kf[2 * u + 1].w);
                        const uint32_t k0 = add_bf16x2(ka[2 * u].x, ka[2 * u + 1].x), k1 = add_bf16x2(ka[2 * u].y, ka[2 * u + 1].y);
                        mma16816(sa[0], q0, qf[u].x, q1, qf[u].y, k0, k1);
                        if (u == 0) SCHED_FENCE();
                    }
                    redo = __any_sync(~0u, or3(orx2(qa[0].x, ka[0].x, tag), orx2(qa[1].x, ka[1].x, tag),
                                               orx(orx(orx2(qa[2].x, ka[2].x, tag), qa[3].x, tag), ka[3].x, tag)) & 1);
#pragma unroll
                    for (int i = 1; i <= 5; i++) sts128(sw + (i % 5) * 512, sa[i % 5][0], sa[i % 5][1], sa[i % 5][2], sa[i % 5][3]);
                } while (redo);
                if (w == 0) TSV(20, n - 1);
            }
            TS(2);
            bar_sync(1, 128);
            float sc[5];
            {
                float x[4][5];
#pragma unroll
                for (int q = 0; q < 4; q++)
#pragma unroll
                    for (int n = 0; n < 5; n++) asm volatile("ld.shared.f32 %0, [%1];" : "=f"(x[q][n]) : "r"(sr + q * 2560 + n * 512) : "memory");
                if (lane == 0) mbar_arrive(bars + 8 * B_SDONE);
#pragma unroll
                for (int n = 0; n < 5; n++) sc[n] = (x[0][n] + x[1][n]) + (x[2][n] + x[3][n]);
            }
            TS(15);
#pragma unroll
            for (int n = 1; n < 5; n++) if (8 * (n - 1) > lim) sc[n] = MASK_VAL;
            float m = fmaxf(fmaxf(fmaxf(sc[0], sc[1]), fmaxf(sc[2], sc[3])), sc[4]);
            m = fmaxf(m, __shfl_xor_sync(~0u, m, 1));
            m = fmaxf(m, __shfl_xor_sync(~0u, m, 4));
            m = fmaxf(m, __shfl_xor_sync(~0u, m, 8));
            SCHED_FENCE();
            uint4 vf[4];
#pragma unroll
            for (int i = 0; i < 4; i++) vf[i] = lds128u(l16 + O_KVQ + 8192 + w * 2048 + i * 512);
            m *= -SM_SCALE_LOG2;
#pragma unroll
            for (int n = 0; n < 5; n++) {
                const uint32_t pv = pack_bf16(ex2(fmaf(sc[n], SM_SCALE_LOG2, m)), 0.f);
                asm volatile("st.shared.u16 [%0], %1;" ::"r"(pw + n * 128), "h"((uint16_t)pv) : "memory");
            }
            KEEP2(vf[0].x, vf[1].x); KEEP2(vf[2].x, vf[3].x);
            SCHED_FENCE();
            bar_sync(1, 128);
            TS(3);
            if (lane == 0) mbar_arrive(bars + 8 * B_SRDY);
            float ox[2][4], sm[4], sx[4], cc[4][4];
            unsigned char *pa, *pb;
#pragma unroll 1
            for (uint32_t nv = 0;; nv++) {
                uint32_t pf[4], p0, px[4], px0;
                ldsm4(pf, l16 + O_P + 128);
                ldsm4(px, l16 + O_P + 128 + 704);
                asm volatile("ld.shared.u32 %0, [%1];" : "=r"(p0) : "r"(l4 + O_P) : "memory");
                asm volatile("ld.shared.u32 %0, [%1];" : "=r"(px0) : "r"(l4 + O_P + 704) : "memory");
                float o[2][4];
#pragma unroll
                for (int i = 0; i < 4; i++) o[0][i] = o[1][i] = ox[0][i] = ox[1][i] = sm[i] = sx[i] = 0.f;
                constexpr uint32_t ONE2 = 0x3f803f80u;
                mma1688(sm, ONE2, ONE2, p0);
                mma1688(sx, ONE2, ONE2, px0);
#pragma unroll
                for (int c = 0; c < 2; c++) {
#pragma unroll
                    for (int u = 0; u < 2; u++) mma16816(o[u], vf[2 * u + c].x, vf[2 * u + c].y, vf[2 * u + c].z, vf[2 * u + c].w, pf[2 * c], pf[2 * c + 1]);
#pragma unroll
                    for (int u = 0; u < 2; u++) mma16816(ox[u], vf[2 * u + c].x, vf[2 * u + c].y, vf[2 * u + c].z, vf[2 * u + c].w, px[2 * c], px[2 * c + 1]);
                    mma16816(sm, ONE2, ONE2, ONE2, ONE2, pf[2 * c], pf[2 * c + 1]);
                    mma16816(sx, ONE2, ONE2, ONE2, ONE2, px[2 * c], px[2 * c + 1]);
                }
                const uint32_t vbad = orx(orx(orx2(vf[0].x, vf[1].x, tg), vf[2].x, tg), vf[3].x, tg);
                uint4 vm;
                {
                    uint32_t n = 0;
                    bool redo;
#pragma unroll 1
                    do {
                        vm = lds128v(l16 + O_VM + w * 512);
                        float o2[2][4];
#pragma unroll
                        for (int i = 0; i < 4; i++) { o2[0][i] = o[0][i]; o2[1][i] = o[1][i]; }
                        mma1688(o2[0], vm.x, vm.y, p0);
                        mma1688(o2[1], vm.z, vm.w, p0);
                        redo = __any_sync(~0u, ((vm.x ^ ~s) & 1) && ++n < SPIN_LIMIT);
                        const uint32_t oa = l4 + O_O + w * 512;
                        sts32(oa, pack_bf16(o2[0][0], o2[0][1]));
                        sts32(oa + 128, pack_bf16(o2[0][2], o2[0][3]));
                        sts32(oa + 256, pack_bf16(o2[1][0], o2[1][1]));
                        sts32(oa + 384, pack_bf16(o2[1][2], o2[1][3]));
                    } while (redo);
                    if (w == 0) TSV(21, n);
                }
                TS(4);
                fence_async_smem();
                mma1688(ox[0], vm.x, vm.y, px0);
                mma1688(ox[1], vm.z, vm.w, px0);
                sm[0] = rcp(sm[0]); sm[1] = rcp(sm[1]);
                bar_sync(1, 128);
                TS(5);
#define OP_ISSUE(t0, t1)                                                                                       \
                wg_fence();                                                                                    \
                _Pragma("unroll") for (int ks = 0; ks < 8; ks++)                                               \
                    _Pragma("unroll") for (int t = t0; t < t1; t++) {                                          \
                        constexpr uint64_t da0 = mkdesc(SM_BASE + O_WO, 16, 1024, 1), db0 = mkdesc(SM_BASE + O_O, 128, 128, 0); \
                        if (ks == 0) wg_ss8<0>(cc[t], da0 + t * 1024, db0); else wg_ss8<1>(cc[t], da0 + t * 1024 + ks * 128, db0 + ks * 16); \
                    }                                                                                          \
                wg_commit();
                OP_ISSUE(0, (OP_SPLIT ? 2 : 4));
                pa = redp + (s & 3) * 32768 + red_grp(j * 16 + (tid >> 3));
                pb = pa + 512 + ((lane >> 3) & 1) * 64 + (lane & 7) * 8;
                pa += (lane & 7) * 16;
                KEEPP(pa); KEEPP(pb);
                SCHED_FENCE();
                if (!bar_or(1, 128, vbad)) break;
                wg_wait<0>();
                const uint4* vp = &g_kvq[((s & 3) * 32 + h) * (3 * 512) + 1024 + w * 128 + lane];
#pragma unroll
                for (int i = 0; i < 4; i++) vf[i] = ldg_rlx128(vp + i * 32);
                if (nv > SPIN_LIMIT) __trap();
                bar_sync(1, 128);
            }
            {
                const float i0 = sm[0], i1 = sm[1];
#pragma unroll
                for (int hf = 0; hf < 2; hf++) {
                    if (hf == 0 || OP_SPLIT) wg_wait<0>();
                    if (hf == 0) TS(6);
                    if (OPD_EARLY && hf == OP_SPLIT && lane == 0) mbar_arrive(bars + 8 * B_OPDONE);
                    asm volatile("red.relaxed.gpu.global.add.noftz.v4.bf16x2 [%0], {%1,%2,%3,%4};" ::"l"(pa + hf * 128),
                                 "r"(pack_bf16(cc[2 * hf][0] * i0, cc[2 * hf][1] * i1)), "r"(pack_bf16(cc[2 * hf][2] * i0, cc[2 * hf][3] * i1)),
                                 "r"(pack_bf16(cc[2 * hf + 1][0] * i0, cc[2 * hf + 1][1] * i1)), "r"(pack_bf16(cc[2 * hf + 1][2] * i0, 1.f)) : "memory");
                    if (OP_SPLIT && hf == 0) { SCHED_FENCE(); OP_ISSUE(2, 4); }
                }
                asm volatile("red.relaxed.gpu.global.add.noftz.v2.bf16x2 [%0], {%1,%2};" ::"l"(pb), "r"(pack_bf16(cc[1][3] * i1, cc[3][3] * i1)), "r"(0x3f800000u) : "memory");
                if (!OPD_EARLY && lane == 0) mbar_arrive(bars + 8 * B_OPDONE);
                SCHED_FENCE();
                TS(7);
            }
            {
                const float ix0 = rcp(sx[0]), ix1 = rcp(sx[1]);
                const uint32_t xo = sb + O_XO + w * 512;
                stsm4t(xo + (lane & 7) * 64 + (((lane >> 3) ^ ((lane >> 1) & 3)) << 4), pack_bf16(ox[0][0] * ix0, ox[0][1] * ix1),
                       pack_bf16(ox[0][2] * ix0, ox[0][3] * ix1), pack_bf16(ox[1][0] * ix0, ox[1][1] * ix1), pack_bf16(ox[1][2] * ix0, ox[1][3] * ix1));
                __syncwarp();
                const uint4 ov = lds128u(xo + (lane >> 2) * 64 + (((lane & 3) ^ ((lane >> 3) & 3)) << 4));
                stg128(&g_ox[(size_t)(s * 32 + j * 8 + (lane >> 2)) * 4096 + h * 128 + w * 32 + (lane & 3) * 8], ov.x, ov.y, ov.z, ov.w);
            }
            TS(8);
            if (w == 2) { LT(s, 0, gtime()); LT(s, 1, clk()); }
            if (s == 0) GT(2);
        }
        GT(3);
        sts32(bars + 508, sf);
        TSDUMP();
        bar_sync(7, 512);
        const int m0 = (role >> 3) * 128, nb = (role & 7) * 2;
#define W2_LOAD(st, kt) { mbar_expect_tx(bars + 8 * (B_GF + (st)), 32768); tma3d(sb + (st) * 32768 + 16384, &tm_w2, 0, (kt) * 64, nb, bars + 8 * (B_GF + (st))); }
        if (w == 1 && lane == 0) {
            fence_async_smem();
#pragma unroll 1
            for (int kt = 0; kt < G_ST; kt++) W2_LOAD(kt, kt);
        }
        if (w == 0) {
            gbar_wait(&g_end, gbar_arrive(&g_end, 1, 128, lane), 0);
            int st = 0, ph = 1;
#pragma unroll 1
            for (int kt = 0; kt < 64; kt++) {
                if (kt >= G_ST) mbar_wait(bars + 8 * (B_GE + st), ph);
                if (lane == 0) {
                    if (kt >= G_ST) W2_LOAD(st, kt);
                    tma2d(sb + st * 32768, &tm_o, kt * 64, m0, bars + 8 * (B_GF + st));
                }
                if (++st == G_ST) { st = 0; ph ^= 1; }
            }
        }
    }
}

typedef CUresult (*EncodeFn)(CUtensorMap*, CUtensorMapDataType, cuuint32_t, void*, const cuuint64_t*, const cuuint64_t*,
                             const cuuint32_t*, const cuuint32_t*, CUtensorMapInterleave, CUtensorMapSwizzle,
                             CUtensorMapL2promotion, CUtensorMapFloatOOBfill);

static void make_map(EncodeFn fn, CUtensorMap* m, const void* p, uint64_t cols, uint64_t rows, uint32_t bc, uint32_t br) {
    cuuint64_t dims[2] = {cols, rows}, strides[1] = {cols * 2};
    cuuint32_t box[2] = {bc, br}, es[2] = {1, 1};
    fn(m, CU_TENSOR_MAP_DATA_TYPE_BFLOAT16, 2, (void*)p, dims, strides, box, es, CU_TENSOR_MAP_INTERLEAVE_NONE,
       CU_TENSOR_MAP_SWIZZLE_128B, CU_TENSOR_MAP_L2_PROMOTION_L2_128B, CU_TENSOR_MAP_FLOAT_OOB_FILL_NONE);
}

static Tune h_tune = {480, 1888, 6 + 16 * 2 + 256 * 4, 200, 960, 4000, 600};

extern "C" void kernel_launch(void* const* d_in, const int* in_sizes, int n_in, void* d_out, int out_size) {
    static bool init = false;
    static FftMaps fm;
    static CUtensorMap tm_x, tm_wq, tm_wk, tm_wv, tm_wo, tm_o, tm_wo2;
    if (!init) {
        void* fp = nullptr; cudaDriverEntryPointQueryResult qr;
        cudaGetDriverEntryPoint("cuTensorMapEncodeTiled", &fp, cudaEnableDefault, &qr);
        EncodeFn fn = (EncodeFn)fp;
        void* ox = nullptr; cudaGetSymbolAddress(&ox, g_ox);
        {
            cuuint64_t dims[4] = {64, 8, 16, 256}, strides[3] = {2048, 128, 16384};
            cuuint32_t box[4] = {64, 8, 8, 4}, es[4] = {1, 1, 1, 1};
            fn(&tm_x, CU_TENSOR_MAP_DATA_TYPE_BFLOAT16, 4, d_in[3], dims, strides, box, es, CU_TENSOR_MAP_INTERLEAVE_NONE,
               CU_TENSOR_MAP_SWIZZLE_128B, CU_TENSOR_MAP_L2_PROMOTION_L2_128B, CU_TENSOR_MAP_FLOAT_OOB_FILL_NONE);
        }
        void* fy = nullptr; cudaGetSymbolAddress(&fy, g_fy);
        for (int i = 0; i < 3; i++) {
            const cuuint64_t pitch = i == 2 ? 4096 : 2048;
            cuuint64_t dims[4] = {1024, 8, 16, 16}, strides[3] = {pitch, 128 * pitch, 8 * pitch};
            cuuint32_t box[4] = {64, 1, 16, 16}, es[4] = {1, 1, 1, 1};
            fn(i == 0 ? &fm.x : i == 1 ? &fm.y : &fm.o, CU_TENSOR_MAP_DATA_TYPE_BFLOAT16, 4, i == 0 ? d_in[0] : i == 1 ? fy : d_out, dims, strides, box, es,
               CU_TENSOR_MAP_INTERLEAVE_NONE, CU_TENSOR_MAP_SWIZZLE_128B, CU_TENSOR_MAP_L2_PROMOTION_L2_256B, CU_TENSOR_MAP_FLOAT_OOB_FILL_NONE);
        }
        {
            cuuint64_t dims[3] = {64, 2048, 16}, strides[2] = {2048, 128};
            cuuint32_t box[3] = {64, 8, 16}, es[3] = {1, 1, 1};
            fn(&fm.y2, CU_TENSOR_MAP_DATA_TYPE_BFLOAT16, 3, fy, dims, strides, box, es, CU_TENSOR_MAP_INTERLEAVE_NONE,
               CU_TENSOR_MAP_SWIZZLE_128B, CU_TENSOR_MAP_L2_PROMOTION_L2_128B, CU_TENSOR_MAP_FLOAT_OOB_FILL_NONE);
        }
        for (int i = 0; i < 2; i++) {
            cuuint64_t dims[3] = {256 * 513 - 448, 8, 8}, strides[2] = {128, 256 * 1026};
            cuuint32_t box[3] = {72, 8, 8}, es[3] = {1, 1, 1};
            fn(i ? &fm.wi : &fm.wr, CU_TENSOR_MAP_DATA_TYPE_BFLOAT16, 3, d_in[1 + i], dims, strides, box, es, CU_TENSOR_MAP_INTERLEAVE_NONE,
               CU_TENSOR_MAP_SWIZZLE_NONE, CU_TENSOR_MAP_L2_PROMOTION_L2_128B, CU_TENSOR_MAP_FLOAT_OOB_FILL_NONE);
        }
        make_map(fn, &tm_wq, d_in[5], 4096, 1024, 64, 128);
        make_map(fn, &tm_wk, d_in[6], 4096, 1024, 64, 128);
        make_map(fn, &tm_wv, d_in[7], 4096, 1024, 64, 128);
        make_map(fn, &tm_wo, d_in[8], 1024, 4096, 64, 128);
        make_map(fn, &tm_o, ox, 4096, 2048, 64, 128);
        {
            cuuint64_t dims[3] = {64, 4096, 16}, strides[2] = {2048, 128};
            cuuint32_t box[3] = {64, 64, 2}, es[3] = {1, 1, 1};
            fn(&tm_wo2, CU_TENSOR_MAP_DATA_TYPE_BFLOAT16, 3, d_in[8], dims, strides, box, es, CU_TENSOR_MAP_INTERLEAVE_NONE,
               CU_TENSOR_MAP_SWIZZLE_128B, CU_TENSOR_MAP_L2_PROMOTION_L2_128B, CU_TENSOR_MAP_FLOAT_OOB_FILL_NONE);
        }
        cudaFuncSetAttribute(rmt_main, cudaFuncAttributeMaxDynamicSharedMemorySize, MAIN_SMEM);
        init = true;
    }
    rmt_main<<<132, 512, MAIN_SMEM>>>(tm_x, tm_wq, tm_wk, tm_wv, tm_wo, (const bf16*)d_in[4], h_tune, fm, tm_o, tm_wo2, (bf16*)d_out);
}
```

```cpp
#include <cuda_runtime.h>
#include <cuda_bf16.h>
#include <cuda.h>
#include <stdint.h>

typedef __nv_bfloat16 bf16;

#define DBG_TIMING 0

#define SPIN_LIMIT (1u << 22)

__device__ __forceinline__ uint32_t smem_u32(const void* p) { return (uint32_t)__cvta_generic_to_shared(p); }
__device__ __forceinline__ uint32_t clk() { uint32_t c; asm volatile("mov.u32 %0, %%clock;" : "=r"(c)::"memory"); return c; }
#define SCHED_FENCE() sf ^= (uint32_t)clock64()
#define KEEP2(a, b) asm volatile("lop3.b32 %0, %0, %1, %2, 0x96;" : "+r"(sf) : "r"((uint32_t)(a)), "r"((uint32_t)(b)))
#define KEEPP(p) KEEP2((uintptr_t)(p), (uintptr_t)(p) >> 32)
__device__ __forceinline__ uint32_t gtime() { uint32_t c; asm volatile("mov.u32 %0, %%globaltimer_lo;" : "=r"(c)::"memory"); return c; }
__device__ __forceinline__ void wait_clk(uint32_t t0, uint32_t d) {
    asm volatile("{\n.reg .pred p;\n.reg .s32 t;\n.reg .b64 c;\nWL:\nmov.u64 c, %%clock64;\ncvt.u32.u64 t, c;\nsub.s32 t, t, %0;\nsetp.lt.s32 p, t, 0;\n@p bra.uni WL;\n}" ::"r"(t0 + d) : "memory");
}
__device__ __forceinline__ void wait_gtime(uint32_t t1) {
    asm volatile("{\n.reg .pred p;\n.reg .s32 t;\n.reg .b64 c;\nWL:\nmov.u64 c, %%globaltimer;\ncvt.u32.u64 t, c;\nsub.s32 t, t, %0;\nsetp.lt.s32 p, t, 0;\n@p bra.uni WL;\n}" ::"r"(t1) : "memory");
}

__device__ __forceinline__ void mbar_init(uint32_t bar, uint32_t cnt) {
    asm volatile("mbarrier.init.shared::cta.b64 [%0], %1;" ::"r"(bar), "r"(cnt) : "memory");
}
__device__ __forceinline__ void mbar_arrive(uint32_t bar) {
    asm volatile("mbarrier.arrive.shared::cta.b64 _, [%0];" ::"r"(bar) : "memory");
}
__device__ __forceinline__ void mbar_expect_tx(uint32_t bar, uint32_t bytes) {
    asm volatile("mbarrier.arrive.expect_tx.shared::cta.b64 _, [%0], %1;" ::"r"(bar), "r"(bytes) : "memory");
}
__device__ __forceinline__ void mbar_wait(uint32_t bar, uint32_t parity) {
    asm volatile(
        "{\n.reg .pred p, q;\n.reg .u32 n;\nmov.u32 n, 0;\n"
        "WL:\nmbarrier.try_wait.parity.shared::cta.b64 p, [%0], %1;\n"
        "add.u32 n, n, 1;\nsetp.gt.u32 q, n, %2;\n@q trap;\n@!p bra.uni WL;\n}" ::"r"(bar), "r"(parity), "n"(SPIN_LIMIT) : "memory");
}
__device__ __forceinline__ void mbar_wait_cluster(uint32_t bar, uint32_t parity) {
    asm volatile(
        "{\n.reg .pred p, q;\n.reg .u32 n;\nmov.u32 n, 0;\n"
        "WL:\nmbarrier.try_wait.parity.acquire.cluster.shared::cta.b64 p, [%0], %1;\n"
        "add.u32 n, n, 1;\nsetp.gt.u32 q, n, %2;\n@q trap;\n@!p bra.uni WL;\n}" ::"r"(bar), "r"(parity), "n"(SPIN_LIMIT) : "memory");
}
__device__ __forceinline__ void tma2d(uint32_t dst, const CUtensorMap* m, int c0, int c1, uint32_t bar) {
    asm volatile("cp.async.bulk.tensor.2d.shared::cluster.global.mbarrier::complete_tx::bytes [%0], [%1, {%3, %4}], [%2];"
                 ::"r"(dst), "l"(m), "r"(bar), "r"(c0), "r"(c1) : "memory");
}
__device__ __forceinline__ void tma3d(uint32_t dst, const CUtensorMap* m, int c0, int c1, int c2, uint32_t bar) {
    asm volatile("cp.async.bulk.tensor.3d.shared::cluster.global.mbarrier::complete_tx::bytes [%0], [%1, {%3, %4, %5}], [%2];"
                 ::"r"(dst), "l"(m), "r"(bar), "r"(c0), "r"(c1), "r"(c2) : "memory");
}
__device__ __forceinline__ void tma4d(uint32_t dst, const CUtensorMap* m, int c2, int c3, uint32_t bar) {
    asm volatile("cp.async.bulk.tensor.4d.shared::cluster.global.mbarrier::complete_tx::bytes [%0], [%1, {%5, %5, %3, %4}], [%2];"
                 ::"r"(dst), "l"(m), "r"(bar), "r"(c2), "r"(c3), "r"(0) : "memory");
}
__device__ __forceinline__ void bulk_g2s(uint32_t dst, const void* src, uint32_t bytes, uint32_t bar) {
    asm volatile("cp.async.bulk.shared::cluster.global.mbarrier::complete_tx::bytes [%0], [%1], %2, [%3];"
                 ::"r"(dst), "l"(src), "r"(bytes), "r"(bar) : "memory");
}
__device__ __forceinline__ void tma4d_prefetch(const CUtensorMap* m, int c2, int c3) {
    asm volatile("cp.async.bulk.prefetch.tensor.4d.L2.global [%0, {%3, %3, %1, %2}];" ::"l"(m), "r"(c2), "r"(c3), "r"(0) : "memory");
}
__device__ __forceinline__ void tma2d_prefetch(const CUtensorMap* m, int c0, int c1) {
    asm volatile("cp.async.bulk.prefetch.tensor.2d.L2.global [%0, {%1, %2}];" ::"l"(m), "r"(c0), "r"(c1) : "memory");
}
__device__ __forceinline__ void fence_async_smem() { asm volatile("fence.proxy.async.shared::cta;" ::: "memory"); }
__device__ __forceinline__ void fence_gpu() { asm volatile("fence.acq_rel.gpu;" ::: "memory"); }
__device__ __forceinline__ float rcp(float x) { float r; asm("rcp.approx.ftz.f32 %0, %1;" : "=f"(r) : "f"(x)); return r; }
__device__ __forceinline__ void bar_sync(int id, int n) { asm volatile("bar.sync %0, %1;" ::"r"(id), "r"(n) : "memory"); }

__device__ __forceinline__ bool bar_or(int id, int n, uint32_t x) {
    uint32_t r;
    asm volatile("{\n.reg .pred p, q;\n.reg .b32 t;\nand.b32 t, %3, 1;\nsetp.ne.u32 p, t, 0;\nbar.red.or.pred q, %1, %2, p;\nselp.u32 %0, 1, 0, q;\n}"
                 : "=r"(r) : "r"(id), "r"(n), "r"(x) : "memory");
    return __any_sync(~0u, r);
}
__device__ __forceinline__ uint32_t or3(uint32_t a, uint32_t b, uint32_t c) {
    uint32_t r; asm("lop3.b32 %0, %1, %2, %3, 0xFE;" : "=r"(r) : "r"(a), "r"(b), "r"(c)); return r;
}
__device__ __forceinline__ uint32_t pack_bf16(float lo, float hi) {
    uint32_t r; asm("cvt.rn.bf16x2.f32 %0, %1, %2;" : "=r"(r) : "f"(hi), "f"(lo)); return r;
}
__device__ __forceinline__ uint32_t add_bf16x2(uint32_t a, uint32_t b) {
    uint32_t r; asm volatile("add.rn.bf16x2 %0, %1, %2;" : "=r"(r) : "r"(a), "r"(b)); return r;
}
__device__ __forceinline__ uint32_t movm(uint32_t a) {
    uint32_t r; asm volatile("movmatrix.sync.aligned.m8n8.trans.b16 %0, %1;" : "=r"(r) : "r"(a)); return r;
}
__device__ __forceinline__ uint32_t orx(uint32_t acc, uint32_t a, uint32_t t) {
    uint32_t r; asm("lop3.b32 %0, %1, %2, %3, 0xF6;" : "=r"(r) : "r"(acc), "r"(a), "r"(t)); return r;
}
__device__ __forceinline__ uint32_t orx2(uint32_t a, uint32_t b, uint32_t t) {
    uint32_t r; asm("lop3.b32 %0, %1, %2, %3, 0x7E;" : "=r"(r) : "r"(a), "r"(b), "r"(t)); return r;
}
__device__ __forceinline__ float ex2(float x) { float r; asm("ex2.approx.ftz.f32 %0, %1;" : "=f"(r) : "f"(x)); return r; }
__device__ __forceinline__ void ldsm4t(uint32_t (&r)[4], uint32_t a) {
    asm volatile("ldmatrix.sync.aligned.m8n8.x4.trans.shared.b16 {%0,%1,%2,%3}, [%4];"
                 : "=r"(r[0]), "=r"(r[1]), "=r"(r[2]), "=r"(r[3]) : "r"(a) : "memory");
}
__device__ __forceinline__ void ldsm4(uint32_t (&r)[4], uint32_t a) {
    asm volatile("ldmatrix.sync.aligned.m8n8.x4.shared.b16 {%0,%1,%2,%3}, [%4];"
                 : "=r"(r[0]), "=r"(r[1]), "=r"(r[2]), "=r"(r[3]) : "r"(a) : "memory");
}
__device__ __forceinline__ void stsm4t(uint32_t a, uint32_t r0, uint32_t r1, uint32_t r2, uint32_t r3) {
    asm volatile("stmatrix.sync.aligned.m8n8.x4.trans.shared.b16 [%0], {%1,%2,%3,%4};"
                 ::"r"(a), "r"(r0), "r"(r1), "r"(r2), "r"(r3) : "memory");
}
__device__ __forceinline__ void stsm4(uint32_t a, uint32_t r0, uint32_t r1, uint32_t r2, uint32_t r3) {
    asm volatile("stmatrix.sync.aligned.m8n8.x4.shared.b16 [%0], {%1,%2,%3,%4};"
                 ::"r"(a), "r"(r0), "r"(r1), "r"(r2), "r"(r3) : "memory");
}
__device__ __forceinline__ void mma16816(float* c, uint32_t a0, uint32_t a1, uint32_t a2, uint32_t a3, uint32_t b0, uint32_t b1) {
    asm volatile("mma.sync.aligned.m16n8k16.row.col.f32.bf16.bf16.f32 {%0,%1,%2,%3}, {%4,%5,%6,%7}, {%8,%9}, {%0,%1,%2,%3};"
                 : "+f"(c[0]), "+f"(c[1]), "+f"(c[2]), "+f"(c[3]) : "r"(a0), "r"(a1), "r"(a2), "r"(a3), "r"(b0), "r"(b1));
}
__device__ __forceinline__ void mma1688(float* c, uint32_t a0, uint32_t a1, uint32_t b0) {
    asm volatile("mma.sync.aligned.m16n8k8.row.col.f32.bf16.bf16.f32 {%0,%1,%2,%3}, {%4,%5}, {%6}, {%0,%1,%2,%3};"
                 : "+f"(c[0]), "+f"(c[1]), "+f"(c[2]), "+f"(c[3]) : "r"(a0), "r"(a1), "r"(b0));
}
__device__ __forceinline__ void sts128(uint32_t a, float x, float y, float z, float w) {
    asm volatile("st.shared.v4.f32 [%0], {%1,%2,%3,%4};" ::"r"(a), "f"(x), "f"(y), "f"(z), "f"(w) : "memory");
}
__device__ __forceinline__ void sts64(uint32_t a, float x, float y) {
    asm volatile("st.shared.v2.f32 [%0], {%1,%2};" ::"r"(a), "f"(x), "f"(y) : "memory");
}
__device__ __forceinline__ void sts32(uint32_t a, uint32_t x) { asm volatile("st.shared.b32 [%0], %1;" ::"r"(a), "r"(x) : "memory"); }
__device__ __forceinline__ void sts128u(uint32_t a, uint4 v) {
    asm volatile("st.shared.v4.b32 [%0], {%1,%2,%3,%4};" ::"r"(a), "r"(v.x), "r"(v.y), "r"(v.z), "r"(v.w) : "memory");
}
__device__ __forceinline__ float4 lds128(uint32_t a) {
    float4 v; asm volatile("ld.shared.v4.f32 {%0,%1,%2,%3}, [%4];" : "=f"(v.x), "=f"(v.y), "=f"(v.z), "=f"(v.w) : "r"(a) : "memory"); return v;
}
__device__ __forceinline__ uint4 lds128u(uint32_t a) {
    uint4 v; asm volatile("ld.shared.v4.b32 {%0,%1,%2,%3}, [%4];" : "=r"(v.x), "=r"(v.y), "=r"(v.z), "=r"(v.w) : "r"(a) : "memory"); return v;
}
__device__ __forceinline__ uint4 lds128v(uint32_t a) {
    uint4 v; asm volatile("ld.volatile.shared.v4.b32 {%0,%1,%2,%3}, [%4];" : "=r"(v.x), "=r"(v.y), "=r"(v.z), "=r"(v.w) : "r"(a) : "memory"); return v;
}
__device__ __forceinline__ void sts64u(uint32_t a, uint2 v) { asm volatile("st.shared.v2.b32 [%0], {%1,%2};" ::"r"(a), "r"(v.x), "r"(v.y) : "memory"); }
__device__ __forceinline__ uint2 lds64u(uint32_t a) {
    uint2 v; asm volatile("ld.shared.v2.b32 {%0,%1}, [%2];" : "=r"(v.x), "=r"(v.y) : "r"(a) : "memory"); return v;
}
__device__ __forceinline__ float2 lds64(uint32_t a) {
    float2 v; asm volatile("ld.shared.v2.f32 {%0,%1}, [%2];" : "=f"(v.x), "=f"(v.y) : "r"(a) : "memory"); return v;
}
__device__ __forceinline__ uint2 ldg_rlx64(const void* p) {
    uint2 v; asm volatile("ld.relaxed.gpu.global.v2.b32 {%0,%1}, [%2];" : "=r"(v.x), "=r"(v.y) : "l"(p) : "memory"); return v;
}
__device__ __forceinline__ uint4 ldg_rlx128(const void* p) {
    uint4 v; asm volatile("ld.relaxed.gpu.global.v4.b32 {%0,%1,%2,%3}, [%4];" : "=r"(v.x), "=r"(v.y), "=r"(v.z), "=r"(v.w) : "l"(p) : "memory"); return v;
}
__device__ __forceinline__ void stg_rlx64(void* p, uint32_t x, uint32_t y) {
    asm volatile("st.relaxed.gpu.global.v2.b32 [%0], {%1,%2};" ::"l"(p), "r"(x), "r"(y) : "memory");
}
__device__ __forceinline__ void stg_rlx128(void* p, uint32_t x, uint32_t y, uint32_t z, uint32_t w) {
    asm volatile("st.relaxed.gpu.global.v4.b32 [%0], {%1,%2,%3,%4};" ::"l"(p), "r"(x), "r"(y), "r"(z), "r"(w) : "memory");
}
__device__ __forceinline__ uint32_t ldg_rlx32(const void* p) {
    uint32_t v; asm volatile("ld.relaxed.gpu.global.b32 %0, [%1];" : "=r"(v) : "l"(p) : "memory"); return v;
}
__device__ __forceinline__ void stg128(void* p, uint32_t x, uint32_t y, uint32_t z, uint32_t w) {
    asm volatile("st.global.v4.b32 [%0], {%1,%2,%3,%4};" ::"l"(p), "r"(x), "r"(y), "r"(z), "r"(w) : "memory");
}
__device__ __forceinline__ uint32_t ld_acquire(const unsigned* p) {
    uint32_t v; asm volatile("ld.acquire.gpu.global.u32 %0, [%1];" : "=r"(v) : "l"(p) : "memory"); return v;
}
__device__ __forceinline__ void red_add_u32(unsigned* p, uint32_t v) {
    asm volatile("red.relaxed.gpu.global.add.u32 [%0], %1;" ::"l"(p), "r"(v) : "memory");
}
__device__ __forceinline__ void wait_counter(const unsigned* p, uint32_t target) {
    uint32_t n = 0;
    while (ld_acquire(p) < target) { if (++n > SPIN_LIMIT) __trap(); }
}

__device__ __forceinline__ void wg_fence() { asm volatile("wgmma.fence.sync.aligned;" ::: "memory"); }
__device__ __forceinline__ void wg_commit() { asm volatile("wgmma.commit_group.sync.aligned;" ::: "memory"); }
template <int N> __device__ __forceinline__ void wg_wait() { asm volatile("wgmma.wait_group.sync.aligned %0;" ::"n"(N) : "memory"); }
__host__ __device__ constexpr uint64_t mkdesc(uint32_t addr, uint32_t lbo, uint32_t sbo, uint32_t swz) {
    return (uint64_t)((addr & 0x3FFFF) >> 4) | ((uint64_t)(lbo >> 4) << 16) | ((uint64_t)(sbo >> 4) << 32) | ((uint64_t)swz << 62);
}
#define F4(d, o) "+f"(d[o]), "+f"(d[o + 1]), "+f"(d[o + 2]), "+f"(d[o + 3])
template <int SC> __device__ __forceinline__ void wg_rs32(float (&d)[16], const uint32_t (&a)[4], uint64_t db) {
    asm volatile("wgmma.mma_async.sync.aligned.m64n32k16.f32.bf16.bf16 "
                 "{%0,%1,%2,%3,%4,%5,%6,%7,%8,%9,%10,%11,%12,%13,%14,%15}, {%16,%17,%18,%19}, %20, %21, 1, 1, 0;"
                 : F4(d, 0), F4(d, 4), F4(d, 8), F4(d, 12)
                 : "r"(a[0]), "r"(a[1]), "r"(a[2]), "r"(a[3]), "l"(db), "n"(SC));
}
template <int SC> __device__ __forceinline__ void wg_rs40(float (&d)[20], const uint32_t (&a)[4], uint64_t db) {
    asm volatile("wgmma.mma_async.sync.aligned.m64n40k16.f32.bf16.bf16 "
                 "{%0,%1,%2,%3,%4,%5,%6,%7,%8,%9,%10,%11,%12,%13,%14,%15,%16,%17,%18,%19}, {%20,%21,%22,%23}, %24, %25, 1, 1, 0;"
                 : F4(d, 0), F4(d, 4), F4(d, 8), F4(d, 12), F4(d, 16)
                 : "r"(a[0]), "r"(a[1]), "r"(a[2]), "r"(a[3]), "l"(db), "n"(SC));
}
template <int SC> __device__ __forceinline__ void wg_ss40(float (&d)[20], uint64_t da, uint64_t db) {
    asm volatile("wgmma.mma_async.sync.aligned.m64n40k16.f32.bf16.bf16 "
                 "{%0,%1,%2,%3,%4,%5,%6,%7,%8,%9,%10,%11,%12,%13,%14,%15,%16,%17,%18,%19}, %20, %21, %22, 1, 1, 1, 0;"
                 : F4(d, 0), F4(d, 4), F4(d, 8), F4(d, 12), F4(d, 16)
                 : "l"(da), "l"(db), "n"(SC));
}
template <int SC> __device__ __forceinline__ void wg_ss8(float (&d)[4], uint64_t da, uint64_t db) {
    asm volatile("wgmma.mma_async.sync.aligned.m64n8k16.f32.bf16.bf16 {%0,%1,%2,%3}, %4, %5, %6, 1, 1, 1, 1;"
                 : F4(d, 0) : "l"(da), "l"(db), "n"(SC));
}

constexpr int DBG_N = 11;
#define LT(st, k, v) do {} while (0)
#define TSI(st) do {} while (0)
#define TS(k) do {} while (0)
#define TSV(k, v) do {} while (0)
#define TSDUMP() do {} while (0)
#define GT(k) do {} while (0)

__device__ __align__(256) uint4 g_fy[2048 * 128];

constexpr uint32_t FG_SIZE = 2 * 32768 + 36864;
constexpr uint32_t FT_F16 = 2 * FG_SIZE, FT_B1F = FT_F16 + 2048, FT_B1I = FT_B1F + 2048, FT_C = FT_B1I + 2048, FT_A8 = FT_C + 2048,
                   FT_TWC = FT_A8 + 512, FT_TWB = FT_TWC + 8192, FT_BAR = FT_TWB + 8192, FFT_SMEM = FT_BAR + 256;
struct FftMaps { CUtensorMap x, y, o, y2, wr, wi; const unsigned char* w[3]; };

__device__ __forceinline__ float2 wroot(int e) {
    float s, c; sincospif((float)(e & 2047) * (-1.f / 1024.f), &s, &c); return make_float2(c, s);
}
__device__ __forceinline__ uint4 afrag(float2 a, float2 b) {
    return make_uint4(pack_bf16(a.x, -a.y), pack_bf16(a.y, a.x), pack_bf16(b.x, -b.y), pack_bf16(b.y, b.x));
}
__device__ __forceinline__ uint4 conjfrag(uint4 v) { return make_uint4(v.x ^ 0x80000000u, v.y ^ 0x8000u, v.z ^ 0x80000000u, v.w ^ 0x8000u); }
__device__ __forceinline__ uint4 negfrag(uint4 v) { return make_uint4(v.x ^ 0x80008000u, v.y ^ 0x80008000u, v.z ^ 0x80008000u, v.w ^ 0x80008000u); }
__device__ __forceinline__ uint32_t comp(const uint4& v, int i) { return i == 0 ? v.x : i == 1 ? v.y : i == 2 ? v.z : v.w; }
__device__ __forceinline__ void setcomp(uint4& v, int i, uint32_t x) { if (i == 0) v.x = x; else if (i == 1) v.y = x; else if (i == 2) v.z = x; else v.w = x; }
__device__ __forceinline__ float2 cmul(float2 a, float2 b) { return make_float2(a.x * b.x - a.y * b.y, a.x * b.y + a.y * b.x); }
__device__ __forceinline__ float2 cmulc(float2 a, float2 b) { return make_float2(a.x * b.x + a.y * b.y, a.y * b.x - a.x * b.y); }

__device__ __forceinline__ uint32_t pack_h2(float2 a) { uint32_t r; asm("cvt.rn.f16x2.f32 %0, %1, %2;" : "=r"(r) : "f"(a.y), "f"(a.x)); return r; }
__device__ __forceinline__ float2 unpack_h2(uint32_t v) {
    float2 r; asm("{\n.reg .b16 l, h;\nmov.b32 {l, h}, %2;\ncvt.f32.f16 %0, l;\ncvt.f32.f16 %1, h;\n}" : "=f"(r.x), "=f"(r.y) : "r"(v)); return r;
}
__device__ __forceinline__ void fft_tables(uint32_t tb, int tid, int nthr) {
    for (int i = tid; i < 128; i += nthr) {
        const int lane = i & 31, q = i >> 5, g = lane >> 2, t = lane & 3, o = 8 * (q >> 1) + g, in = 8 * (q & 1) + 2 * t;
        sts128u(tb + FT_F16 + i * 16, afrag(wroot(128 * o * in), wroot(128 * o * (in + 1))));
        sts128u(tb + FT_B1F + i * 16, afrag(wroot(64 * (1 + 2 * o) * in), wroot(64 * (1 + 2 * o) * (in + 1))));
        sts128u(tb + FT_B1I + i * 16, afrag(wroot(-64 * o * (1 + 2 * in)), wroot(-64 * o * (3 + 2 * in))));
        uint4 v;
        for (int r = 0; r < 4; r++) {
            const float2 a = wroot(128 * (4 * r + t) * (4 * q + (g >> 1)));
            setcomp(v, r, (g & 1) ? pack_bf16(a.y, a.x) : pack_bf16(a.x, -a.y));
        }
        sts128u(tb + FT_C + i * 16, v);
        if (q == 0) sts128u(tb + FT_A8 + lane * 16, afrag(wroot(256 * g * 2 * t), wroot(256 * g * (2 * t + 1))));
    }
    for (int i = tid; i < 512; i += nthr) {
        const int lane = i & 31, r = (i >> 5) & 3, phi = 8 * (i >> 7) + (lane >> 2), c = 4 * r + (lane & 3);
        const float2 a = wroot(4 * c * phi), b = wroot(2 * (phi + 32 * c));
        constexpr float SC = 1.f / (2.f * 2048.f * 512.f);
        sts128(tb + FT_TWC + i * 16, a.x * SC, a.y * SC, b.x, b.y);
    }
    for (int i = tid; i < 512; i += nthr) {
        const int lane = i & 31, r = (i >> 5) & 3, fa = (i >> 7) & 1, hf = i >> 8, c = 8 * (lane & 1) + r;
        const int p0 = fa + 2 * (lane >> 2), p1 = p0 + 16, s0 = (hf && p0) ? 32 - p0 : p0, s1 = hf ? 32 - p1 : p1;
        sts128u(tb + FT_TWB + i * 16, make_uint4(pack_h2(wroot(4 * c * s0)), pack_h2(wroot(4 * (c + 4) * s0)),
                                                 pack_h2(wroot(4 * c * s1)), pack_h2(wroot(4 * (c + 4) * s1))));
    }
}

template <bool TW>
__device__ __forceinline__ void dft16(uint4 (&out)[4], const uint4 (&in)[4], const uint4 (&m)[4], const uint4 (&tw)[4]) {
#pragma unroll
    for (int i = 0; i < 4; i++)
#pragma unroll
        for (int mt = 0; mt < 2; mt++) {
            float c[4] = {0.f, 0.f, 0.f, 0.f};
            mma16816(c, m[2 * mt].x, m[2 * mt].y, m[2 * mt].z, m[2 * mt].w, comp(in[0], i), comp(in[1], i));
            mma16816(c, m[2 * mt + 1].x, m[2 * mt + 1].y, m[2 * mt + 1].z, m[2 * mt + 1].w, comp(in[2], i), comp(in[3], i));
            if (TW) {
                const float2 a = cmul(make_float2(c[0], c[2]), unpack_h2(comp(tw[i], 2 * mt))), b = cmul(make_float2(c[1], c[3]), unpack_h2(comp(tw[i], 2 * mt + 1)));
                setcomp(out[2 * mt], i, pack_bf16(a.x, a.y));
                setcomp(out[2 * mt + 1], i, pack_bf16(b.x, b.y));
            } else {
                setcomp(out[2 * mt], i, pack_bf16(c[0], c[2]));
                setcomp(out[2 * mt + 1], i, pack_bf16(c[1], c[3]));
            }
        }
}
__device__ __forceinline__ void tma_ld4(uint32_t dst, const CUtensorMap* m, int c0, int c1, uint32_t bar) {
    asm volatile("cp.async.bulk.tensor.4d.shared::cluster.global.mbarrier::complete_tx::bytes [%0], [%1, {%3, %4, %5, %5}], [%2];"
                 ::"r"(dst), "l"(m), "r"(bar), "r"(c0), "r"(c1), "r"(0) : "memory");
}
__device__ __forceinline__ void tma_st4(uint32_t src, const CUtensorMap* m, int c0, int c1) {
    asm volatile("cp.async.bulk.tensor.4d.global.shared::cta.bulk_group [%1, {%2, %3, %4, %4}], [%0];" ::"r"(src), "l"(m), "r"(c0), "r"(c1), "r"(0) : "memory");
}
__device__ __forceinline__ void tma_ld3(uint32_t dst, const CUtensorMap* m, int c0, int c1, uint32_t bar) {
    asm volatile("cp.async.bulk.tensor.3d.shared::cluster.global.mbarrier::complete_tx::bytes [%0], [%1, {%3, %4, %5}], [%2];"
                 ::"r"(dst), "l"(m), "r"(bar), "r"(c0), "r"(c1), "r"(0) : "memory");
}
__device__ __forceinline__ void tma_st3(uint32_t src, const CUtensorMap* m, int c0, int c1) {
    asm volatile("cp.async.bulk.tensor.3d.global.shared::cta.bulk_group [%1, {%2, %3, %4}], [%0];" ::"r"(src), "l"(m), "r"(c0), "r"(c1), "r"(0) : "memory");
}
__device__ __forceinline__ void bulk_commit() { asm volatile("cp.async.bulk.commit_group;" ::: "memory"); }
__device__ __forceinline__ void bulk_wait_read() { asm volatile("cp.async.bulk.wait_group.read 0;" ::: "memory"); }
__device__ __forceinline__ void bulk_wait_all() { asm volatile("cp.async.bulk.wait_group 0;" ::: "memory"); }

__device__ __forceinline__ float2 wroot_fast(int e) {
    float s, c; __sincosf((float)(((e + 1024) & 2047) - 1024) * (-3.14159265358979f / 1024.f), &s, &c); return make_float2(c, s);
}
template <bool INV, int NT>
__device__ __forceinline__ void fft_col(int s2, int t0, const CUtensorMap* src, const CUtensorMap* dst, uint32_t gb, uint32_t mb,
                                        int w, int lane, int bar) {
    const int g = lane >> 2, t = lane & 3;
    const bool lead = w == 4 && lane == 0;
    if (NT > 1 && lead)
        for (int i = 0; i < 2; i++) { mbar_expect_tx(mb + 8 * i, 32768); tma_ld4(gb + i * 32768, src, (t0 + i) * 64, s2, mb + 8 * i); }
    uint4 f[4], m[2][4];
#pragma unroll
    for (int i = 0; i < 4; i++) {
        const int o = 8 * (i >> 1) + g, in = 8 * (i & 1) + 2 * t, sg = INV ? -128 : 128;
        f[i] = afrag(wroot_fast(sg * o * in), wroot_fast(sg * o * (in + 1)));
#pragma unroll
        for (int q = 0; q < 2; q++) {
            const int z = 2 * w + q;
            m[q][i] = INV ? afrag(wroot_fast(-(8 * o + s2) * (z + 16 * in)), wroot_fast(-(8 * o + s2) * (z + 16 * in + 16)))
                          : afrag(wroot_fast((z + 16 * o) * (8 * in + s2)), wroot_fast((z + 16 * o) * (8 * in + 8 + s2)));
        }
    }
    const uint32_t r1 = (32 * w + 2 * t) * 128 + ((g ^ (2 * t)) << 4);
    const uint32_t w1 = (32 * w + g) * 128 + (((2 * t) ^ (((w & 3) << 1) | (g & 1))) << 4);
    const uint32_t r2 = (32 * t + 2 * w) * 128 + ((g ^ (2 * t)) << 4);
    const uint32_t w2 = (32 * w + g) * 128 + (((2 * t) ^ g) << 4);
    int bi = 0, ph = 0;
#pragma unroll 1
    for (int it = 0; it < NT; it++) {
        const uint32_t buf = gb + bi * 32768;
        mbar_wait(mb + 8 * bi, ph);
        uint4 in[2][4], out[4];
#pragma unroll
        for (int q = 0; q < 2; q++)
#pragma unroll
            for (int i = 0; i < 4; i++) in[q][i] = lds128u(buf + (r1 ^ ((i & 1) * 0x90)) + (i >> 1) * 1024 + q * 2048);
        __syncwarp();
#pragma unroll
        for (int q = 0; q < 2; q++) {
            if (INV) dft16<false>(out, in[q], m[q], f); else dft16<false>(out, in[q], f, f);
#pragma unroll
            for (int i = 0; i < 4; i++) sts128u(buf + (w1 ^ ((i & 1) << 4)) + (i >> 1) * 1024 + q * 2048, out[i]);
        }
        bar_sync(bar, 256);
#pragma unroll
        for (int q = 0; q < 2; q++)
#pragma unroll
            for (int i = 0; i < 4; i++) in[q][i] = lds128u(buf + (r2 ^ (q * 0x90)) + (i & 1) * 2048 + (i >> 1) * 16384);
        const int bn = bi == 0 ? 2 : bi - 1;
        if (lead && it < NT - 2) { bulk_wait_read(); mbar_expect_tx(mb + 8 * bn, 32768); tma_ld4(gb + bn * 32768, src, (t0 + it + 2) * 64, s2, mb + 8 * bn); }
        bar_sync(bar, 256);
#pragma unroll
        for (int q = 0; q < 2; q++) {
            if (INV) dft16<false>(out, in[q], f, f); else dft16<false>(out, in[q], m[q], f);
#pragma unroll
            for (int i = 0; i < 4; i++) sts128u(buf + (w2 ^ ((i & 1) << 4)) + (i >> 1) * 1024 + q * 2048, out[i]);
        }
        fence_async_smem();
        bar_sync(bar, 256);
        if (NT > 1 && lead) { tma_st4(buf, dst, (t0 + it) * 64, s2); bulk_commit(); }
        if (++bi == 3) { bi = 0; ph ^= 1; }
    }
    if (NT > 1 && lead) bulk_wait_read();
}

__device__ __forceinline__ float ldw(uint32_t a) {
    uint16_t v; asm volatile("ld.shared.u16 %0, [%1];" : "=h"(v) : "r"(a) : "memory");
    return __uint_as_float((uint32_t)v << 16);
}
__device__ __forceinline__ void fft_mid(int grp, const FftMaps& fm, uint32_t tb,
                                        uint32_t gb, uint32_t mb, uint32_t& cnt, int w, int lane, int bar) {
    const int g = lane >> 2, t = lane & 3;
    const bool lead = w == 4 && lane == 0;
    const uint32_t wb = gb + 65536;
#define MID_LOAD(k, c)                                                                                                  \
    { mbar_expect_tx(mb + 8 * ((c) & 1), 32768);                                                                        \
      tma_ld3(gb + ((c) & 1) * 32768, &fm.y2, 0, (k) * 8, mb + 8 * ((c) & 1));                                          \
      tma_ld3(gb + ((c) & 1) * 32768 + 16384, &fm.y2, 0, ((256 - (k)) & 255) * 8, mb + 8 * ((c) & 1)); }
#define MID_LOADW(k)                                                                                                    \
    { mbar_expect_tx(mb + 16, 36864);                                                                                   \
      tma_ld3(wb, &fm.wr, (k) * 513 & ~7, 0, mb + 16); tma_ld3(wb + 9216, &fm.wi, (k) * 513 & ~7, 0, mb + 16);          \
      tma_ld3(wb + 18432, &fm.wr, ((256 - (k)) & 255) * 513 & ~7, 0, mb + 16); tma_ld3(wb + 27648, &fm.wi, ((256 - (k)) & 255) * 513 & ~7, 0, mb + 16); }
    if (lead) { MID_LOAD(grp, cnt); MID_LOADW(grp); }
    const int hB = w >> 2, faB = (w >> 1) & 1, xB = faB;
    const int phi = 8 * (w & 3) + g;
    const uint32_t rA = (8 * w + 2 * t) * 128 + ((g ^ (2 * t)) << 4);
    const uint32_t wA = (8 * w + g) * 128 + (((2 * t) ^ ((g & 1) | ((w & 3) << 1))) << 4);
    const uint32_t oB = (w >> 1) * 8192 + (w & 1) * 512;
    const uint32_t rB = oB + (8 * t + (g >> 2)) * 128 + (((g & 3) ^ ((g >> 2) | (t << 1)) ^ xB) << 4);
    const uint32_t wB = oB + (8 * (g >> 1) + (t >> 1)) * 128 + (((((g & 1) << 2) | (2 * (t & 1))) ^ ((t >> 1) | ((g >> 1) << 1)) ^ xB) << 4);
    const uint32_t wBi = oB + (8 * (g >> 1) + (t >> 1)) * 128 + (((((g & 1) << 2) | (2 * (t & 1))) ^ ((t >> 1) | ((w & 1) << 2))) << 4);
    const int hC = (lane >> 3) & 1, pr = 8 * (w & 3) + (lane & 7), pc = hC ? (32 - pr) & 31 : pr;
    const uint32_t aC = hC * 16384 + (pc & 1) * 8192 + (pc >> 2) * 1024 + (((((pc & 2) << 1) | (lane >> 4)) ^ (((pc >> 2) & 3) << 1) ^ (pc & 1)) << 4);
    const uint32_t g0 = wb + (t >> 1) * 144 + (32 * (t & 1) + phi) * 2, g1 = wb + 18432 + (7 - (t >> 1)) * 144 + (64 - 32 * (t & 1) - phi) * 2;
    const uint32_t wAo = (8 * w + g) * 128 + (((2 * t) ^ g) << 4);
    uint32_t wph = 0;
#pragma unroll 1
    for (int k1 = grp; k1 < 129; k1 += 8, cnt++, wph ^= 1) {
        const uint32_t buf = gb + (cnt & 1) * 32768;
        uint4 in[2][4], m[4], out[4];
        m[0] = m[1] = m[2] = lds128u(tb + FT_A8 + lane * 16);
        m[3] = negfrag(m[0]);
        mbar_wait(mb + 8 * (cnt & 1), (cnt >> 1) & 1);
#pragma unroll
        for (int q = 0; q < 2; q++)
#pragma unroll
            for (int i = 0; i < 4; i++) in[q][i] = lds128u(buf + (rA ^ ((i & 1) * 0x90)) + (i >> 1) * 8192 + q * 16384);
        __syncwarp();
#pragma unroll
        for (int q = 0; q < 2; q++) {
            dft16<false>(out, in[q], m, m);
#pragma unroll
            for (int i = 0; i < 4; i++) sts128u(buf + (wA ^ (((i ^ (i >> 1)) & 1) << 4)) + (i >> 1) * 8192 + q * 16384, out[i]);
        }
        {
            uint4 tw[4];
#pragma unroll
            for (int i = 0; i < 4; i++) {
                m[i] = lds128u(tb + (faB ? FT_B1F : FT_F16) + i * 512 + lane * 16);
                if (hB) { m[i].y ^= 0x80008000u; m[i].w ^= 0x80008000u; }
                tw[i] = lds128u(tb + FT_TWB + (w >> 1) * 2048 + i * 512 + lane * 16);
            }
            bar_sync(bar, 256);
#pragma unroll
            for (int q = 0; q < 2; q++)
#pragma unroll
                for (int i = 0; i < 4; i++) in[q][i] = lds128u(buf + (rB ^ ((i & 1) << 6)) + (i >> 1) * 4096 + q * 256);
            __syncwarp();
#pragma unroll
            for (int q = 0; q < 2; q++) {
                dft16<true>(out, in[q], m, tw);
#pragma unroll
                for (int i = 0; i < 4; i++) sts128u(buf + (wB ^ ((i & 1) << 4)) + (i >> 1) * 4096 + q * 256, out[i]);
            }
        }
        {
            const uint32_t cjm = (g & 1) ? 0x8000u : 0x80000000u;
            float4 tw[4];
#pragma unroll
            for (int i = 0; i < 4; i++) { m[i] = lds128u(tb + FT_C + i * 512 + lane * 16); tw[i] = lds128(tb + FT_TWC + ((w & 3) * 4 + i) * 512 + lane * 16); }
            if (lead && k1 + 8 < 129) { bulk_wait_read(); MID_LOAD(k1 + 8, cnt + 1); }
            __syncwarp();
            mbar_wait(mb + 16, wph);
            const uint32_t o0 = (k1 & 7) * 2, o1 = (-k1 & 7) * 2;
            if (w == 1 && lane < 16) {
                const int k2 = lane & 7, k2p = k1 ? 7 - k2 : (8 - k2) & 7;
                const uint32_t p0 = wb + (lane >> 3) * 9216 + k2 * 1152 + o0, p1 = wb + 18432 + (lane >> 3) * 9216 + k2p * 1152 + o1;
                const float sg = lane < 8 ? 0.5f : -0.5f;
                const uint32_t v = pack_bf16(0.5f * ldw(p0) + sg * ldw(p1), 0.5f * ldw(p1 + 1136) + sg * ldw(p0 + 1136));
                asm volatile("st.shared.u16 [%0], %1;" ::"r"(p0), "h"((uint16_t)v) : "memory");
                asm volatile("st.shared.u16 [%0], %1;" ::"r"(p1 + 1136), "h"((uint16_t)(v >> 16)) : "memory");
                fence_async_smem();
            }
            bar_sync(bar, 256);
#define FFT_CU 1
            constexpr int CU = FFT_CU;
#pragma unroll CU
            for (int q = 0; q < 4; q++) {
                const int k2 = 4 * (w >> 2) + q, k2p = k1 ? 7 - k2 : (8 - k2) & 7, kr = hC ? k2p : k2;
                const uint32_t a0 = buf + (aC ^ ((kr & 1) << 4)) + kr * 128;
                const uint32_t r0 = g0 + k2 * 1152 + o0, r1 = g1 + k2p * 1152 + o1;
                uint32_t x[4], y[4];
                ldsm4(x, a0); ldsm4(y, a0 ^ 32);
                float c[4][4];
#pragma unroll
                for (int i = 0; i < 4; i++) { c[i][0] = c[i][1] = c[i][2] = c[i][3] = 0.f; mma16816(c[i], x[0], x[1], x[2], x[3], m[i].x, m[i].y); }
#pragma unroll
                for (int i = 0; i < 4; i++) mma16816(c[i], y[0], y[1], y[2], y[3], m[i].z, m[i].w);
#pragma unroll
                for (int i = 0; i < 4; i++) {
                    const float2 ga = make_float2(ldw(r0 + i * 288), ldw(r0 + 9216 + i * 288));
                    const float2 gc = make_float2(ldw(r1 - i * 288), ldw(r1 + 9216 - i * 288));
                    const float tc = tw[i].z, ts = tw[i].w;
                    const float* z = c[i];
                    const float2 S = make_float2(ga.x + gc.x, ga.y - gc.y), D = make_float2(ga.x - gc.x, ga.y + gc.y);
                    const float2 u = make_float2(ts * z[0] - tc * z[3], ts * z[1] + tc * z[2]), v = make_float2(ts * z[2] - tc * z[1], ts * z[3] + tc * z[0]);
                    uint32_t* o = (i < 2 ? x : y) + 2 * (i & 1);
                    o[0] = pack_bf16(fmaf(S.x, z[0], fmaf(-S.y, z[1], fmaf(D.x, u.x, -D.y * u.y))), fmaf(S.x, z[1], fmaf(S.y, z[0], fmaf(D.x, u.y, D.y * u.x))));
                    o[1] = pack_bf16(fmaf(S.x, z[2], fmaf(-S.y, z[3], fmaf(-D.x, v.x, D.y * v.y))), fmaf(S.x, z[3], fmaf(S.y, z[2], fmaf(-D.x, v.y, -D.y * v.x))));
                }
#pragma unroll
                for (int i = 0; i < 4; i++) { c[i][0] = c[i][1] = c[i][2] = c[i][3] = 0.f; mma16816(c[i], x[0], x[1], x[2], x[3], m[i].x ^ cjm, m[i].y ^ cjm); }
#pragma unroll
                for (int i = 0; i < 4; i++) mma16816(c[i], y[0], y[1], y[2], y[3], m[i].z ^ cjm, m[i].w ^ cjm);
#pragma unroll
                for (int i = 0; i < 4; i++) {
                    uint32_t* o = (i < 2 ? x : y) + 2 * (i & 1);
                    o[0] = pack_bf16(c[i][0] * tw[i].x + c[i][1] * tw[i].y, c[i][1] * tw[i].x - c[i][0] * tw[i].y);
                    o[1] = pack_bf16(c[i][2] * tw[i].x + c[i][3] * tw[i].y, c[i][2] * tw[i].y - c[i][3] * tw[i].x);
                }
                stsm4(a0, x[0], x[1], x[2], x[3]);
                stsm4(a0 ^ 32, y[0], y[1], y[2], y[3]);
            }
        }
#pragma unroll
        for (int i = 0; i < 4; i++) { m[i] = lds128u(tb + (faB ? FT_B1I : FT_F16) + i * 512 + lane * 16); if (!faB) m[i] = conjfrag(m[i]); }
        bar_sync(bar, 256);
        if (lead && k1 + 8 < 129) MID_LOADW(k1 + 8);
        __syncwarp();
#pragma unroll
        for (int q = 0; q < 2; q++)
#pragma unroll
            for (int i = 0; i < 4; i++) in[q][i] = lds128u(buf + (rB ^ ((i & 1) << 6)) + (i >> 1) * 4096 + q * 256);
        __syncwarp();
#pragma unroll
        for (int q = 0; q < 2; q++) {
            dft16<false>(out, in[q], m, m);
#pragma unroll
            for (int i = 0; i < 4; i++) sts128u(buf + (wBi ^ ((i & 1) << 4) ^ (q << 5)) + (i >> 1) * 4096 + q * 256, out[i]);
        }
        m[0] = m[1] = m[2] = conjfrag(lds128u(tb + FT_A8 + lane * 16));
        m[3] = negfrag(m[0]);
        bar_sync(bar, 256);
#pragma unroll
        for (int q = 0; q < 2; q++)
#pragma unroll
            for (int i = 0; i < 4; i++) in[q][i] = lds128u(buf + (rA ^ ((i & 1) * 0x90)) + (i >> 1) * 8192 + q * 16384);
        __syncwarp();
#pragma unroll
        for (int q = 0; q < 2; q++) {
            dft16<false>(out, in[q], m, m);
#pragma unroll
            for (int i = 0; i < 4; i++) sts128u(buf + (wAo ^ ((i & 1) << 4)) + (i >> 1) * 8192 + q * 16384, out[i]);
        }
        fence_async_smem();
        bar_sync(bar, 256);
        if (lead) {
            tma_st3(buf, &fm.y2, 0, k1 * 8);
            if (k1 & 127) tma_st3(buf + 16384, &fm.y2, 0, (256 - k1) * 8);
            bulk_commit();
        }
    }
    if (lead) bulk_wait_all();
}

__device__ __align__(128) unsigned g_start;
__device__ __align__(128) unsigned g_fbar;
__device__ __align__(128) unsigned g_end;
__device__ __forceinline__ unsigned gbar_arrive(unsigned* c, unsigned inc, unsigned total, int lane) {
    unsigned v = 0;
    if (lane == 0) { asm volatile("fence.proxy.async;" ::: "memory"); fence_gpu(); v = atomicAdd(c, inc); }
    return (__shfl_sync(~0u, v, 0) & ~(total - 1)) + total;
}
__device__ __forceinline__ void gbar_wait(unsigned* c, unsigned target, unsigned ns) {
    uint32_t n = 0;
    while (__any_sync(~0u, (int)(ld_acquire(c) - target) < 0)) { if (ns) __nanosleep(ns); if (++n > SPIN_LIMIT) __trap(); }
    asm volatile("fence.proxy.async;" ::: "memory");
}
__device__ __forceinline__ void fft_rest(int cta, const FftMaps& fm, uint32_t sb, uint32_t opt) {
    const int hi = __shfl_sync(~0u, threadIdx.x >> 8, 0), w = __shfl_sync(~0u, (threadIdx.x >> 5) & 7, 0), lane = threadIdx.x & 31;
    unsigned target = 0;
    if (w == 4) target = gbar_arrive(&g_start, 16, 256, lane);
    if (threadIdx.x < 32) mbar_init(sb + FT_BAR + 8 * threadIdx.x, 1);
    fft_tables(sb, threadIdx.x, 512);
    fence_async_smem();
    __syncthreads();
    const int grp = cta * 2 + hi, bar = 1 + hi;
    const uint32_t gb = sb + hi * FG_SIZE, mb = sb + FT_BAR + hi * 128;
    uint32_t cnt = 0;
    if (w == 4) gbar_wait(&g_start, target, 200);
    if (w == 4 && (opt & 8192)) {
        const unsigned char* p = fm.w[2] + (size_t)(lane * 8 + grp) * 16384;
        asm volatile("cp.async.bulk.prefetch.L2.global [%0], %1;" ::"l"(p), "r"(16384) : "memory");
    }
    if (w == 4 && (opt & 4096)) {
        const unsigned char* p = fm.w[hi] + (size_t)(cta * 32 + lane) * 16416;
        asm volatile("cp.async.bulk.prefetch.L2.global [%0], %1;" ::"l"(p), "r"(16416) : "memory");
    }
    GT(1);
    fft_mid(grp, fm, sb, gb, mb, cnt, w, lane, bar);
    if (w == 4) gbar_wait(&g_fbar, gbar_arrive(&g_fbar, 1, 8, lane), 200);
    GT(2);
    fft_col<true, 16>(grp, 0, &fm.y, &fm.o, gb, mb + 64, w, lane, bar);
}

__device__ __align__(256) uint4 g_kvq[4 * 32 * 3 * 8 * 2 * 32];
__device__ __align__(256) uint2 g_alpha[2 * 32 * 3 * 8 * 2 * 32];
__device__ __align__(256) uint4 g_red[5 * 32768 / 16];
__device__ __align__(256) uint4 g_stamp[32];
__device__ __align__(256) uint4 g_qst[128 * 2];
__device__ __align__(256) bf16 g_ox[2048 * 4096];
struct Tune { uint32_t d_alpha, d_r, opt, d_q, d_v, spread, extra; };
#define OP_SPLIT 1
#define X_SEQ 24
#define OPD_EARLY 0
constexpr int RA = 2;

constexpr uint32_t SM_BASE = 1024;
constexpr uint32_t O_WO = 0;
constexpr uint32_t O_WV = 65536;
constexpr uint32_t O_XB = 131072;
constexpr uint32_t O_MEM = O_XB + 32768;
constexpr uint32_t O_RECV = O_MEM + 8192;
constexpr uint32_t O_KVQ = O_RECV + 12288;
constexpr uint32_t O_STG = O_KVQ + 18432;
constexpr uint32_t O_S = O_STG + 8192;
constexpr uint32_t O_XO = O_STG + 16384;
constexpr uint32_t O_P = O_S + 10240;
constexpr uint32_t O_O = O_P + 1536;
constexpr uint32_t O_DBG = O_O + 2048;
constexpr uint32_t O_F1 = 196608;
constexpr uint32_t O_VM = O_F1 + 32768;
constexpr uint32_t O_BAR = 232448 - 512;
constexpr uint32_t MAIN_SMEM = 232448;
static_assert(O_DBG + (DBG_TIMING ? (4 * DBG_N + 1) * 96 : 0) <= O_VM && FFT_SMEM <= MAIN_SMEM && O_VM + 2048 <= O_BAR, "smem");
constexpr int G_ST = 6;
enum { B_W = 0, B_WO = B_W + 12, B_F1, B_XP, B_XFULL, B_RFULL, B_AFULL, B_KVFULL, B_QST, B_RECV, B_GF = B_RECV + 6,
       B_QDONE = B_GF + G_ST, B_KDONE, B_XEMPTY, B_SDONE, B_SRDY, B_OPDONE, B_QX, B_GE, B_XPE = B_GE + G_ST, B_QKW, B_MEM, B_COUNT };

constexpr float SM_SCALE_LOG2 = 0.08838834764831845f * 1.4426950408889634f;
constexpr float MASK_VAL = -1.0e9f / 0.08838834764831845f;

__device__ __forceinline__ uint32_t red_grp(int grp) { return (uint32_t)((grp >> 1) * 1024 + (grp & 1) * 256); }
__host__ __device__ constexpr uint64_t xdesc(int ks) { return mkdesc(SM_BASE + O_XB + (ks >> 2) * 1024 + (ks & 3) * 32, 16, 8192, 1); }

__device__ __forceinline__ void x_split(const float* d, uint32_t (&sn)[4], uint32_t (&kp)[4], int kh) {
#pragma unroll
    for (int i = 0; i < 4; i++) {
        const uint32_t lo = pack_bf16(d[2 * i], d[2 * i + 1]), hi = pack_bf16(d[8 + 2 * i], d[8 + 2 * i + 1]);
        sn[i] = kh ? lo : hi; kp[i] = kh ? hi : lo;
    }
}
__device__ __forceinline__ void x_send(int R, const uint32_t (&sn)[4], int sg, int tid, uint32_t sb, uint32_t mate) {
    const uint32_t par = sg & 1;
    const uint32_t bar = O_BAR + 8 * (B_RECV + R * 2) + 8 * par;
    if (tid == 0) mbar_expect_tx(sb + bar, 2048);
    asm volatile("st.async.shared::cluster.mbarrier::complete_tx::bytes.v4.b32 [%0], {%1,%2,%3,%4}, [%5];"
                 ::"r"(mate + O_RECV + (par * 3 + R) * 2048 + tid * 16), "r"(sn[0]), "r"(sn[1]), "r"(sn[2]), "r"(sn[3]), "r"(mate + bar) : "memory");
}
__device__ __forceinline__ void x_wait(int R, int sg, uint32_t sb) {
    mbar_wait_cluster(sb + O_BAR + 8 * (B_RECV + R * 2) + 8 * (sg & 1), (sg >> 1) & 1);
}
template <int R>
__device__ __forceinline__ void x_finish(const uint32_t (&kp)[4], int sg, int h, int mt, int kh, int tid, uint32_t sb) {
    const uint4 r = lds128u(sb + O_RECV + ((sg & 1) * 3 + R) * 2048 + tid * 16);
    uint32_t u0 = add_bf16x2(kp[0], r.x), u1 = add_bf16x2(kp[1], r.y), u2 = add_bf16x2(kp[2], r.z), u3 = add_bf16x2(kp[3], r.w);
    if (R < 2) { u0 = movm(u0); u1 = movm(u1); u2 = movm(u2); u3 = movm(u3); }
    const uint32_t tag = ((sg >> 2) & 1) ^ 1;
    u0 = (u0 & ~1u) | tag;
    uint4* const hb = &g_kvq[((sg & 3) * 32 + h) * (3 * 512)];
    if (R == 0) {
        uint2* p = (uint2*)hb + (kh * 16 + mt) * 32 + (tid & 31);
        asm volatile("{\n.reg .pred p;\nsetp.lt.s32 p, %5, 64;\n@p st.relaxed.gpu.global.v2.b32 [%0], {%1,%2};\n@p st.relaxed.gpu.global.v2.b32 [%0+2048], {%3,%4};\n}"
                     ::"l"(p), "r"(u0), "r"(u1), "r"((u2 & ~1u) | tag), "r"(u3), "r"(sg) : "memory");
    } else {
        asm volatile("{\n.reg .pred p;\nsetp.lt.s32 p, %5, 64;\n@p st.relaxed.gpu.global.v4.b32 [%0], {%1,%2,%3,%4};\n}"
                     ::"l"(hb + R * 512 + (mt * 2 + kh) * 32 + (tid & 31)), "r"(u0), "r"(u1), "r"(u2), "r"(u3), "r"(sg) : "memory");
    }
}

__device__ __forceinline__ uint32_t convert_mem(const unsigned char* redp, int s, int kh, int jj, int w, int lane, uint32_t sb, uint32_t& sf) {
    const uint32_t off = red_grp(jj * 16 + w * 4 + (lane >> 3)), o16 = off + (lane & 7) * 16, o8 = off + 512 + ((lane >> 3) & 1) * 64 + (lane & 7) * 8;
    uint32_t ma = sb + O_MEM + (jj * 4 + (lane >> 4)) * 1024 + (lane & 7) * 128 + (((2 * w + ((lane >> 3) & 1)) ^ (lane & 7)) << 4);
    uint32_t a16 = sb + O_STG + o16, a8 = sb + O_STG + o8;
    const uint32_t target = (s & 4) ? 0x42C00000u : 0x42000000u;
    uint32_t n = 0;
    bool redo;
    KEEP2(ma, a16); KEEP2(a8, target);
#pragma unroll 1
    do {
        asm volatile("" : "+r"(n));
        if (n) {
            const unsigned char* pg = redp + (s & 3) * 32768 + kh * 16384;
            const uint4 x = ldg_rlx128(pg + o16), y = ldg_rlx128(pg + o16 + 128);
            const uint2 z = ldg_rlx64(pg + o8);
            sts128u(a16, x); sts128u(a16 + 128, y); sts64u(a8, z);
            if (n > SPIN_LIMIT) __trap();
        }
        n++;
        mbar_wait(sb + O_BAR + 8 * B_RFULL, s & 1);
        const uint4 ra = lds128u(a16), rb = lds128u(a16 + 128);
        const uint2 rc = lds64u(a8);
        stsm4t(ma, ra.x, ra.y, ra.z, __byte_perm(ra.w, rc.x, 0x5410));
        stsm4t(ma + 2048, rb.x, rb.y, rb.z, __byte_perm(rb.w, rc.x, 0x7610));
        redo = __any_sync(~0u, orx(orx2(ra.w, rb.w, target), rc.y, target) > 0xffffu);
    } while (redo);
    if (lane == 0) mbar_arrive(sb + O_BAR + 8 * B_MEM);
    fence_async_smem();
    __syncwarp();
    if (lane == 0) mbar_arrive(sb + O_BAR + 8 * B_QKW);
    return n - 1;
}

#define F16(d, o) F4(d, o), F4(d, o + 4), F4(d, o + 8), F4(d, o + 12)
__device__ __forceinline__ void wg_ss128(float (&d)[64], uint64_t da, uint64_t db, int sc) {
    asm volatile("{\n.reg .pred p;\nsetp.ne.b32 p, %66, 0;\nwgmma.mma_async.sync.aligned.m64n128k16.f32.bf16.bf16 "
                 "{%0,%1,%2,%3,%4,%5,%6,%7,%8,%9,%10,%11,%12,%13,%14,%15,%16,%17,%18,%19,%20,%21,%22,%23,%24,%25,%26,%27,%28,%29,%30,%31,"
                 "%32,%33,%34,%35,%36,%37,%38,%39,%40,%41,%42,%43,%44,%45,%46,%47,%48,%49,%50,%51,%52,%53,%54,%55,%56,%57,%58,%59,%60,%61,%62,%63}, "
                 "%64, %65, p, 1, 1, 0, 1;\n}"
                 : F16(d, 0), F16(d, 16), F16(d, 32), F16(d, 48) : "l"(da), "l"(db), "r"(sc));
}
__device__ __forceinline__ void stg_rlx32(void* p, uint32_t v) { asm volatile("st.relaxed.gpu.global.u32 [%0], %1;" ::"l"(p), "r"(v) : "memory"); }

__global__ void __cluster_dims__(2, 1, 1) __launch_bounds__(512, 1)
rmt_main(const __grid_constant__ CUtensorMap tm_x, const __grid_constant__ CUtensorMap tm_wq, const __grid_constant__ CUtensorMap tm_wk,
         const __grid_constant__ CUtensorMap tm_wv, const __grid_constant__ CUtensorMap tm_wo, const bf16* __restrict__ mem0,
         const Tune tn, const __grid_constant__ FftMaps fm, const __grid_constant__ CUtensorMap tm_o,
         const __grid_constant__ CUtensorMap tm_w2, bf16* __restrict__ out) {
    extern __shared__ __align__(1024) unsigned char smem_raw[];
    const uint32_t sb = smem_u32(smem_raw);
    if ((sb & 0x3FFFF) != SM_BASE) __trap();
    GT(6);
    const int cid = blockIdx.x >> 1, kh = blockIdx.x & 1;
    const int tpc = cid < 4 ? 62 + cid : cid - 4;
    int h, nh;
    if (tpc < 32) { h = (tpc >> 4) * 8 + (tpc & 7); nh = (tpc >> 3) & 1; }
    else if (tpc < 60) { int u = tpc - 32, r = u % 14; h = 16 + (u / 14) * 7 + r % 7; nh = r / 7; }
    else if (tpc < 62) { GT(0); fft_rest((tpc - 60) * 2 + kh, fm, sb, tn.opt); GT(3); return; }
    else { h = 30 + ((tpc - 62) >> 1); nh = tpc & 1; }
    const int j = nh * 2 + kh, role = h * 4 + j;
    const int wgi = __shfl_sync(~0u, threadIdx.x >> 7, 0);
    const int w = __shfl_sync(~0u, (threadIdx.x >> 5) & 3, 0);
    const int tid = threadIdx.x & 127, lane = tid & 31;
#define PIN_IDS() const int tid = __shfl_sync(~0u, threadIdx.x & 127, threadIdx.x & 31), lane = tid & 31
#define OPAQUE_IDS() int tid_ = tid; asm volatile("" : "+r"(tid_)); const int tid = tid_, lane = tid_ & 31; (void)lane
    unsigned char* const redp = (unsigned char*)(((uintptr_t)g_red + 32767) & ~(uintptr_t)32767);
    const uint32_t bars = sb + O_BAR;

    if (threadIdx.x < B_COUNT) {
        const int i = threadIdx.x;
        mbar_init(bars + 8 * i, i < B_QDONE ? 1 : i < B_GE ? 4 : i < B_XPE ? 8 : i < B_QKW ? 12 : 16);
        asm volatile("fence.mbarrier_init.release.cluster;" ::: "memory");
        fence_async_smem();
    } else if (threadIdx.x >= 64 && threadIdx.x < 71) {
        const int i = threadIdx.x - 64;
        const CUtensorMap* m = i == 0 ? &tm_wk : i == 1 ? &tm_wq : i == 2 ? &fm.x : i == 3 ? &tm_x : i == 4 ? &tm_wv : i == 5 ? &tm_wo : &fm.y;
        asm volatile("prefetch.tensormap [%0];" ::"l"(m) : "memory");
    }
    __syncthreads();
    const int wc0 = h * 128 + nh * 64;
#define W_LOAD(i)                                                                                                     \
    if (lane == 0) {                                                                                                  \
        mbar_expect_tx(bars + 8 * (B_W + (i)), 16384);                                                                \
        tma2d(sb + ((i) < 4 ? O_XB : (i) < 8 ? O_WO : O_WV) + ((i) & 3) * 16384, (i) < 4 ? &tm_wk : (i) < 8 ? &tm_wq : &tm_wv, \
              wc0, kh * 512 + ((i) & 3) * 128, bars + 8 * (B_W + (i)));                                               \
    }
    const int depth = (tn.opt >> 8) & 15, nearly = 8 + ((tn.opt >> 4) & 7);
    if (wgi == 0 && w == 3) {
        if (lane == 0) {
            mbar_expect_tx(bars + 8 * B_F1, 32768);
            tma_ld4(sb + O_F1, &fm.x, (role & 15) * 64, role >> 4, bars + 8 * B_F1);
        }
#pragma unroll 1
        for (int i = 0; i < nearly; i++) {
            if (i == depth - 2) mbar_wait(bars + 8 * B_F1, 0);
            if (i >= depth) mbar_wait(bars + 8 * (B_W + i - depth), 0);
            W_LOAD(i);
        }
    } else if (wgi == 1 && w == 2 && lane == 0 && role < 2 * (RA + 3)) tma4d_prefetch(&tm_x, kh * 8, (role >> 1) * 4);
    GT(7);
    uint32_t mate;
    asm volatile("mapa.shared::cluster.u32 %0, %1, %2;" : "=r"(mate) : "r"(sb), "r"(kh ^ 1));
    if (wgi >= 2) fft_col<false, 1>(role >> 4, role & 15, &fm.x, &fm.y, sb + O_F1, bars + 8 * B_F1, (wgi - 2) * 4 + w, lane, 6);

    if (wgi < 2) {
        asm volatile("setmaxnreg.inc.sync.aligned.u32 176;");
        PIN_IDS();
        uint32_t a[32][4], sf = 0;
        {
            const uint32_t stage = sb + (wgi == 0 ? O_WO : O_XB);
            const uint32_t ad = stage + (((lane >> 4) & 1) * 8 + (lane & 7)) * 128 + (((2 * w + ((lane >> 3) & 1)) ^ (lane & 7)) << 4);
#pragma unroll
            for (int i = 0; i < 4; i++) {
                mbar_wait(bars + 8 * (B_W + 4 * (wgi ^ 1) + i), 0);
#pragma unroll
                for (int ks = 0; ks < 8; ks++) ldsm4t(a[i * 8 + ks], ad + (i * 8 + ks) * 2048);
            }
#pragma unroll
            for (int ks = 0; ks < 32; ks += 2) KEEP2(a[ks][0], a[ks + 1][0]);
            SCHED_FENCE();
            if (lane == 0) mbar_arrive(bars + 8 * (B_QDONE + wgi));
            if (wgi == 0) GT(10); else GT(11);
        }
        asm volatile("barrier.cluster.arrive.relaxed.aligned;" ::: "memory");
        asm volatile("barrier.cluster.wait.acquire.aligned;" ::: "memory");
        uint32_t kp[4];
#define X_PASS(d, dofs)                                                                                    \
        wg_fence();                                                                                        \
        _Pragma("unroll") for (int ks = 0; ks < 32; ks++) { if (ks == 0) wg_rs32<0>(d, a[ks], xdesc(ks) + (dofs)); else wg_rs32<1>(d, a[ks], xdesc(ks) + (dofs)); } \
        wg_commit();                                                                                       \
        wg_wait<0>();
#define X_FINISH(sg) { if (wgi == 0) x_finish<0>(kp, sg, h, nh * 4 + w, kh, tid, sb); else x_finish<1>(kp, sg, h, nh * 4 + w, kh, tid, sb); }
        mbar_wait(bars + 8 * B_XP, 0);
        if (wgi == 0) GT(8);
#pragma unroll 1
        for (int sg = 0; sg < RA; sg++) {
            float d[16]; uint32_t sn[4];
            X_PASS(d, sg * 2048 - (int)((O_XB - O_WO) >> 4));
            if (sg > 0) {
                if (lane == 0) mbar_arrive(bars + 8 * B_XPE);
                x_wait(wgi, sg - 1, sb); X_FINISH(sg - 1);
            }
            x_split(d, sn, kp, kh);
            x_send(wgi, sn, sg, tid, sb, mate);
        }
        const int lq = wgi == 0 ? 4 : 0;
#pragma unroll 1
        for (int s = 0; s < 64; s++) {
            TSI(s);
            {
                float d[16]; uint32_t sn[4], kc[4];
                x_wait(wgi, s + RA - 1, sb);
                mbar_wait(bars + 8 * B_XFULL, s & 1);
                if (wgi == 1) {
                    mbar_wait(bars + 8 * B_OPDONE, s & 1);
                    x_finish<1>(kp, s + RA - 1, h, nh * 4 + w, kh, tid, sb);
                    TS(5);
                    mbar_wait(bars + 8 * B_QX, s & 1);
                } else mbar_wait(bars + 8 * B_OPDONE, s & 1);
                TS(6);
                wg_fence();
#pragma unroll
                for (int ks = 0; ks < 32; ks++) {
                    if (ks == 0) wg_rs32<0>(d, a[ks], xdesc(ks)); else wg_rs32<1>(d, a[ks], xdesc(ks));
                    if (ks == X_SEQ - 1) wg_commit();
                }
                wg_commit();
                wg_wait<1>();
                if (tid < lq) mbar_arrive(bars + 8 * B_QX);
                wg_wait<0>();
                TS(7);
                x_split(d, sn, kc, kh);
                x_send(wgi, sn, s + RA, tid, sb, mate);
                TS(4);
                if (wgi == 0) { x_finish<0>(kp, s + RA - 1, h, nh * 4 + w, kh, tid, sb); TS(5); }
#pragma unroll
                for (int i = 0; i < 4; i++) kp[i] = kc[i];
            }
            uint2* ap = &g_alpha[((s & 1) * 32 + h) * (3 * 512) + wgi * 512 + ((nh * 4 + w) * 2 + kh) * 32 + lane];
            uint32_t mb0 = sb + O_MEM + (lane & 7) * 128 + (((lane >> 3) ^ (lane & 7)) << 4), mb1 = mb0 ^ 64;
            const uint32_t tag = ((s >> 1) & 1) ^ 1;
            KEEP2(mb0, mb1); KEEPP(ap);
            float e[2][4];
#pragma unroll
            for (int i = 0; i < 4; i++) e[0][i] = e[1][i] = 0.f;
            if (lane == 0) mbar_arrive(bars + 8 * B_MEM);
            mbar_wait(bars + 8 * B_MEM, s & 1);
            TS(0);
#pragma unroll
            for (int ks = 0; ks < 32; ks += 2) {
                uint32_t b[4];
                ldsm4(b, ((ks & 2) ? mb1 : mb0) + (ks >> 2) * 1024);
                mma16816(e[0], a[ks][0], a[ks][1], a[ks][2], a[ks][3], b[0], b[1]);
                mma16816(e[1], a[ks + 1][0], a[ks + 1][1], a[ks + 1][2], a[ks + 1][3], b[2], b[3]);
            }
            TS(2);
            uint32_t u0 = pack_bf16(e[0][0] + e[1][0], e[0][1] + e[1][1]), u1 = pack_bf16(e[0][2] + e[1][2], e[0][3] + e[1][3]);
            u0 = movm(u0); u1 = movm(u1);
            SCHED_FENCE();
            if (lane == 0) mbar_arrive(bars + 8 * B_QKW);
            stg_rlx64(ap, (u0 & ~1u) | tag, u1);
            TS(3);
            if (wgi == 1) {
                const uint2* vp = &g_alpha[((s & 1) * 32 + h) * (3 * 512) + 1024 + w * 128 + lane];
                const uint32_t vs = sb + O_VM + tid * 16;
                KEEPP(vp); KEEP2(vs, 0);
                mbar_wait(bars + 8 * B_QST, s & 1);
                uint32_t n, bad;
                asm volatile("ld.shared.u32 %0, [%1];" : "=r"(n) : "r"(bars + 504) : "memory");
                wait_gtime(n + tn.d_v);
                TS(8);
                n = 0;
                do {
                    uint2 va[4];
#pragma unroll
                    for (int i = 0; i < 4; i++) va[i] = ldg_rlx64(vp + i * 32);
                    if (++n > SPIN_LIMIT) __trap();
                    bad = (orx2(va[0].x, va[1].x, tag) | orx2(va[2].x, va[3].x, tag)) & 1;
                    sts128u(vs, make_uint4((add_bf16x2(va[0].x, va[1].x) & ~1u) | ((~s ^ bad) & 1), add_bf16x2(va[0].y, va[1].y),
                                                             add_bf16x2(va[2].x, va[3].x), add_bf16x2(va[2].y, va[3].y)));
                } while (__any_sync(~0u, bad));
                TS(9);
                TSV(16 + w, n - 1);
                LT(s, 4 + w, n - 1);
            }
        }
        x_wait(wgi, 63 + RA, sb);
        sts32(bars + 508, sf);
        TSDUMP();
        asm volatile("bar.arrive 7, 512;" ::: "memory");
        float d[64];
        int st = 0, ph = 0;
#pragma unroll 1
        for (int kt = 0; kt < 64; kt++) {
            mbar_wait(bars + 8 * (B_GF + st), ph);
            if (kt == 0) GT(4);
            const uint64_t da = mkdesc(SM_BASE + st * 32768 + wgi * 8192, 16, 1024, 1), db = mkdesc(SM_BASE + st * 32768 + 16384, 8192, 1024, 1);
            wg_fence();
#pragma unroll
            for (int k = 0; k < 4; k++) wg_ss128(d, da + k * 2, db + k * 128, kt | k);
            wg_commit();
            if (kt > 0) {
                wg_wait<1>();
                if (lane == 0) mbar_arrive(bars + 8 * (B_GE + (st == 0 ? G_ST - 1 : st - 1)));
            }
            if (++st == G_ST) { st = 0; ph ^= 1; }
        }
        wg_wait<0>();
        {
            const uint32_t sl = sb + O_F1 + (wgi * 4 + w) * 4096;
#pragma unroll
            for (int i = 0; i < 8; i++)
                stsm4(sl + (lane & 15) * 256 + (((2 * i + (lane >> 4)) ^ (lane & 7)) << 4), pack_bf16(d[8 * i], d[8 * i + 1]),
                      pack_bf16(d[8 * i + 2], d[8 * i + 3]), pack_bf16(d[8 * i + 4], d[8 * i + 5]), pack_bf16(d[8 * i + 6], d[8 * i + 7]));
            __syncwarp();
            bf16* op = out + (size_t)((role >> 3) * 128 + wgi * 64 + w * 16 + (lane >> 4)) * 2048 + 1024 + (role & 7) * 128 + (lane & 15) * 8;
#pragma unroll
            for (int i = 0; i < 8; i++) {
                const int r = 2 * i + (lane >> 4);
                const uint4 v = lds128u(sl + r * 256 + (((lane & 15) ^ (r & 7)) << 4));
                stg128(op + (size_t)i * 4096, v.x, v.y, v.z, v.w);
            }
        }
        GT(5);
    } else if (wgi == 2) {
        asm volatile("setmaxnreg.dec.sync.aligned.u32 64;");
        PIN_IDS();
        asm volatile("barrier.cluster.arrive.relaxed.aligned;" ::: "memory");
#define X_LOAD(dst, sg, bar) tma4d(sb + (dst), &tm_x, kh * 8, ((sg) & 63) * 4, bars + 8 * (bar))
        if (w == 0) {
            mbar_wait(bars + 8 * B_KDONE, 0);
            if (lane == 0) { mbar_expect_tx(bars + 8 * B_XFULL, 32768); X_LOAD(O_XB, RA, B_XFULL); }
            mbar_wait(bars + 8 * B_QDONE, 0);
            if (lane == 0) { mbar_expect_tx(bars + 8 * B_XP, 65536); X_LOAD(O_WO, 0, B_XP); X_LOAD(O_WO + 32768, 1, B_XP); }
#pragma unroll 1
            for (int i = nearly; i < 12; i++) { mbar_wait(bars + 8 * (B_W + i - depth), 0); W_LOAD(i); }
        }
        asm volatile("barrier.cluster.wait.acquire.aligned;" ::: "memory");
#pragma unroll 1
        for (int i = 8; i < 12; i++) mbar_wait(bars + 8 * (B_W + i), 0);
        GT(12);
        uint32_t sf = 0, tref = gtime() - 4000;
#define V_PASS(d, dofs)                                                                                    \
        wg_fence();                                                                                        \
        _Pragma("unroll") for (int ks = 0; ks < 32; ks++) {                                                \
            constexpr uint64_t da0 = mkdesc(SM_BASE + O_WV, 16, 1024, 1);                                  \
            if (ks == 0) wg_ss40<0>(d, da0 + ks * 128, xdesc(ks) + (dofs)); else wg_ss40<1>(d, da0 + ks * 128, xdesc(ks) + (dofs)); \
        }                                                                                                  \
        wg_commit();                                                                                       \
        wg_wait<0>();
        mbar_wait(bars + 8 * B_XP, 0);
        {
            uint32_t kp[4];
#pragma unroll 1
            for (int sg = 0; sg <= RA; sg++) {
                float d[20]; uint32_t sn[4];
                if (sg < RA) {
#pragma unroll
                    for (int i = 0; i < 20; i++) d[i] = 0.f;
#pragma unroll 1
                    for (int kb = 0; kb < 8; kb++) {
                        const uint64_t da = mkdesc(SM_BASE + O_WV, 16, 1024, 1) + kb * 512, db = mkdesc(SM_BASE + O_WO, 16, 8192, 1) + sg * 2048 + kb * 64;
                        wg_fence();
#pragma unroll
                        for (int i = 0; i < 4; i++) wg_ss40<1>(d, da + i * 128, db + i * 2);
                        wg_commit();
                    }
                    wg_wait<0>();
                }
                if (sg == RA - 1) {
                    if (lane == 0) mbar_arrive(bars + 8 * B_XPE);
                    if (w == 0) {
                        mbar_wait(bars + 8 * B_XPE, 0);
                        GT(9);
                        if (lane == 0) {
                            mbar_expect_tx(bars + 8 * B_WO, 65536);
#pragma unroll
                            for (int i = 0; i < 4; i++) tma2d(sb + O_WO + i * 16384, &tm_wo, j * 256 + i * 64, h * 128, bars + 8 * B_WO);
                        }
                    }
                }
                if (sg > 0) { x_wait(2, sg - 1, sb); x_finish<2>(kp, sg - 1, h, nh * 4 + w, kh, tid, sb); }
                if (sg < RA) { x_split(d, sn, kp, kh); x_send(2, sn, sg, tid, sb, mate); }
            }
        }
#pragma unroll 1
        for (int s = 0; s < 64; s++) {
            TSI(s);
            OPAQUE_IDS();
            uint2* ap = &g_alpha[((s & 1) * 32 + h) * (3 * 512) + 1024 + ((nh * 4 + w) * 2 + kh) * 32 + lane];
            KEEPP(ap);
            float d[20];
            mbar_wait(bars + 8 * B_QKW, s & 1);
            TS(0);
            if (s == 0) GT(14);
            V_PASS(d, 0);
            TS(1);
            stg_rlx64(ap, (pack_bf16(d[16], d[17]) & ~1u) | (((s >> 1) & 1) ^ 1), pack_bf16(d[18], d[19]));
            if (lane == 0) mbar_arrive(bars + 8 * B_XEMPTY);
            if (s == 63) break;
            uint32_t sn[4], kp[4];
            x_split(d, sn, kp, kh);
            if (w == 3) {
                uint32_t n = 0, mx, mn;
                do {
                    const uint4 st = ldg_rlx128(&g_stamp[lane]);
                    mx = __reduce_max_sync(~0u, max(max(st.x - tref, st.y - tref), max(st.z - tref, st.w - tref)));
                    mn = __reduce_min_sync(~0u, min(min(st.x - tref, st.y - tref), min(st.z - tref, st.w - tref)));
                } while (mx >= 200000u && ++n < 64);
                tref = mx < 200000u ? tref + mx + (mx - mn > tn.spread ? tn.extra : 1) : gtime();
                TSV(12, clk()); TSV(13, n); TSV(14, mx - mn);
            }
            if (tn.opt & 1) { mbar_wait(bars + 8 * B_SDONE, s & 1); x_send(2, sn, s + RA, tid, sb, mate); }
            if (w == 0) {
                mbar_wait(bars + 8 * B_XEMPTY, s & 1);
                mbar_wait(bars + 8 * ((tn.opt & 2) ? B_SRDY : B_SDONE), s & 1);
                if (lane == 0) {
                    mbar_expect_tx(bars + 8 * B_XFULL, 32768);
                    X_LOAD(O_XB, s + RA + 1, B_XFULL);
                }
                mbar_wait(bars + 8 * B_SRDY, s & 1);
                if (lane == 0) {
                    const uint4* hb = &g_kvq[(((s + 1) & 3) * 32 + h) * (3 * 512)];
                    mbar_expect_tx(bars + 8 * B_KVFULL, 18432);
                    bulk_g2s(sb + O_KVQ, hb + 512, 16384, bars + 8 * B_KVFULL);
                    bulk_g2s(sb + O_KVQ + 16384, hb + j * 128, 2048, bars + 8 * B_KVFULL);
                    if (!(tn.opt & 16384) && nh == 0 && ((h ^ s) & 7) == 0 && s < 61 - RA) tma4d_prefetch(&tm_x, kh * 8, (s + RA + 3) * 4);
                }
            }
            mbar_wait(bars + 8 * B_OPDONE, (s + 1) & 1);
            if (!(tn.opt & 1)) x_send(2, sn, s + RA, tid, sb, mate);
            if (w == 3) {
                wait_gtime(tref + tn.d_r);
                if (lane == 0) {
                    mbar_expect_tx(bars + 8 * B_RFULL, 16384);
                    bulk_g2s(sb + O_STG, redp + (s & 3) * 32768 + kh * 16384, 16384, bars + 8 * B_RFULL);
                }
                TSV(3, clk());
            }
            x_wait(2, s + RA, sb);
            const bool late = w == 3 || (tn.opt & 4);
            if (!late) { x_finish<2>(kp, s + RA, h, nh * 4 + w, kh, tid, sb); TS(6); }
            if (DBG_TIMING && w == 0) { mbar_wait(bars + 8 * B_RFULL, s & 1); TS(4); }
            const uint32_t n = convert_mem(redp, s, kh, 0, w, lane, sb, sf); (void)n;
            TS(5);
            TSV(8 + w, n);
            LT(s, 8 + w, n);
            if (late) x_finish<2>(kp, s + RA, h, nh * 4 + w, kh, tid, sb);
        }
        sts32(bars + 508, sf);
        TSDUMP();
        asm volatile("bar.arrive 7, 512;" ::: "memory");
    } else {
        asm volatile("setmaxnreg.dec.sync.aligned.u32 96;");
        PIN_IDS();
        GT(0);
        asm volatile("barrier.cluster.arrive.relaxed.aligned;" ::: "memory");
#define RED_CLEAR(st)                                                                                           \
        if (lane < 16) {                                                                                        \
            const uint32_t cb = ((st) & 4) ? 0x42800000u : 0u;                                                  \
            stg128(redp + ((st) & 3) * 32768 + role * 256 + lane * 16, 0, (role & 2) ? cb : 0u, 0, cb);        \
        }
        if (w == 0) {
            RED_CLEAR(0); RED_CLEAR(1); RED_CLEAR(2);
            if (lane == 0) { tma_st4(sb + O_F1, &fm.y, (role & 15) * 64, role >> 4); bulk_commit(); }
        }
        sts128u(sb + O_VM + tid * 16, make_uint4(0, 0, 0, 0));
        {
            uint4 v[4];
#pragma unroll
            for (int q = 0; q < 4; q++) v[q] = *(const uint4*)(mem0 + ((lane >> 3) + (q & 1) * 4) * 1024 + kh * 512 + (2 * w + (q >> 1)) * 64 + (lane & 7) * 8);
            mbar_wait(bars + 8 * B_KDONE, 0);
#pragma unroll
            for (int q = 0; q < 4; q++) {
                const int row = (lane >> 3) + (q & 1) * 4;
                sts128u(sb + O_MEM + (2 * w + (q >> 1)) * 1024 + row * 128 + (((lane & 7) ^ row) << 4), v[q]);
            }
            fence_async_smem();
            __syncwarp();
            if (lane < 2) { mbar_arrive(bars + 8 * B_MEM); mbar_arrive(bars + 8 * B_QKW); }
            if (lane == 0) mbar_arrive(bars + 8 * B_OPDONE);
            if (tid == 0) mbar_arrive(bars + 8 * B_KVFULL);
        }
        asm volatile("barrier.cluster.wait.acquire.aligned;" ::: "memory");
        if (w == 0) {
            if (lane == 0) bulk_wait_all();
            __syncwarp();
            gbar_wait(&g_start, gbar_arrive(&g_start, 1, 256, lane), 0);
            GT(13);
        }
        if (w == 1) {
            mbar_wait(bars + 8 * (B_W + 10), 0);
            uint32_t t = gtime();
#pragma unroll 1
            for (int i = 0; i < 4; i++) { if (lane == 0) tma2d_prefetch(&tm_wo, j * 256 + i * 64, h * 128); t += tn.extra; if (i < 3) wait_gtime(t); }
        }
        bar_sync(1, 128);
        uint32_t sf = 0;
#pragma unroll 1
        for (int s = 0; s < 64; s++) {
            TSI(s);
            OPAQUE_IDS();
            uint4 kf[4]; uint2 qf[2];
            const uint32_t tg = ((s >> 2) & 1) ^ 1;
            {
                const uint32_t ka = sb + O_KVQ + w * 2048 + lane * 16, qa = sb + O_KVQ + 16384 + w * 512 + lane * 8;
                uint32_t n = s == 0;
                bool redo;
#pragma unroll 1
                do {
                    asm volatile("" : "+r"(n));
                    if (n) {
                        const uint4* hb = &g_kvq[((s & 3) * 32 + h) * (3 * 512)];
                        uint4 y[4];
                        do {
#pragma unroll
                            for (int i = 0; i < 4; i++) { kf[i] = ldg_rlx128(hb + 512 + w * 128 + i * 32 + lane); y[i] = ldg_rlx128(hb + 1024 + w * 128 + i * 32 + lane); }
#pragma unroll
                            for (int u = 0; u < 2; u++) qf[u] = ldg_rlx64((const uint2*)hb + j * 256 + (2 * w + u) * 32 + lane);
                            if (++n > SPIN_LIMIT) __trap();
                        } while (__any_sync(~0u, (orx2(y[0].x, y[1].x, tg) | orx2(y[2].x, y[3].x, tg)) & 1));
#pragma unroll
                        for (int i = 0; i < 4; i++) { sts128u(ka + i * 512, kf[i]); sts128u(ka + 8192 + i * 512, y[i]); }
#pragma unroll
                        for (int u = 0; u < 2; u++) sts64u(qa + u * 256, qf[u]);
                        fence_async_smem();
                    }
                    n++;
                    mbar_wait(bars + 8 * B_KVFULL, s & 1);
#pragma unroll
                    for (int i = 0; i < 4; i++) kf[i] = lds128u(ka + i * 512);
#pragma unroll
                    for (int u = 0; u < 2; u++) qf[u] = lds64u(qa + u * 256);
                    redo = __any_sync(~0u, or3(orx2(kf[0].x, kf[1].x, tg), orx2(kf[2].x, kf[3].x, tg), orx2(qf[0].x, qf[1].x, tg)) & 1);
                } while (redo);
                if (w == 0) TSV(22, n - 1);
            }
            TS(9);
            if (s == 0) GT(15);
            if (s > 0) {
                const uint32_t n = convert_mem(redp, s - 1, kh, 1, w, lane, sb, sf); (void)n;
                TS(11);
                TSV(16 + w, n);
                LT(s - 1, 12 + w, n);
                if (w == 1 && s < 62) RED_CLEAR(s + 2);
            }
            const uint32_t tag = ((s >> 1) & 1) ^ 1;
            const uint2* ap = &g_alpha[((s & 1) * 32 + h) * (3 * 512) + w * 128 + lane];
            const uint32_t l16 = sb + lane * 16, l4 = sb + lane * 4;
            const uint32_t sw = l16 + O_S + w * 2560, sr = l4 + O_S + w * 128;
            uint32_t pw = sb + O_P + ((lane >> 1) & 1) * 704 + (2 * w + (lane >> 4)) * 16 + ((lane >> 2) & 3) * 4 + (lane & 1) * 2;
            int lim = (lane & 2) ? 8 * j + 2 * w + (lane >> 4) - 2 * ((lane >> 2) & 3) - (lane & 1) : 64;
            uint32_t aa = sb + O_STG + w * 1024 + lane * 8;
            KEEP2(l16, l4); KEEP2(pw, lim); KEEP2(aa, tag);
            TS(0);
            if (w == 0) {
                mbar_wait(bars + 8 * B_MEM, s & 1);
                uint32_t tq = gtime();
                if (lane < 9) stg_rlx32(lane < 8 ? (uint32_t*)g_qst + role * 8 + lane : (uint32_t*)g_stamp + role, tq);
                wait_clk(clk(), tn.d_q);
                uint32_t n = 0, mx;
                do { mx = __reduce_max_sync(~0u, ldg_rlx32((const uint32_t*)g_qst + h * 32 + lane) - (tq - 1024)); } while (mx > 100000u && ++n < 16);
                TSV(13, n);
                LT(s, 2, n);
                if (mx <= 100000u) tq += mx - 1024;
                if (lane == 0) { sts32(bars + 504, tq); mbar_arrive(bars + 8 * B_QST); }
                TS(14);
                mbar_wait(bars + 8 * B_QKW, s & 1);
                TS(1);
                wait_gtime(tq + tn.d_alpha);
                if (lane == 0) {
                    mbar_expect_tx(bars + 8 * B_AFULL, 8192);
                    bulk_g2s(sb + O_STG, ap, 8192, bars + 8 * B_AFULL);
                }
                if (s == 0) { mbar_wait(bars + 8 * B_WO, 0); GT(1); }
            }
            {
                uint32_t n = 0;
                bool redo;
#pragma unroll 1
                do {
                    asm volatile("" : "+r"(n));
                    if (n) {
                        uint2 x[8];
#pragma unroll
                        for (int q = 0; q < 8; q++) x[q] = ldg_rlx64(ap + (q >> 2) * 512 + (q & 3) * 32);
#pragma unroll
                        for (int q = 0; q < 8; q++) sts64u(aa + (q >> 2) * 4096 + (q & 3) * 256, x[q]);
                        if (n > SPIN_LIMIT) __trap();
                    }
                    n++;
                    mbar_wait(bars + 8 * B_AFULL, s & 1);
                    TS(12);
                    uint2 qa[4], ka[4];
#pragma unroll
                    for (int i = 0; i < 4; i++) qa[i] = lds64u(aa + i * 256);
#pragma unroll
                    for (int i = 0; i < 4; i++) ka[i] = lds64u(aa + 4096 + i * 256);
                    float sa[5][4];
#pragma unroll
                    for (int i = 0; i < 5; i++) sa[i][0] = sa[i][1] = sa[i][2] = sa[i][3] = 0.f;
#pragma unroll
                    for (int u = 0; u < 2; u++) {
                        const uint32_t q0 = add_bf16x2(qa[2 * u].x, qa[2 * u + 1].x), q1 = add_bf16x2(qa[2 * u].y, qa[2 * u + 1].y);
                        mma16816(sa[1], q0, qf[u].x, q1, qf[u].y, kf[2 * u].x, kf[2 * u].y);
                        mma16816(sa[2], q0, qf[u].x, q1, qf[u].y, kf[2 * u].z, kf[2 * u].w);
                        mma16816(sa[3], q0, qf[u].x, q1, qf[u].y, kf[2 * u + 1].x, kf[2 * u + 1].y);
                        mma16816(sa[4], q0, qf[u].x, q1, qf[u].y, kf[2 * u + 1].z, kf[2 * u + 1].w);
                        const uint32_t k0 = add_bf16x2(ka[2 * u].x, ka[2 * u + 1].x), k1 = add_bf16x2(ka[2 * u].y, ka[2 * u + 1].y);
                        mma16816(sa[0], q0, qf[u].x, q1, qf[u].y, k0, k1);
                        if (u == 0) SCHED_FENCE();
                    }
                    redo = __any_sync(~0u, or3(orx2(qa[0].x, ka[0].x, tag), orx2(qa[1].x, ka[1].x, tag),
                                               orx(orx(orx2(qa[2].x, ka[2].x, tag), qa[3].x, tag), ka[3].x, tag)) & 1);
#pragma unroll
                    for (int i = 1; i <= 5; i++) sts128(sw + (i % 5) * 512, sa[i % 5][0], sa[i % 5][1], sa[i % 5][2], sa[i % 5][3]);
                } while (redo);
                if (w == 0) TSV(20, n - 1);
            }
            TS(2);
            bar_sync(1, 128);
            float sc[5];
            {
                float x[4][5];
#pragma unroll
                for (int q = 0; q < 4; q++)
#pragma unroll
                    for (int n = 0; n < 5; n++) asm volatile("ld.shared.f32 %0, [%1];" : "=f"(x[q][n]) : "r"(sr + q * 2560 + n * 512) : "memory");
                if (lane == 0) mbar_arrive(bars + 8 * B_SDONE);
#pragma unroll
                for (int n = 0; n < 5; n++) sc[n] = (x[0][n] + x[1][n]) + (x[2][n] + x[3][n]);
            }
            TS(15);
#pragma unroll
            for (int n = 1; n < 5; n++) if (8 * (n - 1) > lim) sc[n] = MASK_VAL;
            float m = fmaxf(fmaxf(fmaxf(sc[0], sc[1]), fmaxf(sc[2], sc[3])), sc[4]);
            m = fmaxf(m, __shfl_xor_sync(~0u, m, 1));
            m = fmaxf(m, __shfl_xor_sync(~0u, m, 4));
            m = fmaxf(m, __shfl_xor_sync(~0u, m, 8));
            SCHED_FENCE();
            uint4 vf[4];
#pragma unroll
            for (int i = 0; i < 4; i++) vf[i] = lds128u(l16 + O_KVQ + 8192 + w * 2048 + i * 512);
            m *= -SM_SCALE_LOG2;
#pragma unroll
            for (int n = 0; n < 5; n++) {
                const uint32_t pv = pack_bf16(ex2(fmaf(sc[n], SM_SCALE_LOG2, m)), 0.f);
                asm volatile("st.shared.u16 [%0], %1;" ::"r"(pw + n * 128), "h"((uint16_t)pv) : "memory");
            }
            KEEP2(vf[0].x, vf[1].x); KEEP2(vf[2].x, vf[3].x);
            SCHED_FENCE();
            bar_sync(1, 128);
            TS(3);
            if (lane == 0) mbar_arrive(bars + 8 * B_SRDY);
            float ox[2][4], sm[4], sx[4], cc[4][4];
            unsigned char *pa, *pb;
#pragma unroll 1
            for (uint32_t nv = 0;; nv++) {
                uint32_t pf[4], p0, px[4], px0;
                ldsm4(pf, l16 + O_P + 128);
                ldsm4(px, l16 + O_P + 128 + 704);
                asm volatile("ld.shared.u32 %0, [%1];" : "=r"(p0) : "r"(l4 + O_P) : "memory");
                asm volatile("ld.shared.u32 %0, [%1];" : "=r"(px0) : "r"(l4 + O_P + 704) : "memory");
                float o[2][4];
#pragma unroll
                for (int i = 0; i < 4; i++) o[0][i] = o[1][i] = ox[0][i] = ox[1][i] = sm[i] = sx[i] = 0.f;
                constexpr uint32_t ONE2 = 0x3f803f80u;
                mma1688(sm, ONE2, ONE2, p0);
                mma1688(sx, ONE2, ONE2, px0);
#pragma unroll
                for (int c = 0; c < 2; c++) {
#pragma unroll
                    for (int u = 0; u < 2; u++) mma16816(o[u], vf[2 * u + c].x, vf[2 * u + c].y, vf[2 * u + c].z, vf[2 * u + c].w, pf[2 * c], pf[2 * c + 1]);
#pragma unroll
                    for (int u = 0; u < 2; u++) mma16816(ox[u], vf[2 * u + c].x, vf[2 * u + c].y, vf[2 * u + c].z, vf[2 * u + c].w, px[2 * c], px[2 * c + 1]);
                    mma16816(sm, ONE2, ONE2, ONE2, ONE2, pf[2 * c], pf[2 * c + 1]);
                    mma16816(sx, ONE2, ONE2, ONE2, ONE2, px[2 * c], px[2 * c + 1]);
                }
                const uint32_t vbad = orx(orx(orx2(vf[0].x, vf[1].x, tg), vf[2].x, tg), vf[3].x, tg);
                uint4 vm;
                {
                    uint32_t n = 0;
                    bool redo;
#pragma unroll 1
                    do {
                        vm = lds128v(l16 + O_VM + w * 512);
                        float o2[2][4];
#pragma unroll
                        for (int i = 0; i < 4; i++) { o2[0][i] = o[0][i]; o2[1][i] = o[1][i]; }
                        mma1688(o2[0], vm.x, vm.y, p0);
                        mma1688(o2[1], vm.z, vm.w, p0);
                        redo = __any_sync(~0u, ((vm.x ^ ~s) & 1) && ++n < SPIN_LIMIT);
                        const uint32_t oa = l4 + O_O + w * 512;
                        sts32(oa, pack_bf16(o2[0][0], o2[0][1]));
                        sts32(oa + 128, pack_bf16(o2[0][2], o2[0][3]));
                        sts32(oa + 256, pack_bf16(o2[1][0], o2[1][1]));
                        sts32(oa + 384, pack_bf16(o2[1][2], o2[1][3]));
                    } while (redo);
                    if (w == 0) TSV(21, n);
                }
                TS(4);
                fence_async_smem();
                mma1688(ox[0], vm.x, vm.y, px0);
                mma1688(ox[1], vm.z, vm.w, px0);
                sm[0] = rcp(sm[0]); sm[1] = rcp(sm[1]);
                bar_sync(1, 128);
                TS(5);
#define OP_ISSUE(t0, t1)                                                                                       \
                wg_fence();                                                                                    \
                _Pragma("unroll") for (int ks = 0; ks < 8; ks++)                                               \
                    _Pragma("unroll") for (int t = t0; t < t1; t++) {                                          \
                        constexpr uint64_t da0 = mkdesc(SM_BASE + O_WO, 16, 1024, 1), db0 = mkdesc(SM_BASE + O_O, 128, 128, 0); \
                        if (ks == 0) wg_ss8<0>(cc[t], da0 + t * 1024, db0); else wg_ss8<1>(cc[t], da0 + t * 1024 + ks * 128, db0 + ks * 16); \
                    }                                                                                          \
                wg_commit();
                OP_ISSUE(0, (OP_SPLIT ? 2 : 4));
                pa = redp + (s & 3) * 32768 + red_grp(j * 16 + (tid >> 3));
                pb = pa + 512 + ((lane >> 3) & 1) * 64 + (lane & 7) * 8;
                pa += (lane & 7) * 16;
                KEEPP(pa); KEEPP(pb);
                SCHED_FENCE();
                if (!bar_or(1, 128, vbad)) break;
                wg_wait<0>();
                const uint4* vp = &g_kvq[((s & 3) * 32 + h) * (3 * 512) + 1024 + w * 128 + lane];
#pragma unroll
                for (int i = 0; i < 4; i++) vf[i] = ldg_rlx128(vp + i * 32);
                if (nv > SPIN_LIMIT) __trap();
                bar_sync(1, 128);
            }
            {
                const float i0 = sm[0], i1 = sm[1];
#pragma unroll
                for (int hf = 0; hf < 2; hf++) {
                    if (hf == 0 || OP_SPLIT) wg_wait<0>();
                    if (hf == 0) TS(6);
                    if (OPD_EARLY && hf == OP_SPLIT && lane == 0) mbar_arrive(bars + 8 * B_OPDONE);
                    asm volatile("red.relaxed.gpu.global.add.noftz.v4.bf16x2 [%0], {%1,%2,%3,%4};" ::"l"(pa + hf * 128),
                                 "r"(pack_bf16(cc[2 * hf][0] * i0, cc[2 * hf][1] * i1)), "r"(pack_bf16(cc[2 * hf][2] * i0, cc[2 * hf][3] * i1)),
                                 "r"(pack_bf16(cc[2 * hf + 1][0] * i0, cc[2 * hf + 1][1] * i1)), "r"(pack_bf16(cc[2 * hf + 1][2] * i0, 1.f)) : "memory");
                    if (OP_SPLIT && hf == 0) { SCHED_FENCE(); OP_ISSUE(2, 4); }
                }
                asm volatile("red.relaxed.gpu.global.add.noftz.v2.bf16x2 [%0], {%1,%2};" ::"l"(pb), "r"(pack_bf16(cc[1][3] * i1, cc[3][3] * i1)), "r"(0x3f800000u) : "memory");
                if (!OPD_EARLY && lane == 0) mbar_arrive(bars + 8 * B_OPDONE);
                SCHED_FENCE();
                TS(7);
            }
            {
                const float ix0 = rcp(sx[0]), ix1 = rcp(sx[1]);
                const uint32_t xo = sb + O_XO + w * 512;
                stsm4t(xo + (lane & 7) * 64 + (((lane >> 3) ^ ((lane >> 1) & 3)) << 4), pack_bf16(ox[0][0] * ix0, ox[0][1] * ix1),
                       pack_bf16(ox[0][2] * ix0, ox[0][3] * ix1), pack_bf16(ox[1][0] * ix0, ox[1][1] * ix1), pack_bf16(ox[1][2] * ix0, ox[1][3] * ix1));
                __syncwarp();
                const uint4 ov = lds128u(xo + (lane >> 2) * 64 + (((lane & 3) ^ ((lane >> 3) & 3)) << 4));
                stg128(&g_ox[(size_t)(s * 32 + j * 8 + (lane >> 2)) * 4096 + h * 128 + w * 32 + (lane & 3) * 8], ov.x, ov.y, ov.z, ov.w);
            }
            TS(8);
            if (w == 2) { LT(s, 0, gtime()); LT(s, 1, clk()); }
            if (s == 0) GT(2);
        }
        GT(3);
        sts32(bars + 508, sf);
        TSDUMP();
        bar_sync(7, 512);
        const int m0 = (role >> 3) * 128, nb = (role & 7) * 2;
#define W2_LOAD(st, kt) { mbar_expect_tx(bars + 8 * (B_GF + (st)), 32768); tma3d(sb + (st) * 32768 + 16384, &tm_w2, 0, (kt) * 64, nb, bars + 8 * (B_GF + (st))); }
        if (w == 1 && lane == 0) {
            fence_async_smem();
#pragma unroll 1
            for (int kt = 0; kt < G_ST; kt++) W2_LOAD(kt, kt);
        }
        if (w == 0) {
            gbar_wait(&g_end, gbar_arrive(&g_end, 1, 128, lane), 0);
            int st = 0, ph = 1;
#pragma unroll 1
            for (int kt = 0; kt < 64; kt++) {
                if (kt >= G_ST) mbar_wait(bars + 8 * (B_GE + st), ph);
                if (lane == 0) {
                    if (kt >= G_ST) W2_LOAD(st, kt);
                    tma2d(sb + st * 32768, &tm_o, kt * 64, m0, bars + 8 * (B_GF + st));
                }
                if (++st == G_ST) { st = 0; ph ^= 1; }
            }
        }
    }
}

typedef CUresult (*EncodeFn)(CUtensorMap*, CUtensorMapDataType, cuuint32_t, void*, const cuuint64_t*, const cuuint64_t*,
                             const cuuint32_t*, const cuuint32_t*, CUtensorMapInterleave, CUtensorMapSwizzle,
                             CUtensorMapL2promotion, CUtensorMapFloatOOBfill);

static void make_map(EncodeFn fn, CUtensorMap* m, const void* p, uint64_t cols, uint64_t rows, uint32_t bc, uint32_t br) {
    cuuint64_t dims[2] = {cols, rows}, strides[1] = {cols * 2};
    cuuint32_t box[2] = {bc, br}, es[2] = {1, 1};
    fn(m, CU_TENSOR_MAP_DATA_TYPE_BFLOAT16, 2, (void*)p, dims, strides, box, es, CU_TENSOR_MAP_INTERLEAVE_NONE,
       CU_TENSOR_MAP_SWIZZLE_128B, CU_TENSOR_MAP_L2_PROMOTION_L2_128B, CU_TENSOR_MAP_FLOAT_OOB_FILL_NONE);
}

static Tune h_tune = {480, 1888, 6 + 16 * 2 + 256 * 4, 200, 960, 4000, 600};

extern "C" void kernel_launch(void* const* d_in, const int* in_sizes, int n_in, void* d_out, int out_size) {
    static bool init = false;
    static FftMaps fm;
    static CUtensorMap tm_x, tm_wq, tm_wk, tm_wv, tm_wo, tm_o, tm_wo2;
    if (!init) {
        void* fp = nullptr; cudaDriverEntryPointQueryResult qr;
        cudaGetDriverEntryPoint("cuTensorMapEncodeTiled", &fp, cudaEnableDefault, &qr);
        EncodeFn fn = (EncodeFn)fp;
        void* ox = nullptr; cudaGetSymbolAddress(&ox, g_ox);
        {
            cuuint64_t dims[4] = {64, 8, 16, 256}, strides[3] = {2048, 128, 16384};
            cuuint32_t box[4] = {64, 8, 8, 4}, es[4] = {1, 1, 1, 1};
            fn(&tm_x, CU_TENSOR_MAP_DATA_TYPE_BFLOAT16, 4, d_in[3], dims, strides, box, es, CU_TENSOR_MAP_INTERLEAVE_NONE,
               CU_TENSOR_MAP_SWIZZLE_128B, CU_TENSOR_MAP_L2_PROMOTION_L2_128B, CU_TENSOR_MAP_FLOAT_OOB_FILL_NONE);
        }
        void* fy = nullptr; cudaGetSymbolAddress(&fy, g_fy);
        for (int i = 0; i < 3; i++) {
            const cuuint64_t pitch = i == 2 ? 4096 : 2048;
            cuuint64_t dims[4] = {1024, 8, 16, 16}, strides[3] = {pitch, 128 * pitch, 8 * pitch};
            cuuint32_t box[4] = {64, 1, 16, 16}, es[4] = {1, 1, 1, 1};
            fn(i == 0 ? &fm.x : i == 1 ? &fm.y : &fm.o, CU_TENSOR_MAP_DATA_TYPE_BFLOAT16, 4, i == 0 ? d_in[0] : i == 1 ? fy : d_out, dims, strides, box, es,
               CU_TENSOR_MAP_INTERLEAVE_NONE, CU_TENSOR_MAP_SWIZZLE_128B, CU_TENSOR_MAP_L2_PROMOTION_L2_256B, CU_TENSOR_MAP_FLOAT_OOB_FILL_NONE);
        }
        {
            cuuint64_t dims[3] = {64, 2048, 16}, strides[2] = {2048, 128};
            cuuint32_t box[3] = {64, 8, 16}, es[3] = {1, 1, 1};
            fn(&fm.y2, CU_TENSOR_MAP_DATA_TYPE_BFLOAT16, 3, fy, dims, strides, box, es, CU_TENSOR_MAP_INTERLEAVE_NONE,
               CU_TENSOR_MAP_SWIZZLE_128B, CU_TENSOR_MAP_L2_PROMOTION_L2_128B, CU_TENSOR_MAP_FLOAT_OOB_FILL_NONE);
        }
        for (int i = 0; i < 2; i++) {
            cuuint64_t dims[3] = {256 * 513 - 448, 8, 8}, strides[2] = {128, 256 * 1026};
            cuuint32_t box[3] = {72, 8, 8}, es[3] = {1, 1, 1};
            fn(i ? &fm.wi : &fm.wr, CU_TENSOR_MAP_DATA_TYPE_BFLOAT16, 3, d_in[1 + i], dims, strides, box, es, CU_TENSOR_MAP_INTERLEAVE_NONE,
               CU_TENSOR_MAP_SWIZZLE_NONE, CU_TENSOR_MAP_L2_PROMOTION_L2_128B, CU_TENSOR_MAP_FLOAT_OOB_FILL_NONE);
        }
        fm.w[0] = (const unsigned char*)d_in[1]; fm.w[1] = (const unsigned char*)d_in[2]; fm.w[2] = (const unsigned char*)d_in[3];
        make_map(fn, &tm_wq, d_in[5], 4096, 1024, 64, 128);
        make_map(fn, &tm_wk, d_in[6], 4096, 1024, 64, 128);
        make_map(fn, &tm_wv, d_in[7], 4096, 1024, 64, 128);
        make_map(fn, &tm_wo, d_in[8], 1024, 4096, 64, 128);
        make_map(fn, &tm_o, ox, 4096, 2048, 64, 128);
        {
            cuuint64_t dims[3] = {64, 4096, 16}, strides[2] = {2048, 128};
            cuuint32_t box[3] = {64, 64, 2}, es[3] = {1, 1, 1};
            fn(&tm_wo2, CU_TENSOR_MAP_DATA_TYPE_BFLOAT16, 3, d_in[8], dims, strides, box, es, CU_TENSOR_MAP_INTERLEAVE_NONE,
               CU_TENSOR_MAP_SWIZZLE_128B, CU_TENSOR_MAP_L2_PROMOTION_L2_128B, CU_TENSOR_MAP_FLOAT_OOB_FILL_NONE);
        }
        cudaFuncSetAttribute(rmt_main, cudaFuncAttributeMaxDynamicSharedMemorySize, MAIN_SMEM);
        init = true;
    }
    rmt_main<<<132, 512, MAIN_SMEM>>>(tm_x, tm_wq, tm_wk, tm_wv, tm_wo, (const bf16*)d_in[4], h_tune, fm, tm_o, tm_wo2, (bf16*)d_out);
}
```

```cpp
#include <cuda_runtime.h>
#include <cuda_bf16.h>
#include <cuda.h>
#include <stdint.h>

typedef __nv_bfloat16 bf16;

#define DBG_TIMING 0

#define SPIN_LIMIT (1u << 22)

__device__ __forceinline__ uint32_t smem_u32(const void* p) { return (uint32_t)__cvta_generic_to_shared(p); }
__device__ __forceinline__ uint32_t clk() { uint32_t c; asm volatile("mov.u32 %0, %%clock;" : "=r"(c)::"memory"); return c; }
#define SCHED_FENCE() sf ^= (uint32_t)clock64()
#define KEEP2(a, b) asm volatile("lop3.b32 %0, %0, %1, %2, 0x96;" : "+r"(sf) : "r"((uint32_t)(a)), "r"((uint32_t)(b)))
#define KEEPP(p) KEEP2((uintptr_t)(p), (uintptr_t)(p) >> 32)
__device__ __forceinline__ uint32_t gtime() { uint32_t c; asm volatile("mov.u32 %0, %%globaltimer_lo;" : "=r"(c)::"memory"); return c; }
__device__ __forceinline__ void wait_clk(uint32_t t0, uint32_t d) {
    asm volatile("{\n.reg .pred p;\n.reg .s32 t;\n.reg .b64 c;\nWL:\nmov.u64 c, %%clock64;\ncvt.u32.u64 t, c;\nsub.s32 t, t, %0;\nsetp.lt.s32 p, t, 0;\n@p bra.uni WL;\n}" ::"r"(t0 + d) : "memory");
}
__device__ __forceinline__ void wait_gtime(uint32_t t1) {
    asm volatile("{\n.reg .pred p;\n.reg .s32 t;\n.reg .b64 c;\nWL:\nmov.u64 c, %%globaltimer;\ncvt.u32.u64 t, c;\nsub.s32 t, t, %0;\nsetp.lt.s32 p, t, 0;\n@p bra.uni WL;\n}" ::"r"(t1) : "memory");
}

__device__ __forceinline__ void mbar_init(uint32_t bar, uint32_t cnt) {
    asm volatile("mbarrier.init.shared::cta.b64 [%0], %1;" ::"r"(bar), "r"(cnt) : "memory");
}
__device__ __forceinline__ void mbar_arrive(uint32_t bar) {
    asm volatile("mbarrier.arrive.shared::cta.b64 _, [%0];" ::"r"(bar) : "memory");
}
__device__ __forceinline__ void mbar_expect_tx(uint32_t bar, uint32_t bytes) {
    asm volatile("mbarrier.arrive.expect_tx.shared::cta.b64 _, [%0], %1;" ::"r"(bar), "r"(bytes) : "memory");
}
__device__ __forceinline__ void mbar_wait(uint32_t bar, uint32_t parity) {
    asm volatile(
        "{\n.reg .pred p, q;\n.reg .u32 n;\nmov.u32 n, 0;\n"
        "WL:\nmbarrier.try_wait.parity.shared::cta.b64 p, [%0], %1;\n"
        "add.u32 n, n, 1;\nsetp.gt.u32 q, n, %2;\n@q trap;\n@!p bra.uni WL;\n}" ::"r"(bar), "r"(parity), "n"(SPIN_LIMIT) : "memory");
}
__device__ __forceinline__ void mbar_wait_cluster(uint32_t bar, uint32_t parity) {
    asm volatile(
        "{\n.reg .pred p, q;\n.reg .u32 n;\nmov.u32 n, 0;\n"
        "WL:\nmbarrier.try_wait.parity.acquire.cluster.shared::cta.b64 p, [%0], %1;\n"
        "add.u32 n, n, 1;\nsetp.gt.u32 q, n, %2;\n@q trap;\n@!p bra.uni WL;\n}" ::"r"(bar), "r"(parity), "n"(SPIN_LIMIT) : "memory");
}
__device__ __forceinline__ void tma2d(uint32_t dst, const CUtensorMap* m, int c0, int c1, uint32_t bar) {
    asm volatile("cp.async.bulk.tensor.2d.shared::cluster.global.mbarrier::complete_tx::bytes [%0], [%1, {%3, %4}], [%2];"
                 ::"r"(dst), "l"(m), "r"(bar), "r"(c0), "r"(c1) : "memory");
}
__device__ __forceinline__ void tma3d(uint32_t dst, const CUtensorMap* m, int c0, int c1, int c2, uint32_t bar) {
    asm volatile("cp.async.bulk.tensor.3d.shared::cluster.global.mbarrier::complete_tx::bytes [%0], [%1, {%3, %4, %5}], [%2];"
                 ::"r"(dst), "l"(m), "r"(bar), "r"(c0), "r"(c1), "r"(c2) : "memory");
}
__device__ __forceinline__ void tma4d(uint32_t dst, const CUtensorMap* m, int c2, int c3, uint32_t bar) {
    asm volatile("cp.async.bulk.tensor.4d.shared::cluster.global.mbarrier::complete_tx::bytes [%0], [%1, {%5, %5, %3, %4}], [%2];"
                 ::"r"(dst), "l"(m), "r"(bar), "r"(c2), "r"(c3), "r"(0) : "memory");
}
__device__ __forceinline__ void bulk_g2s(uint32_t dst, const void* src, uint32_t bytes, uint32_t bar) {
    asm volatile("cp.async.bulk.shared::cluster.global.mbarrier::complete_tx::bytes [%0], [%1], %2, [%3];"
                 ::"r"(dst), "l"(src), "r"(bytes), "r"(bar) : "memory");
}
__device__ __forceinline__ void tma4d_prefetch(const CUtensorMap* m, int c2, int c3) {
    asm volatile("cp.async.bulk.prefetch.tensor.4d.L2.global [%0, {%3, %3, %1, %2}];" ::"l"(m), "r"(c2), "r"(c3), "r"(0) : "memory");
}
__device__ __forceinline__ void tma2d_prefetch(const CUtensorMap* m, int c0, int c1) {
    asm volatile("cp.async.bulk.prefetch.tensor.2d.L2.global [%0, {%1, %2}];" ::"l"(m), "r"(c0), "r"(c1) : "memory");
}
__device__ __forceinline__ void fence_async_smem() { asm volatile("fence.proxy.async.shared::cta;" ::: "memory"); }
__device__ __forceinline__ void fence_gpu() { asm volatile("fence.acq_rel.gpu;" ::: "memory"); }
__device__ __forceinline__ float rcp(float x) { float r; asm("rcp.approx.ftz.f32 %0, %1;" : "=f"(r) : "f"(x)); return r; }
__device__ __forceinline__ void bar_sync(int id, int n) { asm volatile("bar.sync %0, %1;" ::"r"(id), "r"(n) : "memory"); }

__device__ __forceinline__ bool bar_or(int id, int n, uint32_t x) {
    uint32_t r;
    asm volatile("{\n.reg .pred p, q;\n.reg .b32 t;\nand.b32 t, %3, 1;\nsetp.ne.u32 p, t, 0;\nbar.red.or.pred q, %1, %2, p;\nselp.u32 %0, 1, 0, q;\n}"
                 : "=r"(r) : "r"(id), "r"(n), "r"(x) : "memory");
    return __any_sync(~0u, r);
}
__device__ __forceinline__ uint32_t or3(uint32_t a, uint32_t b, uint32_t c) {
    uint32_t r; asm("lop3.b32 %0, %1, %2, %3, 0xFE;" : "=r"(r) : "r"(a), "r"(b), "r"(c)); return r;
}
__device__ __forceinline__ uint32_t pack_bf16(float lo, float hi) {
    uint32_t r; asm("cvt.rn.bf16x2.f32 %0, %1, %2;" : "=r"(r) : "f"(hi), "f"(lo)); return r;
}
__device__ __forceinline__ uint32_t add_bf16x2(uint32_t a, uint32_t b) {
    uint32_t r; asm volatile("add.rn.bf16x2 %0, %1, %2;" : "=r"(r) : "r"(a), "r"(b)); return r;
}
__device__ __forceinline__ uint32_t movm(uint32_t a) {
    uint32_t r; asm volatile("movmatrix.sync.aligned.m8n8.trans.b16 %0, %1;" : "=r"(r) : "r"(a)); return r;
}
__device__ __forceinline__ uint32_t orx(uint32_t acc, uint32_t a, uint32_t t) {
    uint32_t r; asm("lop3.b32 %0, %1, %2, %3, 0xF6;" : "=r"(r) : "r"(acc), "r"(a), "r"(t)); return r;
}
__device__ __forceinline__ uint32_t orx2(uint32_t a, uint32_t b, uint32_t t) {
    uint32_t r; asm("lop3.b32 %0, %1, %2, %3, 0x7E;" : "=r"(r) : "r"(a), "r"(b), "r"(t)); return r;
}
__device__ __forceinline__ float ex2(float x) { float r; asm("ex2.approx.ftz.f32 %0, %1;" : "=f"(r) : "f"(x)); return r; }
__device__ __forceinline__ void ldsm4t(uint32_t (&r)[4], uint32_t a) {
    asm volatile("ldmatrix.sync.aligned.m8n8.x4.trans.shared.b16 {%0,%1,%2,%3}, [%4];"
                 : "=r"(r[0]), "=r"(r[1]), "=r"(r[2]), "=r"(r[3]) : "r"(a) : "memory");
}
__device__ __forceinline__ void ldsm4(uint32_t (&r)[4], uint32_t a) {
    asm volatile("ldmatrix.sync.aligned.m8n8.x4.shared.b16 {%0,%1,%2,%3}, [%4];"
                 : "=r"(r[0]), "=r"(r[1]), "=r"(r[2]), "=r"(r[3]) : "r"(a) : "memory");
}
__device__ __forceinline__ void stsm4t(uint32_t a, uint32_t r0, uint32_t r1, uint32_t r2, uint32_t r3) {
    asm volatile("stmatrix.sync.aligned.m8n8.x4.trans.shared.b16 [%0], {%1,%2,%3,%4};"
                 ::"r"(a), "r"(r0), "r"(r1), "r"(r2), "r"(r3) : "memory");
}
__device__ __forceinline__ void stsm4(uint32_t a, uint32_t r0, uint32_t r1, uint32_t r2, uint32_t r3) {
    asm volatile("stmatrix.sync.aligned.m8n8.x4.shared.b16 [%0], {%1,%2,%3,%4};"
                 ::"r"(a), "r"(r0), "r"(r1), "r"(r2), "r"(r3) : "memory");
}
__device__ __forceinline__ void mma16816(float* c, uint32_t a0, uint32_t a1, uint32_t a2, uint32_t a3, uint32_t b0, uint32_t b1) {
    asm volatile("mma.sync.aligned.m16n8k16.row.col.f32.bf16.bf16.f32 {%0,%1,%2,%3}, {%4,%5,%6,%7}, {%8,%9}, {%0,%1,%2,%3};"
                 : "+f"(c[0]), "+f"(c[1]), "+f"(c[2]), "+f"(c[3]) : "r"(a0), "r"(a1), "r"(a2), "r"(a3), "r"(b0), "r"(b1));
}
__device__ __forceinline__ void mma1688(float* c, uint32_t a0, uint32_t a1, uint32_t b0) {
    asm volatile("mma.sync.aligned.m16n8k8.row.col.f32.bf16.bf16.f32 {%0,%1,%2,%3}, {%4,%5}, {%6}, {%0,%1,%2,%3};"
                 : "+f"(c[0]), "+f"(c[1]), "+f"(c[2]), "+f"(c[3]) : "r"(a0), "r"(a1), "r"(b0));
}
__device__ __forceinline__ void sts128(uint32_t a, float x, float y, float z, float w) {
    asm volatile("st.shared.v4.f32 [%0], {%1,%2,%3,%4};" ::"r"(a), "f"(x), "f"(y), "f"(z), "f"(w) : "memory");
}
__device__ __forceinline__ void sts64(uint32_t a, float x, float y) {
    asm volatile("st.shared.v2.f32 [%0], {%1,%2};" ::"r"(a), "f"(x), "f"(y) : "memory");
}
__device__ __forceinline__ void sts32(uint32_t a, uint32_t x) { asm volatile("st.shared.b32 [%0], %1;" ::"r"(a), "r"(x) : "memory"); }
__device__ __forceinline__ void sts128u(uint32_t a, uint4 v) {
    asm volatile("st.shared.v4.b32 [%0], {%1,%2,%3,%4};" ::"r"(a), "r"(v.x), "r"(v.y), "r"(v.z), "r"(v.w) : "memory");
}
__device__ __forceinline__ float4 lds128(uint32_t a) {
    float4 v; asm volatile("ld.shared.v4.f32 {%0,%1,%2,%3}, [%4];" : "=f"(v.x), "=f"(v.y), "=f"(v.z), "=f"(v.w) : "r"(a) : "memory"); return v;
}
__device__ __forceinline__ uint4 lds128u(uint32_t a) {
    uint4 v; asm volatile("ld.shared.v4.b32 {%0,%1,%2,%3}, [%4];" : "=r"(v.x), "=r"(v.y), "=r"(v.z), "=r"(v.w) : "r"(a) : "memory"); return v;
}
__device__ __forceinline__ uint4 lds128v(uint32_t a) {
    uint4 v; asm volatile("ld.volatile.shared.v4.b32 {%0,%1,%2,%3}, [%4];" : "=r"(v.x), "=r"(v.y), "=r"(v.z), "=r"(v.w) : "r"(a) : "memory"); return v;
}
__device__ __forceinline__ void sts64u(uint32_t a, uint2 v) { asm volatile("st.shared.v2.b32 [%0], {%1,%2};" ::"r"(a), "r"(v.x), "r"(v.y) : "memory"); }
__device__ __forceinline__ uint2 lds64u(uint32_t a) {
    uint2 v; asm volatile("ld.shared.v2.b32 {%0,%1}, [%2];" : "=r"(v.x), "=r"(v.y) : "r"(a) : "memory"); return v;
}
__device__ __forceinline__ float2 lds64(uint32_t a) {
    float2 v; asm volatile("ld.shared.v2.f32 {%0,%1}, [%2];" : "=f"(v.x), "=f"(v.y) : "r"(a) : "memory"); return v;
}
__device__ __forceinline__ uint2 ldg_rlx64(const void* p) {
    uint2 v; asm volatile("ld.relaxed.gpu.global.v2.b32 {%0,%1}, [%2];" : "=r"(v.x), "=r"(v.y) : "l"(p) : "memory"); return v;
}
__device__ __forceinline__ uint4 ldg_rlx128(const void* p) {
    uint4 v; asm volatile("ld.relaxed.gpu.global.v4.b32 {%0,%1,%2,%3}, [%4];" : "=r"(v.x), "=r"(v.y), "=r"(v.z), "=r"(v.w) : "l"(p) : "memory"); return v;
}
__device__ __forceinline__ void stg_rlx64(void* p, uint32_t x, uint32_t y) {
    asm volatile("st.relaxed.gpu.global.v2.b32 [%0], {%1,%2};" ::"l"(p), "r"(x), "r"(y) : "memory");
}
__device__ __forceinline__ void stg_rlx128(void* p, uint32_t x, uint32_t y, uint32_t z, uint32_t w) {
    asm volatile("st.relaxed.gpu.global.v4.b32 [%0], {%1,%2,%3,%4};" ::"l"(p), "r"(x), "r"(y), "r"(z), "r"(w) : "memory");
}
__device__ __forceinline__ uint32_t ldg_rlx32(const void* p) {
    uint32_t v; asm volatile("ld.relaxed.gpu.global.b32 %0, [%1];" : "=r"(v) : "l"(p) : "memory"); return v;
}
__device__ __forceinline__ void stg128(void* p, uint32_t x, uint32_t y, uint32_t z, uint32_t w) {
    asm volatile("st.global.v4.b32 [%0], {%1,%2,%3,%4};" ::"l"(p), "r"(x), "r"(y), "r"(z), "r"(w) : "memory");
}
__device__ __forceinline__ uint32_t ld_acquire(const unsigned* p) {
    uint32_t v; asm volatile("ld.acquire.gpu.global.u32 %0, [%1];" : "=r"(v) : "l"(p) : "memory"); return v;
}
__device__ __forceinline__ void red_add_u32(unsigned* p, uint32_t v) {
    asm volatile("red.relaxed.gpu.global.add.u32 [%0], %1;" ::"l"(p), "r"(v) : "memory");
}
__device__ __forceinline__ void wait_counter(const unsigned* p, uint32_t target) {
    uint32_t n = 0;
    while (ld_acquire(p) < target) { if (++n > SPIN_LIMIT) __trap(); }
}

__device__ __forceinline__ void wg_fence() { asm volatile("wgmma.fence.sync.aligned;" ::: "memory"); }
__device__ __forceinline__ void wg_commit() { asm volatile("wgmma.commit_group.sync.aligned;" ::: "memory"); }
template <int N> __device__ __forceinline__ void wg_wait() { asm volatile("wgmma.wait_group.sync.aligned %0;" ::"n"(N) : "memory"); }
__host__ __device__ constexpr uint64_t mkdesc(uint32_t addr, uint32_t lbo, uint32_t sbo, uint32_t swz) {
    return (uint64_t)((addr & 0x3FFFF) >> 4) | ((uint64_t)(lbo >> 4) << 16) | ((uint64_t)(sbo >> 4) << 32) | ((uint64_t)swz << 62);
}
#define F4(d, o) "+f"(d[o]), "+f"(d[o + 1]), "+f"(d[o + 2]), "+f"(d[o + 3])
template <int SC> __device__ __forceinline__ void wg_rs32(float (&d)[16], const uint32_t (&a)[4], uint64_t db) {
    asm volatile("wgmma.mma_async.sync.aligned.m64n32k16.f32.bf16.bf16 "
                 "{%0,%1,%2,%3,%4,%5,%6,%7,%8,%9,%10,%11,%12,%13,%14,%15}, {%16,%17,%18,%19}, %20, %21, 1, 1, 0;"
                 : F4(d, 0), F4(d, 4), F4(d, 8), F4(d, 12)
                 : "r"(a[0]), "r"(a[1]), "r"(a[2]), "r"(a[3]), "l"(db), "n"(SC));
}
template <int SC> __device__ __forceinline__ void wg_rs40(float (&d)[20], const uint32_t (&a)[4], uint64_t db) {
    asm volatile("wgmma.mma_async.sync.aligned.m64n40k16.f32.bf16.bf16 "
                 "{%0,%1,%2,%3,%4,%5,%6,%7,%8,%9,%10,%11,%12,%13,%14,%15,%16,%17,%18,%19}, {%20,%21,%22,%23}, %24, %25, 1, 1, 0;"
                 : F4(d, 0), F4(d, 4), F4(d, 8), F4(d, 12), F4(d, 16)
                 : "r"(a[0]), "r"(a[1]), "r"(a[2]), "r"(a[3]), "l"(db), "n"(SC));
}
template <int SC> __device__ __forceinline__ void wg_ss40(float (&d)[20], uint64_t da, uint64_t db) {
    asm volatile("wgmma.mma_async.sync.aligned.m64n40k16.f32.bf16.bf16 "
                 "{%0,%1,%2,%3,%4,%5,%6,%7,%8,%9,%10,%11,%12,%13,%14,%15,%16,%17,%18,%19}, %20, %21, %22, 1, 1, 1, 0;"
                 : F4(d, 0), F4(d, 4), F4(d, 8), F4(d, 12), F4(d, 16)
                 : "l"(da), "l"(db), "n"(SC));
}
template <int SC> __device__ __forceinline__ void wg_ss8(float (&d)[4], uint64_t da, uint64_t db) {
    asm volatile("wgmma.mma_async.sync.aligned.m64n8k16.f32.bf16.bf16 {%0,%1,%2,%3}, %4, %5, %6, 1, 1, 1, 1;"
                 : F4(d, 0) : "l"(da), "l"(db), "n"(SC));
}

constexpr int DBG_N = 11;
#define LT(st, k, v) do {} while (0)
#define TSI(st) do {} while (0)
#define TS(k) do {} while (0)
#define TSV(k, v) do {} while (0)
#define TSDUMP() do {} while (0)
#define GT(k) do {} while (0)

__device__ __align__(256) uint4 g_fy[2048 * 128];

constexpr uint32_t FG_SIZE = 2 * 32768 + 36864;
constexpr uint32_t FT_F16 = 2 * FG_SIZE, FT_B1F = FT_F16 + 2048, FT_B1I = FT_B1F + 2048, FT_C = FT_B1I + 2048, FT_A8 = FT_C + 2048,
                   FT_TWC = FT_A8 + 512, FT_TWB = FT_TWC + 8192, FT_BAR = FT_TWB + 8192, FFT_SMEM = FT_BAR + 256;
struct FftMaps { CUtensorMap x, y, o, y2, wr, wi; const unsigned char* w[3]; };

__device__ __forceinline__ float2 wroot(int e) {
    float s, c; sincospif((float)(e & 2047) * (-1.f / 1024.f), &s, &c); return make_float2(c, s);
}
__device__ __forceinline__ uint4 afrag(float2 a, float2 b) {
    return make_uint4(pack_bf16(a.x, -a.y), pack_bf16(a.y, a.x), pack_bf16(b.x, -b.y), pack_bf16(b.y, b.x));
}
__device__ __forceinline__ uint4 conjfrag(uint4 v) { return make_uint4(v.x ^ 0x80000000u, v.y ^ 0x8000u, v.z ^ 0x80000000u, v.w ^ 0x8000u); }
__device__ __forceinline__ uint4 negfrag(uint4 v) { return make_uint4(v.x ^ 0x80008000u, v.y ^ 0x80008000u, v.z ^ 0x80008000u, v.w ^ 0x80008000u); }
__device__ __forceinline__ uint32_t comp(const uint4& v, int i) { return i == 0 ? v.x : i == 1 ? v.y : i == 2 ? v.z : v.w; }
__device__ __forceinline__ void setcomp(uint4& v, int i, uint32_t x) { if (i == 0) v.x = x; else if (i == 1) v.y = x; else if (i == 2) v.z = x; else v.w = x; }
__device__ __forceinline__ float2 cmul(float2 a, float2 b) { return make_float2(a.x * b.x - a.y * b.y, a.x * b.y + a.y * b.x); }
__device__ __forceinline__ float2 cmulc(float2 a, float2 b) { return make_float2(a.x * b.x + a.y * b.y, a.y * b.x - a.x * b.y); }

__device__ __forceinline__ uint32_t pack_h2(float2 a) { uint32_t r; asm("cvt.rn.f16x2.f32 %0, %1, %2;" : "=r"(r) : "f"(a.y), "f"(a.x)); return r; }
__device__ __forceinline__ float2 unpack_h2(uint32_t v) {
    float2 r; asm("{\n.reg .b16 l, h;\nmov.b32 {l, h}, %2;\ncvt.f32.f16 %0, l;\ncvt.f32.f16 %1, h;\n}" : "=f"(r.x), "=f"(r.y) : "r"(v)); return r;
}
__device__ __forceinline__ void fft_tables(uint32_t tb, int tid, int nthr) {
    for (int i = tid; i < 128; i += nthr) {
        const int lane = i & 31, q = i >> 5, g = lane >> 2, t = lane & 3, o = 8 * (q >> 1) + g, in = 8 * (q & 1) + 2 * t;
        sts128u(tb + FT_F16 + i * 16, afrag(wroot(128 * o * in), wroot(128 * o * (in + 1))));
        sts128u(tb + FT_B1F + i * 16, afrag(wroot(64 * (1 + 2 * o) * in), wroot(64 * (1 + 2 * o) * (in + 1))));
        sts128u(tb + FT_B1I + i * 16, afrag(wroot(-64 * o * (1 + 2 * in)), wroot(-64 * o * (3 + 2 * in))));
        uint4 v;
        for (int r = 0; r < 4; r++) {
            const float2 a = wroot(128 * (4 * r + t) * (4 * q + (g >> 1)));
            setcomp(v, r, (g & 1) ? pack_bf16(a.y, a.x) : pack_bf16(a.x, -a.y));
        }
        sts128u(tb + FT_C + i * 16, v);
        if (q == 0) sts128u(tb + FT_A8 + lane * 16, afrag(wroot(256 * g * 2 * t), wroot(256 * g * (2 * t + 1))));
    }
    for (int i = tid; i < 512; i += nthr) {
        const int lane = i & 31, r = (i >> 5) & 3, phi = 8 * (i >> 7) + (lane >> 2), c = 4 * r + (lane & 3);
        const float2 a = wroot(4 * c * phi), b = wroot(2 * (phi + 32 * c));
        constexpr float SC = 1.f / (2.f * 2048.f * 512.f);
        sts128(tb + FT_TWC + i * 16, a.x * SC, a.y * SC, b.x, b.y);
    }
    for (int i = tid; i < 512; i += nthr) {
        const int lane = i & 31, r = (i >> 5) & 3, fa = (i >> 7) & 1, hf = i >> 8, c = 8 * (lane & 1) + r;
        const int p0 = fa + 2 * (lane >> 2), p1 = p0 + 16, s0 = (hf && p0) ? 32 - p0 : p0, s1 = hf ? 32 - p1 : p1;
        sts128u(tb + FT_TWB + i * 16, make_uint4(pack_h2(wroot(4 * c * s0)), pack_h2(wroot(4 * (c + 4) * s0)),
                                                 pack_h2(wroot(4 * c * s1)), pack_h2(wroot(4 * (c + 4) * s1))));
    }
}

template <bool TW>
__device__ __forceinline__ void dft16(uint4 (&out)[4], const uint4 (&in)[4], const uint4 (&m)[4], const uint4 (&tw)[4]) {
#pragma unroll
    for (int i = 0; i < 4; i++)
#pragma unroll
        for (int mt = 0; mt < 2; mt++) {
            float c[4] = {0.f, 0.f, 0.f, 0.f};
            mma16816(c, m[2 * mt].x, m[2 * mt].y, m[2 * mt].z, m[2 * mt].w, comp(in[0], i), comp(in[1], i));
            mma16816(c, m[2 * mt + 1].x, m[2 * mt + 1].y, m[2 * mt + 1].z, m[2 * mt + 1].w, comp(in[2], i), comp(in[3], i));
            if (TW) {
                const float2 a = cmul(make_float2(c[0], c[2]), unpack_h2(comp(tw[i], 2 * mt))), b = cmul(make_float2(c[1], c[3]), unpack_h2(comp(tw[i], 2 * mt + 1)));
                setcomp(out[2 * mt], i, pack_bf16(a.x, a.y));
                setcomp(out[2 * mt + 1], i, pack_bf16(b.x, b.y));
            } else {
                setcomp(out[2 * mt], i, pack_bf16(c[0], c[2]));
                setcomp(out[2 * mt + 1], i, pack_bf16(c[1], c[3]));
            }
        }
}
__device__ __forceinline__ void tma_ld4(uint32_t dst, const CUtensorMap* m, int c0, int c1, uint32_t bar) {
    asm volatile("cp.async.bulk.tensor.4d.shared::cluster.global.mbarrier::complete_tx::bytes [%0], [%1, {%3, %4, %5, %5}], [%2];"
                 ::"r"(dst), "l"(m), "r"(bar), "r"(c0), "r"(c1), "r"(0) : "memory");
}
__device__ __forceinline__ void tma_st4(uint32_t src, const CUtensorMap* m, int c0, int c1) {
    asm volatile("cp.async.bulk.tensor.4d.global.shared::cta.bulk_group [%1, {%2, %3, %4, %4}], [%0];" ::"r"(src), "l"(m), "r"(c0), "r"(c1), "r"(0) : "memory");
}
__device__ __forceinline__ void tma_ld3(uint32_t dst, const CUtensorMap* m, int c0, int c1, uint32_t bar) {
    asm volatile("cp.async.bulk.tensor.3d.shared::cluster.global.mbarrier::complete_tx::bytes [%0], [%1, {%3, %4, %5}], [%2];"
                 ::"r"(dst), "l"(m), "r"(bar), "r"(c0), "r"(c1), "r"(0) : "memory");
}
__device__ __forceinline__ void tma_st3(uint32_t src, const CUtensorMap* m, int c0, int c1) {
    asm volatile("cp.async.bulk.tensor.3d.global.shared::cta.bulk_group [%1, {%2, %3, %4}], [%0];" ::"r"(src), "l"(m), "r"(c0), "r"(c1), "r"(0) : "memory");
}
__device__ __forceinline__ void bulk_commit() { asm volatile("cp.async.bulk.commit_group;" ::: "memory"); }
__device__ __forceinline__ void bulk_wait_read() { asm volatile("cp.async.bulk.wait_group.read 0;" ::: "memory"); }
__device__ __forceinline__ void bulk_wait_all() { asm volatile("cp.async.bulk.wait_group 0;" ::: "memory"); }

__device__ __forceinline__ float2 wroot_fast(int e) {
    float s, c; __sincosf((float)(((e + 1024) & 2047) - 1024) * (-3.14159265358979f / 1024.f), &s, &c); return make_float2(c, s);
}
template <bool INV, int NT>
__device__ __forceinline__ void fft_col(int s2, int t0, const CUtensorMap* src, const CUtensorMap* dst, uint32_t gb, uint32_t mb,
                                        int w, int lane, int bar) {
    const int g = lane >> 2, t = lane & 3;
    const bool lead = w == 4 && lane == 0;
    if (NT > 1 && lead)
        for (int i = 0; i < 2; i++) { mbar_expect_tx(mb + 8 * i, 32768); tma_ld4(gb + i * 32768, src, (t0 + i) * 64, s2, mb + 8 * i); }
    uint4 f[4], m[2][4];
#pragma unroll
    for (int i = 0; i < 4; i++) {
        const int o = 8 * (i >> 1) + g, in = 8 * (i & 1) + 2 * t, sg = INV ? -128 : 128;
        f[i] = afrag(wroot_fast(sg * o * in), wroot_fast(sg * o * (in + 1)));
#pragma unroll
        for (int q = 0; q < 2; q++) {
            const int z = 2 * w + q;
            m[q][i] = INV ? afrag(wroot_fast(-(8 * o + s2) * (z + 16 * in)), wroot_fast(-(8 * o + s2) * (z + 16 * in + 16)))
                          : afrag(wroot_fast((z + 16 * o) * (8 * in + s2)), wroot_fast((z + 16 * o) * (8 * in + 8 + s2)));
        }
    }
    const uint32_t r1 = (32 * w + 2 * t) * 128 + ((g ^ (2 * t)) << 4);
    const uint32_t w1 = (32 * w + g) * 128 + (((2 * t) ^ (((w & 3) << 1) | (g & 1))) << 4);
    const uint32_t r2 = (32 * t + 2 * w) * 128 + ((g ^ (2 * t)) << 4);
    const uint32_t w2 = (32 * w + g) * 128 + (((2 * t) ^ g) << 4);
    int bi = 0, ph = 0;
#pragma unroll 1
    for (int it = 0; it < NT; it++) {
        const uint32_t buf = gb + bi * 32768;
        mbar_wait(mb + 8 * bi, ph);
        uint4 in[2][4], out[4];
#pragma unroll
        for (int q = 0; q < 2; q++)
#pragma unroll
            for (int i = 0; i < 4; i++) in[q][i] = lds128u(buf + (r1 ^ ((i & 1) * 0x90)) + (i >> 1) * 1024 + q * 2048);
        __syncwarp();
#pragma unroll
        for (int q = 0; q < 2; q++) {
            if (INV) dft16<false>(out, in[q], m[q], f); else dft16<false>(out, in[q], f, f);
#pragma unroll
            for (int i = 0; i < 4; i++) sts128u(buf + (w1 ^ ((i & 1) << 4)) + (i >> 1) * 1024 + q * 2048, out[i]);
        }
        bar_sync(bar, 256);
#pragma unroll
        for (int q = 0; q < 2; q++)
#pragma unroll
            for (int i = 0; i < 4; i++) in[q][i] = lds128u(buf + (r2 ^ (q * 0x90)) + (i & 1) * 2048 + (i >> 1) * 16384);
        const int bn = bi == 0 ? 2 : bi - 1;
        if (lead && it < NT - 2) { bulk_wait_read(); mbar_expect_tx(mb + 8 * bn, 32768); tma_ld4(gb + bn * 32768, src, (t0 + it + 2) * 64, s2, mb + 8 * bn); }
        bar_sync(bar, 256);
#pragma unroll
        for (int q = 0; q < 2; q++) {
            if (INV) dft16<false>(out, in[q], f, f); else dft16<false>(out, in[q], m[q], f);
#pragma unroll
            for (int i = 0; i < 4; i++) sts128u(buf + (w2 ^ ((i & 1) << 4)) + (i >> 1) * 1024 + q * 2048, out[i]);
        }
        fence_async_smem();
        bar_sync(bar, 256);
        if (NT > 1 && lead) { tma_st4(buf, dst, (t0 + it) * 64, s2); bulk_commit(); }
        if (++bi == 3) { bi = 0; ph ^= 1; }
    }
    if (NT > 1 && lead) bulk_wait_read();
}

__device__ __forceinline__ float ldw(uint32_t a) {
    uint16_t v; asm volatile("ld.shared.u16 %0, [%1];" : "=h"(v) : "r"(a) : "memory");
    return __uint_as_float((uint32_t)v << 16);
}
__device__ __forceinline__ void fft_mid(int grp, const FftMaps& fm, uint32_t tb,
                                        uint32_t gb, uint32_t mb, uint32_t& cnt, int w, int lane, int bar) {
    const int g = lane >> 2, t = lane & 3;
    const bool lead = w == 4 && lane == 0;
    const uint32_t wb = gb + 65536;
#define MID_LOAD(k, c)                                                                                                  \
    { mbar_expect_tx(mb + 8 * ((c) & 1), 32768);                                                                        \
      tma_ld3(gb + ((c) & 1) * 32768, &fm.y2, 0, (k) * 8, mb + 8 * ((c) & 1));                                          \
      tma_ld3(gb + ((c) & 1) * 32768 + 16384, &fm.y2, 0, ((256 - (k)) & 255) * 8, mb + 8 * ((c) & 1)); }
#define MID_LOADW(k)                                                                                                    \
    { mbar_expect_tx(mb + 16, 36864);                                                                                   \
      tma_ld3(wb, &fm.wr, (k) * 513 & ~7, 0, mb + 16); tma_ld3(wb + 9216, &fm.wi, (k) * 513 & ~7, 0, mb + 16);          \
      tma_ld3(wb + 18432, &fm.wr, ((256 - (k)) & 255) * 513 & ~7, 0, mb + 16); tma_ld3(wb + 27648, &fm.wi, ((256 - (k)) & 255) * 513 & ~7, 0, mb + 16); }
    if (lead) { MID_LOAD(grp, cnt); MID_LOADW(grp); }
    const int hB = w >> 2, faB = (w >> 1) & 1, xB = faB;
    const int phi = 8 * (w & 3) + g;
    const uint32_t rA = (8 * w + 2 * t) * 128 + ((g ^ (2 * t)) << 4);
    const uint32_t wA = (8 * w + g) * 128 + (((2 * t) ^ ((g & 1) | ((w & 3) << 1))) << 4);
    const uint32_t oB = (w >> 1) * 8192 + (w & 1) * 512;
    const uint32_t rB = oB + (8 * t + (g >> 2)) * 128 + (((g & 3) ^ ((g >> 2) | (t << 1)) ^ xB) << 4);
    const uint32_t wB = oB + (8 * (g >> 1) + (t >> 1)) * 128 + (((((g & 1) << 2) | (2 * (t & 1))) ^ ((t >> 1) | ((g >> 1) << 1)) ^ xB) << 4);
    const uint32_t wBi = oB + (8 * (g >> 1) + (t >> 1)) * 128 + (((((g & 1) << 2) | (2 * (t & 1))) ^ ((t >> 1) | ((w & 1) << 2))) << 4);
    const int hC = (lane >> 3) & 1, pr = 8 * (w & 3) + (lane & 7), pc = hC ? (32 - pr) & 31 : pr;
    const uint32_t aC = hC * 16384 + (pc & 1) * 8192 + (pc >> 2) * 1024 + (((((pc & 2) << 1) | (lane >> 4)) ^ (((pc >> 2) & 3) << 1) ^ (pc & 1)) << 4);
    const uint32_t g0 = wb + (t >> 1) * 144 + (32 * (t & 1) + phi) * 2, g1 = wb + 18432 + (7 - (t >> 1)) * 144 + (64 - 32 * (t & 1) - phi) * 2;
    const uint32_t wAo = (8 * w + g) * 128 + (((2 * t) ^ g) << 4);
    uint32_t wph = 0;
#pragma unroll 1
    for (int k1 = grp; k1 < 129; k1 += 8, cnt++, wph ^= 1) {
        const uint32_t buf = gb + (cnt & 1) * 32768;
        uint4 in[2][4], m[4], out[4];
        m[0] = m[1] = m[2] = lds128u(tb + FT_A8 + lane * 16);
        m[3] = negfrag(m[0]);
        mbar_wait(mb + 8 * (cnt & 1), (cnt >> 1) & 1);
#pragma unroll
        for (int q = 0; q < 2; q++)
#pragma unroll
            for (int i = 0; i < 4; i++) in[q][i] = lds128u(buf + (rA ^ ((i & 1) * 0x90)) + (i >> 1) * 8192 + q * 16384);
        __syncwarp();
#pragma unroll
        for (int q = 0; q < 2; q++) {
            dft16<false>(out, in[q], m, m);
#pragma unroll
            for (int i = 0; i < 4; i++) sts128u(buf + (wA ^ (((i ^ (i >> 1)) & 1) << 4)) + (i >> 1) * 8192 + q * 16384, out[i]);
        }
        {
            uint4 tw[4];
#pragma unroll
            for (int i = 0; i < 4; i++) {
                m[i] = lds128u(tb + (faB ? FT_B1F : FT_F16) + i * 512 + lane * 16);
                if (hB) { m[i].y ^= 0x80008000u; m[i].w ^= 0x80008000u; }
                tw[i] = lds128u(tb + FT_TWB + (w >> 1) * 2048 + i * 512 + lane * 16);
            }
            bar_sync(bar, 256);
#pragma unroll
            for (int q = 0; q < 2; q++)
#pragma unroll
                for (int i = 0; i < 4; i++) in[q][i] = lds128u(buf + (rB ^ ((i & 1) << 6)) + (i >> 1) * 4096 + q * 256);
            __syncwarp();
#pragma unroll
            for (int q = 0; q < 2; q++) {
                dft16<true>(out, in[q], m, tw);
#pragma unroll
                for (int i = 0; i < 4; i++) sts128u(buf + (wB ^ ((i & 1) << 4)) + (i >> 1) * 4096 + q * 256, out[i]);
            }
        }
        {
            const uint32_t cjm = (g & 1) ? 0x8000u : 0x80000000u;
            float4 tw[4];
#pragma unroll
            for (int i = 0; i < 4; i++) { m[i] = lds128u(tb + FT_C + i * 512 + lane * 16); tw[i] = lds128(tb + FT_TWC + ((w & 3) * 4 + i) * 512 + lane * 16); }
            if (lead && k1 + 8 < 129) { bulk_wait_read(); MID_LOAD(k1 + 8, cnt + 1); }
            __syncwarp();
            mbar_wait(mb + 16, wph);
            const uint32_t o0 = (k1 & 7) * 2, o1 = (-k1 & 7) * 2;
            if (w == 1 && lane < 16) {
                const int k2 = lane & 7, k2p = k1 ? 7 - k2 : (8 - k2) & 7;
                const uint32_t p0 = wb + (lane >> 3) * 9216 + k2 * 1152 + o0, p1 = wb + 18432 + (lane >> 3) * 9216 + k2p * 1152 + o1;
                const float sg = lane < 8 ? 0.5f : -0.5f;
                const uint32_t v = pack_bf16(0.5f * ldw(p0) + sg * ldw(p1), 0.5f * ldw(p1 + 1136) + sg * ldw(p0 + 1136));
                asm volatile("st.shared.u16 [%0], %1;" ::"r"(p0), "h"((uint16_t)v) : "memory");
                asm volatile("st.shared.u16 [%0], %1;" ::"r"(p1 + 1136), "h"((uint16_t)(v >> 16)) : "memory");
                fence_async_smem();
            }
            bar_sync(bar, 256);
#define FFT_CU 1
            constexpr int CU = FFT_CU;
#pragma unroll CU
            for (int q = 0; q < 4; q++) {
                const int k2 = 4 * (w >> 2) + q, k2p = k1 ? 7 - k2 : (8 - k2) & 7, kr = hC ? k2p : k2;
                const uint32_t a0 = buf + (aC ^ ((kr & 1) << 4)) + kr * 128;
                const uint32_t r0 = g0 + k2 * 1152 + o0, r1 = g1 + k2p * 1152 + o1;
                uint32_t x[4], y[4];
                ldsm4(x, a0); ldsm4(y, a0 ^ 32);
                float c[4][4];
#pragma unroll
                for (int i = 0; i < 4; i++) { c[i][0] = c[i][1] = c[i][2] = c[i][3] = 0.f; mma16816(c[i], x[0], x[1], x[2], x[3], m[i].x, m[i].y); }
#pragma unroll
                for (int i = 0; i < 4; i++) mma16816(c[i], y[0], y[1], y[2], y[3], m[i].z, m[i].w);
#pragma unroll
                for (int i = 0; i < 4; i++) {
                    const float2 ga = make_float2(ldw(r0 + i * 288), ldw(r0 + 9216 + i * 288));
                    const float2 gc = make_float2(ldw(r1 - i * 288), ldw(r1 + 9216 - i * 288));
                    const float tc = tw[i].z, ts = tw[i].w;
                    const float* z = c[i];
                    const float2 S = make_float2(ga.x + gc.x, ga.y - gc.y), D = make_float2(ga.x - gc.x, ga.y + gc.y);
                    const float2 u = make_float2(ts * z[0] - tc * z[3], ts * z[1] + tc * z[2]), v = make_float2(ts * z[2] - tc * z[1], ts * z[3] + tc * z[0]);
                    uint32_t* o = (i < 2 ? x : y) + 2 * (i & 1);
                    o[0] = pack_bf16(fmaf(S.x, z[0], fmaf(-S.y, z[1], fmaf(D.x, u.x, -D.y * u.y))), fmaf(S.x, z[1], fmaf(S.y, z[0], fmaf(D.x, u.y, D.y * u.x))));
                    o[1] = pack_bf16(fmaf(S.x, z[2], fmaf(-S.y, z[3], fmaf(-D.x, v.x, D.y * v.y))), fmaf(S.x, z[3], fmaf(S.y, z[2], fmaf(-D.x, v.y, -D.y * v.x))));
                }
#pragma unroll
                for (int i = 0; i < 4; i++) { c[i][0] = c[i][1] = c[i][2] = c[i][3] = 0.f; mma16816(c[i], x[0], x[1], x[2], x[3], m[i].x ^ cjm, m[i].y ^ cjm); }
#pragma unroll
                for (int i = 0; i < 4; i++) mma16816(c[i], y[0], y[1], y[2], y[3], m[i].z ^ cjm, m[i].w ^ cjm);
#pragma unroll
                for (int i = 0; i < 4; i++) {
                    uint32_t* o = (i < 2 ? x : y) + 2 * (i & 1);
                    o[0] = pack_bf16(c[i][0] * tw[i].x + c[i][1] * tw[i].y, c[i][1] * tw[i].x - c[i][0] * tw[i].y);
                    o[1] = pack_bf16(c[i][2] * tw[i].x + c[i][3] * tw[i].y, c[i][2] * tw[i].y - c[i][3] * tw[i].x);
                }
                stsm4(a0, x[0], x[1], x[2], x[3]);
                stsm4(a0 ^ 32, y[0], y[1], y[2], y[3]);
            }
        }
#pragma unroll
        for (int i = 0; i < 4; i++) { m[i] = lds128u(tb + (faB ? FT_B1I : FT_F16) + i * 512 + lane * 16); if (!faB) m[i] = conjfrag(m[i]); }
        bar_sync(bar, 256);
        if (lead && k1 + 8 < 129) MID_LOADW(k1 + 8);
        __syncwarp();
#pragma unroll
        for (int q = 0; q < 2; q++)
#pragma unroll
            for (int i = 0; i < 4; i++) in[q][i] = lds128u(buf + (rB ^ ((i & 1) << 6)) + (i >> 1) * 4096 + q * 256);
        __syncwarp();
#pragma unroll
        for (int q = 0; q < 2; q++) {
            dft16<false>(out, in[q], m, m);
#pragma unroll
            for (int i = 0; i < 4; i++) sts128u(buf + (wBi ^ ((i & 1) << 4) ^ (q << 5)) + (i >> 1) * 4096 + q * 256, out[i]);
        }
        m[0] = m[1] = m[2] = conjfrag(lds128u(tb + FT_A8 + lane * 16));
        m[3] = negfrag(m[0]);
        bar_sync(bar, 256);
#pragma unroll
        for (int q = 0; q < 2; q++)
#pragma unroll
            for (int i = 0; i < 4; i++) in[q][i] = lds128u(buf + (rA ^ ((i & 1) * 0x90)) + (i >> 1) * 8192 + q * 16384);
        __syncwarp();
#pragma unroll
        for (int q = 0; q < 2; q++) {
            dft16<false>(out, in[q], m, m);
#pragma unroll
            for (int i = 0; i < 4; i++) sts128u(buf + (wAo ^ ((i & 1) << 4)) + (i >> 1) * 8192 + q * 16384, out[i]);
        }
        fence_async_smem();
        bar_sync(bar, 256);
        if (lead) {
            tma_st3(buf, &fm.y2, 0, k1 * 8);
            if (k1 & 127) tma_st3(buf + 16384, &fm.y2, 0, (256 - k1) * 8);
            bulk_commit();
        }
    }
    if (lead) bulk_wait_all();
}

__device__ __align__(128) unsigned g_start;
__device__ __align__(128) unsigned g_fbar;
__device__ __align__(128) unsigned g_end;
__device__ __forceinline__ unsigned gbar_arrive(unsigned* c, unsigned inc, unsigned total, int lane) {
    unsigned v = 0;
    if (lane == 0) { asm volatile("fence.proxy.async;" ::: "memory"); fence_gpu(); v = atomicAdd(c, inc); }
    return (__shfl_sync(~0u, v, 0) & ~(total - 1)) + total;
}
__device__ __forceinline__ void gbar_wait(unsigned* c, unsigned target, unsigned ns) {
    uint32_t n = 0;
    while (__any_sync(~0u, (int)(ld_acquire(c) - target) < 0)) { if (ns) __nanosleep(ns); if (++n > SPIN_LIMIT) __trap(); }
    asm volatile("fence.proxy.async;" ::: "memory");
}
__device__ __forceinline__ void fft_rest(int cta, const FftMaps& fm, uint32_t sb, uint32_t opt) {
    const int hi = __shfl_sync(~0u, threadIdx.x >> 8, 0), w = __shfl_sync(~0u, (threadIdx.x >> 5) & 7, 0), lane = threadIdx.x & 31;
    unsigned target = 0;
    if (w == 4) target = gbar_arrive(&g_start, 16, 256, lane);
    if (threadIdx.x < 32) mbar_init(sb + FT_BAR + 8 * threadIdx.x, 1);
    fft_tables(sb, threadIdx.x, 512);
    fence_async_smem();
    __syncthreads();
    const int grp = cta * 2 + hi, bar = 1 + hi;
    const uint32_t gb = sb + hi * FG_SIZE, mb = sb + FT_BAR + hi * 128;
    uint32_t cnt = 0;
    if (w == 4) gbar_wait(&g_start, target, 200);
    if (w == 4) {
        const unsigned char* p = fm.w[2] + (size_t)(lane * 8 + grp) * 16384;
        asm volatile("cp.async.bulk.prefetch.L2.global [%0], %1;" ::"l"(p), "r"(16384) : "memory");
    }
    if (w == 4) {
        const unsigned char* p = fm.w[hi] + (size_t)(cta * 32 + lane) * 16416;
        asm volatile("cp.async.bulk.prefetch.L2.global [%0], %1;" ::"l"(p), "r"(16416) : "memory");
    }
    GT(1);
    fft_mid(grp, fm, sb, gb, mb, cnt, w, lane, bar);
    if (w == 4) gbar_wait(&g_fbar, gbar_arrive(&g_fbar, 1, 8, lane), 200);
    GT(2);
    fft_col<true, 16>(grp, 0, &fm.y, &fm.o, gb, mb + 64, w, lane, bar);
}

__device__ __align__(256) uint4 g_kvq[4 * 32 * 3 * 8 * 2 * 32];
__device__ __align__(256) uint2 g_alpha[2 * 32 * 3 * 8 * 2 * 32];
__device__ __align__(256) uint4 g_red[5 * 32768 / 16];
__device__ __align__(256) uint4 g_stamp[32];
__device__ __align__(256) uint4 g_qst[128 * 2];
__device__ __align__(256) bf16 g_ox[2048 * 4096];
struct Tune { uint32_t d_alpha, d_r, opt, d_q, d_v, spread, extra; };
#define OP_SPLIT 1
#define X_SEQ 24
#define QKW_POS 1
#define XO_POS 0
#define V_SEQ 0
#define X_HALF 1
#define V_KEEP 0
#define STAMP_V 1
#define EXP 0
#define FIN_BAR B_SRDY
#define V_LATE 0
#define OPD_EARLY 0
constexpr int RA = 2;

constexpr uint32_t SM_BASE = 1024;
constexpr uint32_t O_WO = 0;
constexpr uint32_t O_WV = 65536;
constexpr uint32_t O_XB = 131072;
constexpr uint32_t O_MEM = O_XB + 16384;
constexpr uint32_t O_RECV = O_XB + 40960;
constexpr uint32_t O_KVQ = O_RECV + 12288;
constexpr uint32_t O_STG = O_KVQ + 18432;
constexpr uint32_t O_S = O_STG + 8192;
constexpr uint32_t O_P = O_S + 10240;
constexpr uint32_t O_O = O_P + 1536;
constexpr uint32_t O_DBG = O_O + 2048;
constexpr uint32_t O_F1 = 196608;
constexpr uint32_t O_VM = O_F1 + 32768;
constexpr uint32_t O_BAR = 232448 - 512;
constexpr uint32_t MAIN_SMEM = 232448;
static_assert(O_DBG + (DBG_TIMING ? (4 * DBG_N + 1) * 96 : 0) <= O_VM && FFT_SMEM <= MAIN_SMEM && O_VM + 2048 <= O_BAR, "smem");
constexpr int G_ST = 6;
enum { B_W = 0, B_WO = B_W + 12, B_F1, B_XP, B_XFULL, B_RFULL, B_AFULL, B_KVFULL, B_XF1, B_QST, B_RECV, B_GF = B_RECV + 6,
       B_QDONE = B_GF + G_ST, B_KDONE, B_XEMPTY, B_VA, B_X0, B_SRDY, B_OPDONE, B_QX, B_GE, B_XPE = B_GE + G_ST, B_QKW, B_MEM, B_COUNT };

constexpr float SM_SCALE_LOG2 = 0.08838834764831845f * 1.4426950408889634f;
constexpr float MASK_VAL = -1.0e9f / 0.08838834764831845f;

__device__ __forceinline__ uint32_t red_grp(int grp) { return (uint32_t)((grp >> 1) * 1024 + (grp & 1) * 256); }
__host__ __device__ constexpr uint32_t kb_off(int kb) { return (uint32_t)((kb >> 2) * 20480 + (kb & 3) * 1024); }
__host__ __device__ constexpr uint64_t xdesc(int ks) { return mkdesc(SM_BASE + O_XB + kb_off(ks >> 2) + (ks & 3) * 32, 16, 4096, 1); }

__device__ __forceinline__ void x_split(const float* d, uint32_t (&sn)[4], uint32_t (&kp)[4], int kh) {
#pragma unroll
    for (int i = 0; i < 4; i++) {
        const uint32_t lo = pack_bf16(d[2 * i], d[2 * i + 1]), hi = pack_bf16(d[8 + 2 * i], d[8 + 2 * i + 1]);
        sn[i] = kh ? lo : hi; kp[i] = kh ? hi : lo;
    }
}
__device__ __forceinline__ void x_send(int R, const uint32_t (&sn)[4], int sg, int tid, uint32_t sb, uint32_t mate) {
    const uint32_t par = sg & 1;
    const uint32_t bar = O_BAR + 8 * (B_RECV + R * 2) + 8 * par;
    if (tid == 0) mbar_expect_tx(sb + bar, 2048);
    asm volatile("st.async.shared::cluster.mbarrier::complete_tx::bytes.v4.b32 [%0], {%1,%2,%3,%4}, [%5];"
                 ::"r"(mate + O_RECV + (par * 3 + R) * 2048 + tid * 16), "r"(sn[0]), "r"(sn[1]), "r"(sn[2]), "r"(sn[3]), "r"(mate + bar) : "memory");
}
__device__ __forceinline__ void x_wait(int R, int sg, uint32_t sb) {
    mbar_wait_cluster(sb + O_BAR + 8 * (B_RECV + R * 2) + 8 * (sg & 1), (sg >> 1) & 1);
}
template <int R>
__device__ __forceinline__ void x_finish(const uint32_t (&kp)[4], int sg, int h, int mt, int kh, int tid, uint32_t sb) {
    const uint4 r = lds128u(sb + O_RECV + ((sg & 1) * 3 + R) * 2048 + tid * 16);
    uint32_t u0 = add_bf16x2(kp[0], r.x), u1 = add_bf16x2(kp[1], r.y), u2 = add_bf16x2(kp[2], r.z), u3 = add_bf16x2(kp[3], r.w);
    const uint32_t tag = ((sg >> 2) & 1) ^ 1;
    uint4* const hb = &g_kvq[((sg & 3) * 32 + h) * (3 * 512)];
    if (R < 2) {
        const uint32_t m = (tid & 7) ? ~0u : ~1u, t = tag & ~m;
        uint32_t* p = (uint32_t*)hb + (R == 0 ? (kh * 16 + mt) * 64 : 2048 + (mt * 2 + kh) * 128) + (tid & 31);
        asm volatile("{\n.reg .pred p;\nsetp.lt.s32 p, %5, 64;\n@p st.relaxed.gpu.global.b32 [%0], %1;\n@p st.relaxed.gpu.global.b32 [%0+128], %2;\n"
                     "@p st.relaxed.gpu.global.b32 [%0+%6], %3;\n@p st.relaxed.gpu.global.b32 [%0+%7], %4;\n}"
                     ::"l"(p), "r"((u0 & m) | t), "r"((u1 & m) | t), "r"((u2 & m) | t), "r"((u3 & m) | t), "r"(sg),
                       "n"(R == 0 ? 2048 : 256), "n"(R == 0 ? 2176 : 384) : "memory");
    } else {
        asm volatile("{\n.reg .pred p;\nsetp.lt.s32 p, %5, 64;\n@p st.relaxed.gpu.global.v4.b32 [%0], {%1,%2,%3,%4};\n}"
                     ::"l"(hb + R * 512 + (mt * 2 + kh) * 32 + (tid & 31)), "r"((u0 & ~1u) | tag), "r"(u1), "r"(u2), "r"(u3), "r"(sg) : "memory");
    }
}
__device__ __forceinline__ uint32_t tags4(const uint32_t (&r)[4], uint32_t tag) { return orx(orx(orx2(r[0], r[1], tag), r[2], tag), r[3], tag); }

__device__ __forceinline__ uint32_t convert_mem(const unsigned char* redp, int s, int kh, int jj, int w, int lane, uint32_t sb, uint32_t& sf) {
    const uint32_t off = red_grp(jj * 16 + w * 4 + (lane >> 3)), o16 = off + (lane & 7) * 16, o8 = off + 512 + ((lane >> 3) & 1) * 64 + (lane & 7) * 8;
    uint32_t ma = sb + O_MEM + jj * 20480 + (lane >> 4) * 1024 + (lane & 7) * 128 + (((2 * w + ((lane >> 3) & 1)) ^ (lane & 7)) << 4);
    uint32_t a16 = sb + O_STG + o16, a8 = sb + O_STG + o8;
    const uint32_t target = (s & 4) ? 0x42C00000u : 0x42000000u;
    uint32_t n = 0;
    bool redo;
    KEEP2(ma, a16); KEEP2(a8, target);
#pragma unroll 1
    do {
        asm volatile("" : "+r"(n));
        if (n) {
            const unsigned char* pg = redp + (s & 3) * 32768 + __shfl_sync(~0u, kh, 0) * 16384;
            const uint4 x = ldg_rlx128(pg + o16), y = ldg_rlx128(pg + o16 + 128);
            const uint2 z = ldg_rlx64(pg + o8);
            sts128u(a16, x); sts128u(a16 + 128, y); sts64u(a8, z);
            if (n > SPIN_LIMIT) __trap();
        }
        n++;
        mbar_wait(sb + O_BAR + 8 * B_RFULL, s & 1);
        const uint4 ra = lds128u(a16), rb = lds128u(a16 + 128);
        const uint2 rc = lds64u(a8);
        stsm4t(ma, ra.x, ra.y, ra.z, __byte_perm(ra.w, rc.x, 0x5410));
        stsm4t(ma + 2048, rb.x, rb.y, rb.z, __byte_perm(rb.w, rc.x, 0x7610));
        redo = __any_sync(~0u, orx(orx2(ra.w, rb.w, target), rc.y, target) > 0xffffu);
    } while (redo);
    if (lane == 0) mbar_arrive(sb + O_BAR + 8 * B_MEM);
    fence_async_smem();
    __syncwarp();
    if (lane == 0) mbar_arrive(sb + O_BAR + 8 * B_QKW);
    return n - 1;
}

#define F16(d, o) F4(d, o), F4(d, o + 4), F4(d, o + 8), F4(d, o + 12)
__device__ __forceinline__ void wg_ss128(float (&d)[64], uint64_t da, uint64_t db, int sc) {
    asm volatile("{\n.reg .pred p;\nsetp.ne.b32 p, %66, 0;\nwgmma.mma_async.sync.aligned.m64n128k16.f32.bf16.bf16 "
                 "{%0,%1,%2,%3,%4,%5,%6,%7,%8,%9,%10,%11,%12,%13,%14,%15,%16,%17,%18,%19,%20,%21,%22,%23,%24,%25,%26,%27,%28,%29,%30,%31,"
                 "%32,%33,%34,%35,%36,%37,%38,%39,%40,%41,%42,%43,%44,%45,%46,%47,%48,%49,%50,%51,%52,%53,%54,%55,%56,%57,%58,%59,%60,%61,%62,%63}, "
                 "%64, %65, p, 1, 1, 1, 1;\n}"
                 : F16(d, 0), F16(d, 16), F16(d, 32), F16(d, 48) : "l"(da), "l"(db), "r"(sc));
}
__device__ __forceinline__ void stg_rlx32(void* p, uint32_t v) { asm volatile("st.relaxed.gpu.global.u32 [%0], %1;" ::"l"(p), "r"(v) : "memory"); }

__global__ void __cluster_dims__(2, 1, 1) __launch_bounds__(512, 1)
rmt_main(const __grid_constant__ CUtensorMap tm_x, const __grid_constant__ CUtensorMap tm_wq, const __grid_constant__ CUtensorMap tm_wk,
         const __grid_constant__ CUtensorMap tm_wv, const __grid_constant__ CUtensorMap tm_wo, const bf16* __restrict__ mem0,
         const Tune tn, const __grid_constant__ FftMaps fm, const __grid_constant__ CUtensorMap tm_o,
         const __grid_constant__ CUtensorMap tm_w2, bf16* __restrict__ out) {
    extern __shared__ __align__(1024) unsigned char smem_raw[];
    const uint32_t sb = smem_u32(smem_raw);
    if ((sb & 0x3FFFF) != SM_BASE) __trap();
    GT(6);
    const int cid = blockIdx.x >> 1, kh = blockIdx.x & 1;
    const int tpc = cid < 4 ? 62 + cid : cid - 4;
    int h, nh;
    if (tpc < 32) { h = (tpc >> 4) * 8 + (tpc & 7); nh = (tpc >> 3) & 1; }
    else if (tpc < 60) { int u = tpc - 32, r = u % 14; h = 16 + (u / 14) * 7 + r % 7; nh = r / 7; }
    else if (tpc < 62) { GT(0); fft_rest((tpc - 60) * 2 + kh, fm, sb, tn.opt); GT(3); return; }
    else { h = 30 + ((tpc - 62) >> 1); nh = tpc & 1; }
    const int j = nh * 2 + kh, role = h * 4 + j;
    const int wgi = __shfl_sync(~0u, threadIdx.x >> 7, 0);
    const int w = __shfl_sync(~0u, (threadIdx.x >> 5) & 3, 0);
    const int tid = threadIdx.x & 127, lane = tid & 31;
#define PIN_IDS() const int tid = __shfl_sync(~0u, threadIdx.x & 127, threadIdx.x & 31), lane = tid & 31
#define OPAQUE_IDS() int tid_ = tid; asm volatile("" : "+r"(tid_)); const int tid = tid_, lane = tid_ & 31; (void)lane
    unsigned char* const redp = (unsigned char*)(((uintptr_t)g_red + 32767) & ~(uintptr_t)32767);
    const uint32_t bars = sb + O_BAR;

    if (threadIdx.x < B_COUNT) {
        const int i = threadIdx.x;
        mbar_init(bars + 8 * i, i == B_XFULL && !X_HALF ? 2 : i < B_QDONE ? 1 : i < B_GE ? 4 : i < B_XPE ? 8 : i < B_QKW ? 12 : 16);
        asm volatile("fence.mbarrier_init.release.cluster;" ::: "memory");
        fence_async_smem();
    } else if (threadIdx.x >= 64 && threadIdx.x < 71) {
        const int i = threadIdx.x - 64;
        const CUtensorMap* m = i == 0 ? &tm_wk : i == 1 ? &tm_wq : i == 2 ? &fm.x : i == 3 ? &tm_x : i == 4 ? &tm_wv : i == 5 ? &tm_wo : &fm.y;
        asm volatile("prefetch.tensormap [%0];" ::"l"(m) : "memory");
    }
    __syncthreads();
    const int wc0 = h * 128 + nh * 64;
#define W_LOAD(i)                                                                                                     \
    if (lane == 0) {                                                                                                  \
        mbar_expect_tx(bars + 8 * (B_W + (i)), 16384);                                                                \
        tma2d(sb + ((i) < 4 ? O_XB : (i) < 8 ? O_WO : O_WV) + ((i) & 3) * 16384, (i) < 4 ? &tm_wk : (i) < 8 ? &tm_wq : &tm_wv, \
              wc0, kh * 512 + ((i) & 3) * 128, bars + 8 * (B_W + (i)));                                               \
    }
#define X_LOAD(dst, sg, u, bar) tma4d(sb + (dst), &tm_x, kh * 8 + (u) * 4, ((sg) & 63) * 4, bars + 8 * (bar))
#define X_REFILL(sg, u) { const int b_ = (X_HALF && (u)) ? B_XF1 : B_XFULL; if (EXP & 1) mbar_arrive(bars + 8 * b_); else { mbar_expect_tx(bars + 8 * b_, 16384); X_LOAD(O_XB + (u) * 20480, sg, u, b_); } }
    const int depth = (tn.opt >> 8) & 15, nearly = 8 + ((tn.opt >> 4) & 7);
    if (wgi == 0 && w == 3) {
        if (lane == 0) {
            mbar_expect_tx(bars + 8 * B_F1, 32768);
            tma_ld4(sb + O_F1, &fm.x, (role & 15) * 64, role >> 4, bars + 8 * B_F1);
        }
#pragma unroll 1
        for (int i = 0; i < nearly; i++) {
            if (i == depth - 2) mbar_wait(bars + 8 * B_F1, 0);
            if (i >= depth) mbar_wait(bars + 8 * (B_W + i - depth), 0);
            W_LOAD(i);
        }
    } else if (wgi == 1 && w == 2 && lane == 0 && role < 4 * (RA + 3)) tma4d_prefetch(&tm_x, j * 4, h * 4);
    GT(7);
    uint32_t mate;
    asm volatile("mapa.shared::cluster.u32 %0, %1, %2;" : "=r"(mate) : "r"(sb), "r"(kh ^ 1));
    if (wgi >= 2) fft_col<false, 1>(role >> 4, role & 15, &fm.x, &fm.y, sb + O_F1, bars + 8 * B_F1, (wgi - 2) * 4 + w, lane, 6);

    if (wgi < 2) {
        asm volatile("setmaxnreg.inc.sync.aligned.u32 176;");
        PIN_IDS();
        uint32_t a[32][4], sf = 0;
        {
            const uint32_t stage = sb + (wgi == 0 ? O_WO : O_XB);
            const uint32_t ad = stage + (((lane >> 4) & 1) * 8 + (lane & 7)) * 128 + (((2 * w + ((lane >> 3) & 1)) ^ (lane & 7)) << 4);
#pragma unroll
            for (int i = 0; i < 4; i++) {
                mbar_wait(bars + 8 * (B_W + 4 * (wgi ^ 1) + i), 0);
#pragma unroll
                for (int ks = 0; ks < 8; ks++) ldsm4t(a[i * 8 + ks], ad + (i * 8 + ks) * 2048);
            }
#pragma unroll
            for (int ks = 0; ks < 32; ks += 2) KEEP2(a[ks][0], a[ks + 1][0]);
            SCHED_FENCE();
            if (lane == 0) mbar_arrive(bars + 8 * (B_QDONE + wgi));
            if (wgi == 0) GT(10); else GT(11);
        }
        asm volatile("barrier.cluster.arrive.relaxed.aligned;" ::: "memory");
        asm volatile("barrier.cluster.wait.acquire.aligned;" ::: "memory");
        uint32_t kp[4];
#define X_PASS(d, dofs)                                                                                    \
        wg_fence();                                                                                        \
        _Pragma("unroll") for (int ks = 0; ks < 32; ks++) { if (ks == 0) wg_rs32<0>(d, a[ks], xdesc(ks) + (dofs)); else wg_rs32<1>(d, a[ks], xdesc(ks) - (ks >> 4) * 256 + (dofs)); } \
        wg_commit();                                                                                       \
        wg_wait<0>();
#define X_FINISH(sg) { if (wgi == 0) x_finish<0>(kp, sg, h, nh * 4 + w, kh, tid, sb); else x_finish<1>(kp, sg, h, nh * 4 + w, kh, tid, sb); }
        mbar_wait(bars + 8 * B_XP, 0);
        if (wgi == 0) GT(8);
#pragma unroll 1
        for (int sg = 0; sg < RA; sg++) {
            float d[16]; uint32_t sn[4];
            X_PASS(d, sg * 2048 - (int)((O_XB - O_WO) >> 4));
            if (sg > 0) {
                if (lane == 0) mbar_arrive(bars + 8 * B_XPE);
                x_wait(wgi, sg - 1, sb); X_FINISH(sg - 1);
            }
            x_split(d, sn, kp, kh);
            x_send(wgi, sn, sg, tid, sb, mate);
        }
        x_wait(wgi, RA - 1, sb); X_FINISH(RA - 1);
        const int lq = wgi == 0 ? 4 : 0;
        const uint32_t xbar = bars + 8 * (wgi ? B_QX : B_OPDONE);
#pragma unroll 1
        for (int s = 0; s < 64; s++) {
            TSI(s);
            uint32_t* ap = (uint32_t*)&g_alpha[((s & 1) * 32 + h) * (3 * 512) + wgi * 512 + ((nh * 4 + w) * 2 + kh) * 32] + lane;
            uint32_t mb0 = sb + O_MEM + (lane & 7) * 128 + (((lane >> 3) ^ (lane & 7)) << 4), mb1 = mb0 ^ 64;
            const uint32_t tag = ((s >> 1) & 1) ^ 1;
            const uint32_t tm = (lane & 7) ? ~0u : ~1u, tt = tag & ~tm;
            {
                float d[16]; uint32_t sn[4];
                mbar_wait(bars + 8 * B_XFULL, s & 1);
                mbar_wait(xbar, s & 1);
                TS(6);
                wg_fence();
#pragma unroll
                for (int ks = 0; ks < 32; ks++) {
                    if (ks == 0) wg_rs32<0>(d, a[ks], xdesc(ks)); else if (!(EXP & 4) || ks >= 8) wg_rs32<1>(d, a[ks], xdesc(ks));
                    if (ks == X_SEQ - 1) wg_commit();
                    if (X_HALF && ks == 15) { mbar_wait(bars + 8 * B_XF1, s & 1); wg_fence(); }
                }
                wg_commit();
                KEEP2(mb0, mb1); KEEPP(ap); KEEP2(tm, tt);
                SCHED_FENCE();
                wg_wait<1>();
                if (tid < lq) mbar_arrive(bars + 8 * B_QX);
                wg_wait<0>();
                TS(7);
                if (lane == 0) mbar_arrive(bars + 8 * B_MEM);
                x_split(d, sn, kp, kh);
                if (!(EXP & 8)) x_send(wgi, sn, s + RA, tid, sb, mate); else { KEEP2(sn[0], sn[1]); KEEP2(sn[2], sn[3]); KEEP2(kp[0], kp[1]); KEEP2(kp[2], kp[3]); }
                TS(4);
            }
            float e[2][4];
#pragma unroll
            for (int i = 0; i < 4; i++) e[0][i] = e[1][i] = 0.f;
            mbar_wait(bars + 8 * B_MEM, s & 1);
            TS(0);
#pragma unroll
            for (int ks = 0; ks < 32; ks += 2) {
                uint32_t b[4];
                ldsm4(b, ((ks & 2) ? mb1 : mb0) + kb_off(ks >> 2));
                mma16816(e[0], a[ks][0], a[ks][1], a[ks][2], a[ks][3], b[0], b[1]);
                mma16816(e[1], a[ks + 1][0], a[ks + 1][1], a[ks + 1][2], a[ks + 1][3], b[2], b[3]);
            }
            TS(2);
            if (QKW_POS == 0) { SCHED_FENCE(); if (lane == 0) mbar_arrive(bars + 8 * B_QKW); }
            stg_rlx32(ap, (pack_bf16(e[0][0] + e[1][0], e[0][1] + e[1][1]) & tm) | tt);
            stg_rlx32(ap + 32, (pack_bf16(e[0][2] + e[1][2], e[0][3] + e[1][3]) & tm) | tt);
            if (QKW_POS == 1 && lane == 0) mbar_arrive(bars + 8 * B_QKW);
            TS(3);
            if (wgi == 1) {
                const uint2* vp = &g_alpha[((s & 1) * 32 + h) * (3 * 512) + 1024 + w * 128 + lane];
                const uint32_t vs = sb + O_VM + tid * 16;
                KEEPP(vp); KEEP2(vs, 0);
                mbar_wait(bars + 8 * B_QST, s & 1);
                uint32_t n, bad;
                asm volatile("ld.shared.u32 %0, [%1];" : "=r"(n) : "r"(bars + 504) : "memory");
                wait_gtime(n + tn.d_v);
                TS(8);
                n = 0;
                do {
                    uint2 va[4];
#pragma unroll
                    for (int i = 0; i < 4; i++) va[i] = ldg_rlx64(vp + i * 32);
                    if (++n > SPIN_LIMIT) __trap();
                    bad = (orx2(va[0].x, va[1].x, tag) | orx2(va[2].x, va[3].x, tag)) & 1;
                    sts128u(vs, make_uint4((add_bf16x2(va[0].x, va[1].x) & ~1u) | ((~s ^ bad) & 1), add_bf16x2(va[0].y, va[1].y),
                                                             add_bf16x2(va[2].x, va[3].x), add_bf16x2(va[2].y, va[3].y)));
                } while (__any_sync(~0u, bad));
                TS(9);
                TSV(16 + w, n - 1);
                LT(s, 4 + w, n - 1);
            }
            if (!(EXP & 8)) {
                x_wait(wgi, s + RA, sb);
                mbar_wait(bars + 8 * FIN_BAR, s & 1);
                X_FINISH(s + RA);
                TS(5);
            }
        }
        sts32(bars + 508, sf);
        TSDUMP();
        asm volatile("bar.arrive 7, 512;" ::: "memory");
        float d[64];
        int st = 0, ph = 0;
#pragma unroll 1
        for (int kt = 0; kt < 64; kt++) {
            mbar_wait(bars + 8 * (B_GF + st), ph);
            if (kt == 0) GT(4);
            const uint64_t da = mkdesc(SM_BASE + st * 32768 + wgi * 8192, 128, 1024, 0), db = mkdesc(SM_BASE + st * 32768 + 16384, 8192, 1024, 1);
            wg_fence();
#pragma unroll
            for (int k = 0; k < 4; k++) wg_ss128(d, da + k * 16, db + k * 128, kt | k);
            wg_commit();
            if (kt > 0) {
                wg_wait<1>();
                if (lane == 0) mbar_arrive(bars + 8 * (B_GE + (st == 0 ? G_ST - 1 : st - 1)));
            }
            if (++st == G_ST) { st = 0; ph ^= 1; }
        }
        wg_wait<0>();
        {
            const uint32_t sl = sb + O_F1 + (wgi * 4 + w) * 4096;
#pragma unroll
            for (int i = 0; i < 8; i++)
                stsm4(sl + (lane & 15) * 256 + (((2 * i + (lane >> 4)) ^ (lane & 7)) << 4), pack_bf16(d[8 * i], d[8 * i + 1]),
                      pack_bf16(d[8 * i + 2], d[8 * i + 3]), pack_bf16(d[8 * i + 4], d[8 * i + 5]), pack_bf16(d[8 * i + 6], d[8 * i + 7]));
            __syncwarp();
            bf16* op = out + (size_t)((role >> 3) * 128 + wgi * 64 + w * 16 + (lane >> 4)) * 2048 + 1024 + (role & 7) * 128 + (lane & 15) * 8;
#pragma unroll
            for (int i = 0; i < 8; i++) {
                const int r = 2 * i + (lane >> 4);
                const uint4 v = lds128u(sl + r * 256 + (((lane & 15) ^ (r & 7)) << 4));
                stg128(op + (size_t)i * 4096, v.x, v.y, v.z, v.w);
            }
        }
        GT(5);
    } else if (wgi == 2) {
        asm volatile("setmaxnreg.dec.sync.aligned.u32 64;");
        PIN_IDS();
        asm volatile("barrier.cluster.arrive.relaxed.aligned;" ::: "memory");
        if (w == 0) {
            mbar_wait(bars + 8 * B_KDONE, 0);
            if (lane == 0) { X_REFILL(RA, 0); X_REFILL(RA, 1); }
            mbar_wait(bars + 8 * B_QDONE, 0);
            if (lane == 0) { mbar_expect_tx(bars + 8 * B_XP, 65536); for (int i = 0; i < 4; i++) X_LOAD(O_WO + i * 16384, i >> 1, i & 1, B_XP); }
#pragma unroll 1
            for (int i = nearly; i < 12; i++) { mbar_wait(bars + 8 * (B_W + i - depth), 0); W_LOAD(i); }
        }
        asm volatile("barrier.cluster.wait.acquire.aligned;" ::: "memory");
#pragma unroll 1
        for (int i = 8; i < 12; i++) mbar_wait(bars + 8 * (B_W + i), 0);
        GT(12);
        uint32_t sf = 0, tref = gtime() - 4000;
        uint32_t* const stp = lane < 8 ? (uint32_t*)g_qst + role * 8 + lane : (uint32_t*)g_stamp + role;
#define STAMP(st) { mbar_wait(bars + 8 * B_MEM, (st) & 1); if (lane < 9) stg_rlx32(stp, gtime()); }
#define V_PASS(d)                                                                                          \
        wg_fence();                                                                                        \
        _Pragma("unroll") for (int ks = 0; ks < 32; ks++) {                                                \
            constexpr uint64_t da0 = mkdesc(SM_BASE + O_WV, 16, 1024, 1);                                  \
            if (ks == 0) wg_ss40<0>(d, da0 + ks * 128, xdesc(ks)); else wg_ss40<1>(d, da0 + ks * 128, xdesc(ks)); \
            if (ks == V_SEQ - 1) wg_commit();                                                              \
        }                                                                                                  \
        wg_commit();                                                                                       \
        if (V_SEQ) wg_wait<1>();                                                                           \
        if (V_SEQ && lane == 0) mbar_arrive(bars + 8 * B_VA);        \
        wg_wait<0>();
        mbar_wait(bars + 8 * B_XP, 0);
        {
            uint32_t kp[4];
#pragma unroll 1
            for (int sg = 0; sg <= RA; sg++) {
                float d[20]; uint32_t sn[4];
                if (sg < RA) {
#pragma unroll
                    for (int i = 0; i < 20; i++) d[i] = 0.f;
#pragma unroll 1
                    for (int kb = 0; kb < 8; kb++) {
                        const uint64_t da = mkdesc(SM_BASE + O_WV, 16, 1024, 1) + kb * 512, db = mkdesc(SM_BASE + O_WO, 16, 4096, 1) + sg * 2048 + (kb >> 2) * 1024 + (kb & 3) * 64;
                        wg_fence();
#pragma unroll
                        for (int i = 0; i < 4; i++) wg_ss40<1>(d, da + i * 128, db + i * 2);
                        wg_commit();
                    }
                    wg_wait<0>();
                }
                if (sg == RA - 1) {
                    if (lane == 0) mbar_arrive(bars + 8 * B_XPE);
                    if (w == 0) {
                        mbar_wait(bars + 8 * B_XPE, 0);
                        GT(9);
                        if (lane == 0) {
                            mbar_expect_tx(bars + 8 * B_WO, 65536);
#pragma unroll
                            for (int i = 0; i < 4; i++) tma2d(sb + O_WO + i * 16384, &tm_wo, j * 256 + i * 64, h * 128, bars + 8 * B_WO);
                        }
                    }
                }
                if (sg > 0) { x_wait(2, sg - 1, sb); x_finish<2>(kp, sg - 1, h, nh * 4 + w, kh, tid, sb); }
                if (sg < RA) { x_split(d, sn, kp, kh); x_send(2, sn, sg, tid, sb, mate); }
            }
        }
        if (STAMP_V && w == 2) STAMP(0);
#pragma unroll 1
        for (int s = 0; s < 64; s++) {
            TSI(s);
            OPAQUE_IDS();
            uint2* ap = &g_alpha[((s & 1) * 32 + h) * (3 * 512) + 1024 + ((nh * 4 + w) * 2 + kh) * 32 + lane];
            KEEPP(ap);
            float d[20];
            mbar_wait(bars + 8 * B_QKW, s & 1);
            TS(0);
            if (s == 0) GT(14);
            V_PASS(d);
            TS(1);
            stg_rlx64(ap, (pack_bf16(d[16], d[17]) & ~1u) | (((s >> 1) & 1) ^ 1), pack_bf16(d[18], d[19]));
            if (lane == 0) mbar_arrive(bars + 8 * B_XEMPTY);
            if (s == 63) break;
            uint32_t sn[4], kp[4];
            x_split(d, sn, kp, kh);
            if (w == 3) {
                uint32_t n = 0, mx;
                do {
                    const uint4 st = ldg_rlx128(&g_stamp[lane]);
                    mx = __reduce_max_sync(~0u, max(max(st.x - tref, st.y - tref), max(st.z - tref, st.w - tref)));
                    if (DBG_TIMING) TSV(14, mx - __reduce_min_sync(~0u, min(min(st.x - tref, st.y - tref), min(st.z - tref, st.w - tref))));
                } while (mx >= 200000u && ++n < 64);
                tref = mx < 200000u ? tref + mx + 1 : gtime();
                TSV(12, clk()); TSV(13, n);
            }
            if (w == 0) {
                mbar_wait(bars + 8 * B_XEMPTY, s & 1);
                mbar_wait(bars + 8 * B_SRDY, s & 1);
                if (lane == 0) { X_REFILL(s + RA + 1, 0); X_REFILL(s + RA + 1, 1); }
            } else if (w == 1) {
                const uint4* hb = &g_kvq[(((s + 1) & 3) * 32 + h) * (3 * 512)];
                if (V_KEEP) { mbar_wait(bars + 8 * B_SRDY, s & 1); wait_clk(clk(), tn.spread); } else mbar_wait(bars + 8 * B_X0, s & 1);
                if (lane == 0) {
                    if (EXP & 2) mbar_arrive(bars + 8 * B_KVFULL); else {
                    mbar_expect_tx(bars + 8 * B_KVFULL, 18432);
                    bulk_g2s(sb + O_KVQ, hb + 512, 16384, bars + 8 * B_KVFULL);
                    bulk_g2s(sb + O_KVQ + 16384, hb + j * 128, 2048, bars + 8 * B_KVFULL);
                    }
                }
            }
            mbar_wait(bars + 8 * B_OPDONE, (s + 1) & 1);
            if (!(EXP & 8)) x_send(2, sn, s + RA, tid, sb, mate); else { KEEP2(sn[0], sn[1]); KEEP2(sn[2], sn[3]); KEEP2(kp[0], kp[1]); KEEP2(kp[2], kp[3]); }
            if (w == 3) {
                wait_gtime(tref + tn.d_r);
                if (lane == 0) {
                    mbar_expect_tx(bars + 8 * B_RFULL, 16384);
                    bulk_g2s(sb + O_STG, redp + (s & 3) * 32768 + kh * 16384, 16384, bars + 8 * B_RFULL);
                }
                TSV(3, clk());
            }
            if (!V_LATE && !(EXP & 8)) { x_wait(2, s + RA, sb); x_finish<2>(kp, s + RA, h, nh * 4 + w, kh, tid, sb); TS(6); }
            if (DBG_TIMING && w == 0) { mbar_wait(bars + 8 * B_RFULL, s & 1); TS(4); }
            const uint32_t n = convert_mem(redp, s, kh, 0, w, lane, sb, sf); (void)n;
            TS(5);
            TSV(8 + w, n);
            LT(s, 8 + w, n);
            if (STAMP_V && w == 2) STAMP(s + 1);
            if (V_LATE && !(EXP & 8)) { x_wait(2, s + RA, sb); x_finish<2>(kp, s + RA, h, nh * 4 + w, kh, tid, sb); }
        }
        sts32(bars + 508, sf);
        TSDUMP();
        asm volatile("bar.arrive 7, 512;" ::: "memory");
    } else {
        asm volatile("setmaxnreg.dec.sync.aligned.u32 96;");
        PIN_IDS();
        GT(0);
        asm volatile("barrier.cluster.arrive.relaxed.aligned;" ::: "memory");
#define RED_CLEAR(st)                                                                                           \
        if (lane < 16) {                                                                                        \
            const uint32_t cb = ((st) & 4) ? 0x42800000u : 0u;                                                  \
            stg128(redp + ((st) & 3) * 32768 + role * 256 + lane * 16, 0, (role & 2) ? cb : 0u, 0, cb);        \
        }
        if (w == 0) {
            RED_CLEAR(0); RED_CLEAR(1); RED_CLEAR(2);
            if (lane == 0) { tma_st4(sb + O_F1, &fm.y, (role & 15) * 64, role >> 4); bulk_commit(); }
        }
        sts128u(sb + O_VM + tid * 16, make_uint4(0, 0, 0, 0));
        {
            uint4 v[4];
#pragma unroll
            for (int q = 0; q < 4; q++) v[q] = *(const uint4*)(mem0 + ((lane >> 3) + (q & 1) * 4) * 1024 + kh * 512 + (2 * w + (q >> 1)) * 64 + (lane & 7) * 8);
            mbar_wait(bars + 8 * B_KDONE, 0);
#pragma unroll
            for (int q = 0; q < 4; q++) {
                const int row = (lane >> 3) + (q & 1) * 4;
                sts128u(sb + O_MEM + kb_off(2 * w + (q >> 1)) + row * 128 + (((lane & 7) ^ row) << 4), v[q]);
            }
            fence_async_smem();
            __syncwarp();
            if (lane < 2) { mbar_arrive(bars + 8 * B_MEM); mbar_arrive(bars + 8 * B_QKW); }
            if (lane == 0) mbar_arrive(bars + 8 * B_OPDONE);
            if (tid == 0) mbar_arrive(bars + 8 * B_KVFULL);
        }
        asm volatile("barrier.cluster.wait.acquire.aligned;" ::: "memory");
        if (w == 0) {
            if (lane == 0) bulk_wait_all();
            __syncwarp();
            gbar_wait(&g_start, gbar_arrive(&g_start, 1, 256, lane), 0);
            GT(13);
        }
        if (w == 1) {
            mbar_wait(bars + 8 * (B_W + 10), 0);
            uint32_t t = gtime();
#pragma unroll 1
            for (int i = 0; i < 4; i++) { if (lane == 0) tma2d_prefetch(&tm_wo, j * 256 + i * 64, h * 128); t += tn.extra; if (i < 3) wait_gtime(t); }
        }
        bar_sync(1, 128);
        uint32_t sf = 0, xo[4];
#define XO_STORE(st) { uint32_t* op = (uint32_t*)g_ox + ((size_t)((st) * 4 + j) * 4096 + h * 128 + w * 32) * 4 + lane; op[0] = xo[0]; op[32] = xo[1]; op[64] = xo[2]; op[96] = xo[3]; }
#pragma unroll 1
        for (int s = 0; s < 64; s++) {
            TSI(s);
            OPAQUE_IDS();
            uint32_t kf[4][4], qf[4];
            const uint32_t l03 = lane < 4;
            const uint32_t tg = ((s >> 2) & 1) ^ 1;
            {
                const uint32_t ka = sb + O_KVQ + w * 2048 + lane * 16, qa = sb + O_KVQ + 16384 + w * 512 + lane * 16;
                uint32_t n = s == 0;
                bool redo;
#pragma unroll 1
                do {
                    asm volatile("" : "+r"(n));
                    if (n) {
                        const uint4* hb = &g_kvq[((s & 3) * 32 + __shfl_sync(~0u, h, 0)) * (3 * 512)];
                        uint4 x[4], y[4], z;
                        do {
#pragma unroll
                            for (int i = 0; i < 4; i++) { x[i] = ldg_rlx128(hb + 512 + w * 128 + i * 32 + lane); y[i] = ldg_rlx128(hb + 1024 + w * 128 + i * 32 + lane); }
                            z = ldg_rlx128(hb + j * 128 + w * 32 + lane);
                            if (++n > SPIN_LIMIT) __trap();
                        } while (__any_sync(~0u, (orx2(y[0].x, y[1].x, tg) | orx2(y[2].x, y[3].x, tg)) & 1));
#pragma unroll
                        for (int i = 0; i < 4; i++) { sts128u(ka + i * 512, x[i]); sts128u(ka + 8192 + i * 512, y[i]); }
                        sts128u(qa, z);
                        fence_async_smem();
                    }
                    n++;
                    mbar_wait(bars + 8 * B_KVFULL, s & 1);
#pragma unroll
                    for (int i = 0; i < 4; i++) ldsm4t(kf[i], ka + i * 512);
                    ldsm4t(qf, qa);
                    redo = __any_sync(~0u, or3(or3(tags4(kf[0], tg), tags4(kf[1], tg), tags4(kf[2], tg)), tags4(kf[3], tg), tags4(qf, tg)) & l03 & ((EXP & 10) ? s >> 8 : ~0u));
                } while (redo);
                if (w == 0) TSV(22, n - 1);
            }
            TS(9);
            if (s == 0) GT(15);
            if (s > 0) {
                if (XO_POS == 0) XO_STORE(s - 1);
                const uint32_t n = convert_mem(redp, s - 1, kh, 1, w, lane, sb, sf); (void)n;
                TS(11);
                TSV(16 + w, n);
                LT(s - 1, 12 + w, n);
                if (XO_POS == 1) XO_STORE(s - 1);
                if (w == 1 && s < 62) RED_CLEAR(s + 2);
            }
            const uint32_t tag = ((s >> 1) & 1) ^ 1;
            const uint4* ap = (const uint4*)&g_alpha[((s & 1) * 32 + h) * (3 * 512) + w * 128] + lane;
            const uint32_t l16 = sb + lane * 16, l4 = sb + lane * 4;
            const uint32_t sw = l16 + O_S + w * 2560, sr = l4 + O_S + w * 128;
            uint32_t pw = sb + O_P + ((lane >> 1) & 1) * 704 + (2 * w + (lane >> 4)) * 16 + ((lane >> 2) & 3) * 4 + (lane & 1) * 2;
            int lim = (lane & 2) ? 8 * j + 2 * w + (lane >> 4) - 2 * ((lane >> 2) & 3) - (lane & 1) : 64;
            const uint32_t aa = l16 + O_STG + w * 1024;
            unsigned char* pa = redp + (s & 3) * 32768 + red_grp(j * 16 + (tid >> 3));
            unsigned char* pb = pa + 512 + ((lane >> 3) & 1) * 64 + (lane & 7) * 8;
            pa += (lane & 7) * 16;
            KEEPP(pa); KEEPP(pb);
            KEEP2(l16, l4); KEEP2(pw, lim); KEEP2(l03, tag);
            TS(0);
            if (w == 0) {
                const uint32_t* qp = (const uint32_t*)g_qst + h * 32 + lane;
                KEEPP(qp);
                mbar_wait(bars + 8 * B_MEM, s & 1);
                uint32_t tq = gtime() - 1024;
                if (!STAMP_V && lane < 9) stg_rlx32(lane < 8 ? (uint32_t*)g_qst + role * 8 + lane : (uint32_t*)g_stamp + role, tq + 1024);
                wait_clk(clk(), tn.d_q);
                uint32_t n = 0, mx;
                do { mx = __reduce_max_sync(~0u, ldg_rlx32(qp) - tq); } while (mx > 100000u && ++n < 16);
                TSV(13, n);
                LT(s, 2, n);
                tq += mx <= 100000u ? mx : 1024;
                if (lane == 0) { sts32(bars + 504, tq); mbar_arrive(bars + 8 * B_QST); }
                TS(14);
                mbar_wait(bars + 8 * B_QKW, s & 1);
                TS(1);
                wait_gtime(tq + tn.d_alpha);
                if (lane == 0) {
                    mbar_expect_tx(bars + 8 * B_AFULL, 8192);
                    bulk_g2s(sb + O_STG, ap, 8192, bars + 8 * B_AFULL);
                }
                if (s == 0) { mbar_wait(bars + 8 * B_WO, 0); GT(1); }
            }
            {
                uint32_t n = 0;
                bool redo;
#pragma unroll 1
                do {
                    asm volatile("" : "+r"(n));
                    if (n) {
                        uint4 x[4];
#pragma unroll
                        for (int q = 0; q < 4; q++) x[q] = ldg_rlx128(ap + (q >> 1) * 256 + (q & 1) * 32);
#pragma unroll
                        for (int q = 0; q < 4; q++) sts128u(aa + (q >> 1) * 4096 + (q & 1) * 512, x[q]);
                        __syncwarp();
                        if (n > SPIN_LIMIT) __trap();
                    }
                    n++;
                    mbar_wait(bars + 8 * B_AFULL, s & 1);
                    TS(12);
                    if (V_SEQ) mbar_wait(bars + 8 * B_VA, s & 1);
                    uint32_t qa[2][4], ka[2][4];
#pragma unroll
                    for (int u = 0; u < 2; u++) { ldsm4t(qa[u], aa + u * 512); ldsm4t(ka[u], aa + 4096 + u * 512); }
                    float sa[5][4];
#pragma unroll
                    for (int i = 0; i < 5; i++) sa[i][0] = sa[i][1] = sa[i][2] = sa[i][3] = 0.f;
#pragma unroll
                    for (int u = 0; u < 2; u++) {
                        const uint32_t q0 = add_bf16x2(qa[u][0], qa[u][2]), q1 = add_bf16x2(qa[u][1], qa[u][3]);
                        mma16816(sa[1], q0, qf[2 * u], q1, qf[2 * u + 1], kf[2 * u][0], kf[2 * u][1]);
                        mma16816(sa[2], q0, qf[2 * u], q1, qf[2 * u + 1], kf[2 * u][2], kf[2 * u][3]);
                        mma16816(sa[3], q0, qf[2 * u], q1, qf[2 * u + 1], kf[2 * u + 1][0], kf[2 * u + 1][1]);
                        mma16816(sa[4], q0, qf[2 * u], q1, qf[2 * u + 1], kf[2 * u + 1][2], kf[2 * u + 1][3]);
                        const uint32_t k0 = add_bf16x2(ka[u][0], ka[u][2]), k1 = add_bf16x2(ka[u][1], ka[u][3]);
                        mma16816(sa[0], q0, qf[2 * u], q1, qf[2 * u + 1], k0, k1);
                        if (u == 0) SCHED_FENCE();
                    }
                    redo = __any_sync(~0u, (or3(tags4(qa[0], tag), tags4(ka[0], tag), tags4(qa[1], tag)) | tags4(ka[1], tag)) & l03);
#pragma unroll
                    for (int i = 1; i <= 5; i++) sts128(sw + (i % 5) * 512, sa[i % 5][0], sa[i % 5][1], sa[i % 5][2], sa[i % 5][3]);
                } while (redo);
                if (w == 0) TSV(20, n - 1);
                if (n > 1) LT(s, 3, 0x10000 + s);
            }
            TS(2);
            bar_sync(1, 128);
            float sc[5];
            {
                float x[4][5];
#pragma unroll
                for (int q = 0; q < 4; q++)
#pragma unroll
                    for (int n = 0; n < 5; n++) asm volatile("ld.shared.f32 %0, [%1];" : "=f"(x[q][n]) : "r"(sr + q * 2560 + n * 512) : "memory");
#pragma unroll
                for (int n = 0; n < 5; n++) sc[n] = (x[0][n] + x[1][n]) + (x[2][n] + x[3][n]);
            }
            TS(15);
#pragma unroll
            for (int n = 1; n < 5; n++) if (8 * (n - 1) > lim) sc[n] = MASK_VAL;
            float m = fmaxf(fmaxf(fmaxf(sc[0], sc[1]), fmaxf(sc[2], sc[3])), sc[4]);
            m = fmaxf(m, __shfl_xor_sync(~0u, m, 1));
            m = fmaxf(m, __shfl_xor_sync(~0u, m, 4));
            m = fmaxf(m, __shfl_xor_sync(~0u, m, 8));
            SCHED_FENCE();
            uint4 vf[4];
#pragma unroll
            for (int i = 0; i < 4; i++) vf[i] = lds128u(l16 + O_KVQ + 8192 + w * 2048 + i * 512);
            m *= -SM_SCALE_LOG2;
#pragma unroll
            for (int n = 0; n < 5; n++) {
                const uint32_t pv = pack_bf16(ex2(fmaf(sc[n], SM_SCALE_LOG2, m)), 0.f);
                asm volatile("st.shared.u16 [%0], %1;" ::"r"(pw + n * 128), "h"((uint16_t)pv) : "memory");
            }
            if (V_KEEP) { KEEP2(vf[0].x, vf[1].x); KEEP2(vf[2].x, vf[3].x); SCHED_FENCE(); }
            bar_sync(1, 128);
            TS(3);
            if (lane == 0) mbar_arrive(bars + 8 * B_SRDY);
            float ox[2][4], sm[4], sx[4], cc[4][4];
#pragma unroll 1
            for (uint32_t nv = 0;; nv++) {
                uint32_t pf[4], p0, px[4], px0;
                ldsm4(pf, l16 + O_P + 128);
                ldsm4(px, l16 + O_P + 128 + 704);
                asm volatile("ld.shared.u32 %0, [%1];" : "=r"(p0) : "r"(l4 + O_P) : "memory");
                asm volatile("ld.shared.u32 %0, [%1];" : "=r"(px0) : "r"(l4 + O_P + 704) : "memory");
                float o[2][4];
#pragma unroll
                for (int i = 0; i < 4; i++) o[0][i] = o[1][i] = ox[0][i] = ox[1][i] = sm[i] = sx[i] = 0.f;
                constexpr uint32_t ONE2 = 0x3f803f80u;
                mma1688(sm, ONE2, ONE2, p0);
                mma1688(sx, ONE2, ONE2, px0);
#pragma unroll
                for (int c = 0; c < 2; c++) {
#pragma unroll
                    for (int u = 0; u < 2; u++) mma16816(o[u], vf[2 * u + c].x, vf[2 * u + c].y, vf[2 * u + c].z, vf[2 * u + c].w, pf[2 * c], pf[2 * c + 1]);
#pragma unroll
                    for (int u = 0; u < 2; u++) mma16816(ox[u], vf[2 * u + c].x, vf[2 * u + c].y, vf[2 * u + c].z, vf[2 * u + c].w, px[2 * c], px[2 * c + 1]);
                    mma16816(sm, ONE2, ONE2, ONE2, ONE2, pf[2 * c], pf[2 * c + 1]);
                    mma16816(sx, ONE2, ONE2, ONE2, ONE2, px[2 * c], px[2 * c + 1]);
                }
                const uint32_t vbad = orx(orx(orx2(vf[0].x, vf[1].x, tg), vf[2].x, tg), vf[3].x, tg);
                uint4 vm;
                {
                    uint32_t n = 0;
                    bool redo;
#pragma unroll 1
                    do {
                        vm = lds128v(l16 + O_VM + w * 512);
                        float o2[2][4];
#pragma unroll
                        for (int i = 0; i < 4; i++) { o2[0][i] = o[0][i]; o2[1][i] = o[1][i]; }
                        mma1688(o2[0], vm.x, vm.y, p0);
                        mma1688(o2[1], vm.z, vm.w, p0);
                        redo = __any_sync(~0u, ((vm.x ^ ~s) & 1) && ++n < SPIN_LIMIT);
                        const uint32_t oa = l4 + O_O + w * 512;
                        sts32(oa, pack_bf16(o2[0][0], o2[0][1]));
                        sts32(oa + 128, pack_bf16(o2[0][2], o2[0][3]));
                        sts32(oa + 256, pack_bf16(o2[1][0], o2[1][1]));
                        sts32(oa + 384, pack_bf16(o2[1][2], o2[1][3]));
                    } while (redo);
                    if (w == 0) TSV(21, n);
                }
                TS(4);
                fence_async_smem();
                mma1688(ox[0], vm.x, vm.y, px0);
                mma1688(ox[1], vm.z, vm.w, px0);
                sm[0] = rcp(sm[0]); sm[1] = rcp(sm[1]);
                bar_sync(1, 128);
                if (!V_KEEP && lane == 0 && nv == 0) mbar_arrive(bars + 8 * B_X0);
                TS(5);
#define OP_ISSUE(t0, t1)                                                                                       \
                wg_fence();                                                                                    \
                _Pragma("unroll") for (int ks = 0; ks < 8; ks++)                                               \
                    _Pragma("unroll") for (int t = t0; t < t1; t++) {                                          \
                        constexpr uint64_t da0 = mkdesc(SM_BASE + O_WO, 16, 1024, 1), db0 = mkdesc(SM_BASE + O_O, 128, 128, 0); \
                        if (ks == 0) wg_ss8<0>(cc[t], da0 + t * 1024, db0); else wg_ss8<1>(cc[t], da0 + t * 1024 + ks * 128, db0 + ks * 16); \
                    }                                                                                          \
                wg_commit();
                OP_ISSUE(0, (OP_SPLIT ? 2 : 4));
                if (!bar_or(1, 128, vbad & ((EXP & 10) ? s >> 8 : ~0u))) break;
                wg_wait<0>();
                const uint4* vp = &g_kvq[((s & 3) * 32 + h) * (3 * 512) + 1024 + w * 128 + __shfl_sync(~0u, lane, lane)];
#pragma unroll
                for (int i = 0; i < 4; i++) vf[i] = ldg_rlx128(vp + i * 32);
                if (nv > SPIN_LIMIT) __trap();
                bar_sync(1, 128);
            }
            {
                const float i0 = sm[0], i1 = sm[1];
#pragma unroll
                for (int hf = 0; hf < 2; hf++) {
                    if (hf == 0 || OP_SPLIT) wg_wait<0>();
                    if (hf == 0) TS(6);
                    if (OPD_EARLY && hf == OP_SPLIT && lane == 0) mbar_arrive(bars + 8 * B_OPDONE);
                    asm volatile("red.relaxed.gpu.global.add.noftz.v4.bf16x2 [%0], {%1,%2,%3,%4};" ::"l"(pa + hf * 128),
                                 "r"(pack_bf16(cc[2 * hf][0] * i0, cc[2 * hf][1] * i1)), "r"(pack_bf16(cc[2 * hf][2] * i0, cc[2 * hf][3] * i1)),
                                 "r"(pack_bf16(cc[2 * hf + 1][0] * i0, cc[2 * hf + 1][1] * i1)), "r"(pack_bf16(cc[2 * hf + 1][2] * i0, 1.f)) : "memory");
                    if (OP_SPLIT && hf == 0) { SCHED_FENCE(); OP_ISSUE(2, 4); }
                }
                asm volatile("red.relaxed.gpu.global.add.noftz.v2.bf16x2 [%0], {%1,%2};" ::"l"(pb), "r"(pack_bf16(cc[1][3] * i1, cc[3][3] * i1)), "r"(0x3f800000u) : "memory");
                if (!OPD_EARLY && lane == 0) mbar_arrive(bars + 8 * B_OPDONE);
                SCHED_FENCE();
                TS(7);
            }
            {
                const float ix0 = rcp(sx[0]), ix1 = rcp(sx[1]);
                xo[0] = pack_bf16(ox[0][0] * ix0, ox[0][1] * ix1); xo[1] = pack_bf16(ox[0][2] * ix0, ox[0][3] * ix1);
                xo[2] = pack_bf16(ox[1][0] * ix0, ox[1][1] * ix1); xo[3] = pack_bf16(ox[1][2] * ix0, ox[1][3] * ix1);
                if (XO_POS == 2) XO_STORE(s);
            }
            TS(8);
            if (w == 2) { LT(s, 0, gtime()); LT(s, 1, clk()); }
            if (s == 0) GT(2);
        }
        if (XO_POS < 2) XO_STORE(63);
        GT(3);
        sts32(bars + 508, sf);
        TSDUMP();
        bar_sync(7, 512);
        const int m0 = (role >> 3) * 16, nb = (role & 7) * 2;
#define W2_LOAD(st, kt) { mbar_expect_tx(bars + 8 * (B_GF + (st)), 32768); tma3d(sb + (st) * 32768 + 16384, &tm_w2, 0, (kt) * 64, nb, bars + 8 * (B_GF + (st))); }
        if (w == 1 && lane == 0) {
            fence_async_smem();
#pragma unroll 1
            for (int kt = 0; kt < G_ST; kt++) W2_LOAD(kt, kt);
        }
        if (w == 0) {
            gbar_wait(&g_end, gbar_arrive(&g_end, 1, 128, lane), 0);
            int st = 0, ph = 1;
#pragma unroll 1
            for (int kt = 0; kt < 64; kt++) {
                if (kt >= G_ST) mbar_wait(bars + 8 * (B_GE + st), ph);
                if (lane == 0) {
                    if (kt >= G_ST) W2_LOAD(st, kt);
                    tma2d(sb + st * 32768, &tm_o, kt * 128, m0, bars + 8 * (B_GF + st));
                }
                if (++st == G_ST) { st = 0; ph ^= 1; }
            }
        }
    }
}

typedef CUresult (*EncodeFn)(CUtensorMap*, CUtensorMapDataType, cuuint32_t, void*, const cuuint64_t*, const cuuint64_t*,
                             const cuuint32_t*, const cuuint32_t*, CUtensorMapInterleave, CUtensorMapSwizzle,
                             CUtensorMapL2promotion, CUtensorMapFloatOOBfill);

static void make_map(EncodeFn fn, CUtensorMap* m, const void* p, uint64_t cols, uint64_t rows, uint32_t bc, uint32_t br) {
    cuuint64_t dims[2] = {cols, rows}, strides[1] = {cols * 2};
    cuuint32_t box[2] = {bc, br}, es[2] = {1, 1};
    fn(m, CU_TENSOR_MAP_DATA_TYPE_BFLOAT16, 2, (void*)p, dims, strides, box, es, CU_TENSOR_MAP_INTERLEAVE_NONE,
       CU_TENSOR_MAP_SWIZZLE_128B, CU_TENSOR_MAP_L2_PROMOTION_L2_128B, CU_TENSOR_MAP_FLOAT_OOB_FILL_NONE);
}

static Tune h_tune = {512, 1952, 16 * 2 + 256 * 4, 100, 992, 300, 600};

extern "C" void kernel_launch(void* const* d_in, const int* in_sizes, int n_in, void* d_out, int out_size) {
    static bool init = false;
    static FftMaps fm;
    static CUtensorMap tm_x, tm_wq, tm_wk, tm_wv, tm_wo, tm_o, tm_wo2;
    if (!init) {
        void* fp = nullptr; cudaDriverEntryPointQueryResult qr;
        cudaGetDriverEntryPoint("cuTensorMapEncodeTiled", &fp, cudaEnableDefault, &qr);
        EncodeFn fn = (EncodeFn)fp;
        void* ox = nullptr; cudaGetSymbolAddress(&ox, g_ox);
        {
            cuuint64_t dims[4] = {64, 8, 16, 256}, strides[3] = {2048, 128, 16384};
            cuuint32_t box[4] = {64, 8, 4, 4}, es[4] = {1, 1, 1, 1};
            fn(&tm_x, CU_TENSOR_MAP_DATA_TYPE_BFLOAT16, 4, d_in[3], dims, strides, box, es, CU_TENSOR_MAP_INTERLEAVE_NONE,
               CU_TENSOR_MAP_SWIZZLE_128B, CU_TENSOR_MAP_L2_PROMOTION_L2_128B, CU_TENSOR_MAP_FLOAT_OOB_FILL_NONE);
        }
        void* fy = nullptr; cudaGetSymbolAddress(&fy, g_fy);
        for (int i = 0; i < 3; i++) {
            const cuuint64_t pitch = i == 2 ? 4096 : 2048;
            cuuint64_t dims[4] = {1024, 8, 16, 16}, strides[3] = {pitch, 128 * pitch, 8 * pitch};
            cuuint32_t box[4] = {64, 1, 16, 16}, es[4] = {1, 1, 1, 1};
            fn(i == 0 ? &fm.x : i == 1 ? &fm.y : &fm.o, CU_TENSOR_MAP_DATA_TYPE_BFLOAT16, 4, i == 0 ? d_in[0] : i == 1 ? fy : d_out, dims, strides, box, es,
               CU_TENSOR_MAP_INTERLEAVE_NONE, CU_TENSOR_MAP_SWIZZLE_128B, CU_TENSOR_MAP_L2_PROMOTION_L2_256B, CU_TENSOR_MAP_FLOAT_OOB_FILL_NONE);
        }
        {
            cuuint64_t dims[3] = {64, 2048, 16}, strides[2] = {2048, 128};
            cuuint32_t box[3] = {64, 8, 16}, es[3] = {1, 1, 1};
            fn(&fm.y2, CU_TENSOR_MAP_DATA_TYPE_BFLOAT16, 3, fy, dims, strides, box, es, CU_TENSOR_MAP_INTERLEAVE_NONE,
               CU_TENSOR_MAP_SWIZZLE_128B, CU_TENSOR_MAP_L2_PROMOTION_L2_128B, CU_TENSOR_MAP_FLOAT_OOB_FILL_NONE);
        }
        for (int i = 0; i < 2; i++) {
            cuuint64_t dims[3] = {256 * 513 - 448, 8, 8}, strides[2] = {128, 256 * 1026};
            cuuint32_t box[3] = {72, 8, 8}, es[3] = {1, 1, 1};
            fn(i ? &fm.wi : &fm.wr, CU_TENSOR_MAP_DATA_TYPE_BFLOAT16, 3, d_in[1 + i], dims, strides, box, es, CU_TENSOR_MAP_INTERLEAVE_NONE,
               CU_TENSOR_MAP_SWIZZLE_NONE, CU_TENSOR_MAP_L2_PROMOTION_L2_128B, CU_TENSOR_MAP_FLOAT_OOB_FILL_NONE);
        }
        fm.w[0] = (const unsigned char*)d_in[1]; fm.w[1] = (const unsigned char*)d_in[2]; fm.w[2] = (const unsigned char*)d_in[3];
        make_map(fn, &tm_wq, d_in[5], 4096, 1024, 64, 128);
        make_map(fn, &tm_wk, d_in[6], 4096, 1024, 64, 128);
        make_map(fn, &tm_wv, d_in[7], 4096, 1024, 64, 128);
        make_map(fn, &tm_wo, d_in[8], 1024, 4096, 64, 128);
        {
            cuuint64_t dims[2] = {8192, 256}, strides[1] = {65536};
            cuuint32_t box[2] = {128, 16}, es[2] = {1, 1};
            fn(&tm_o, CU_TENSOR_MAP_DATA_TYPE_UINT64, 2, ox, dims, strides, box, es, CU_TENSOR_MAP_INTERLEAVE_NONE,
               CU_TENSOR_MAP_SWIZZLE_NONE, CU_TENSOR_MAP_L2_PROMOTION_L2_128B, CU_TENSOR_MAP_FLOAT_OOB_FILL_NONE);
        }
        {
            cuuint64_t dims[3] = {64, 4096, 16}, strides[2] = {2048, 128};
            cuuint32_t box[3] = {64, 64, 2}, es[3] = {1, 1, 1};
            fn(&tm_wo2, CU_TENSOR_MAP_DATA_TYPE_BFLOAT16, 3, d_in[8], dims, strides, box, es, CU_TENSOR_MAP_INTERLEAVE_NONE,
               CU_TENSOR_MAP_SWIZZLE_128B, CU_TENSOR_MAP_L2_PROMOTION_L2_128B, CU_TENSOR_MAP_FLOAT_OOB_FILL_NONE);
        }
        cudaFuncSetAttribute(rmt_main, cudaFuncAttributeMaxDynamicSharedMemorySize, MAIN_SMEM);
        init = true;
    }
    rmt_main<<<132, 512, MAIN_SMEM>>>(tm_x, tm_wq, tm_wk, tm_wv, tm_wo, (const bf16*)d_in[4], h_tune, fm, tm_o, tm_wo2, (bf16*)d_out);
}
```

```cpp
#include <cuda_runtime.h>
#include <cuda_bf16.h>
#include <cuda.h>
#include <stdint.h>

typedef __nv_bfloat16 bf16;

#define DBG_TIMING 0

#define SPIN_LIMIT (1u << 22)

__device__ __forceinline__ uint32_t smem_u32(const void* p) { return (uint32_t)__cvta_generic_to_shared(p); }
__device__ __forceinline__ uint32_t clk() { uint32_t c; asm volatile("mov.u32 %0, %%clock;" : "=r"(c)::"memory"); return c; }
#define SCHED_FENCE() sf ^= (uint32_t)clock64()
#define KEEP2(a, b) asm volatile("lop3.b32 %0, %0, %1, %2, 0x96;" : "+r"(sf) : "r"((uint32_t)(a)), "r"((uint32_t)(b)))
#define KEEPP(p) KEEP2((uintptr_t)(p), (uintptr_t)(p) >> 32)
__device__ __forceinline__ uint32_t gtime() { uint32_t c; asm volatile("mov.u32 %0, %%globaltimer_lo;" : "=r"(c)::"memory"); return c; }
__device__ __forceinline__ void wait_clk(uint32_t t0, uint32_t d) {
    asm volatile("{\n.reg .pred p;\n.reg .s32 t;\n.reg .b64 c;\nWL:\nmov.u64 c, %%clock64;\ncvt.u32.u64 t, c;\nsub.s32 t, t, %0;\nsetp.lt.s32 p, t, 0;\n@p bra.uni WL;\n}" ::"r"(t0 + d) : "memory");
}
__device__ __forceinline__ void wait_gtime(uint32_t t1) {
    asm volatile("{\n.reg .pred p;\n.reg .s32 t;\n.reg .b64 c;\nWL:\nmov.u64 c, %%globaltimer;\ncvt.u32.u64 t, c;\nsub.s32 t, t, %0;\nsetp.lt.s32 p, t, 0;\n@p bra.uni WL;\n}" ::"r"(t1) : "memory");
}

__device__ __forceinline__ void mbar_init(uint32_t bar, uint32_t cnt) {
    asm volatile("mbarrier.init.shared::cta.b64 [%0], %1;" ::"r"(bar), "r"(cnt) : "memory");
}
__device__ __forceinline__ void mbar_arrive(uint32_t bar) {
    asm volatile("mbarrier.arrive.shared::cta.b64 _, [%0];" ::"r"(bar) : "memory");
}
__device__ __forceinline__ void mbar_expect_tx(uint32_t bar, uint32_t bytes) {
    asm volatile("mbarrier.arrive.expect_tx.shared::cta.b64 _, [%0], %1;" ::"r"(bar), "r"(bytes) : "memory");
}
__device__ __forceinline__ void mbar_wait(uint32_t bar, uint32_t parity) {
    asm volatile(
        "{\n.reg .pred p, q;\n.reg .u32 n;\nmov.u32 n, 0;\n"
        "WL:\nmbarrier.try_wait.parity.shared::cta.b64 p, [%0], %1;\n"
        "add.u32 n, n, 1;\nsetp.gt.u32 q, n, %2;\n@q trap;\n@!p bra.uni WL;\n}" ::"r"(bar), "r"(parity), "n"(SPIN_LIMIT) : "memory");
}
__device__ __forceinline__ void mbar_wait_cluster(uint32_t bar, uint32_t parity) {
    asm volatile(
        "{\n.reg .pred p, q;\n.reg .u32 n;\nmov.u32 n, 0;\n"
        "WL:\nmbarrier.try_wait.parity.acquire.cluster.shared::cta.b64 p, [%0], %1;\n"
        "add.u32 n, n, 1;\nsetp.gt.u32 q, n, %2;\n@q trap;\n@!p bra.uni WL;\n}" ::"r"(bar), "r"(parity), "n"(SPIN_LIMIT) : "memory");
}
__device__ __forceinline__ void tma2d(uint32_t dst, const CUtensorMap* m, int c0, int c1, uint32_t bar) {
    asm volatile("cp.async.bulk.tensor.2d.shared::cluster.global.mbarrier::complete_tx::bytes [%0], [%1, {%3, %4}], [%2];"
                 ::"r"(dst), "l"(m), "r"(bar), "r"(c0), "r"(c1) : "memory");
}
__device__ __forceinline__ void tma3d(uint32_t dst, const CUtensorMap* m, int c0, int c1, int c2, uint32_t bar) {
    asm volatile("cp.async.bulk.tensor.3d.shared::cluster.global.mbarrier::complete_tx::bytes [%0], [%1, {%3, %4, %5}], [%2];"
                 ::"r"(dst), "l"(m), "r"(bar), "r"(c0), "r"(c1), "r"(c2) : "memory");
}
__device__ __forceinline__ void tma4d(uint32_t dst, const CUtensorMap* m, int c2, int c3, uint32_t bar) {
    asm volatile("cp.async.bulk.tensor.4d.shared::cluster.global.mbarrier::complete_tx::bytes [%0], [%1, {%5, %5, %3, %4}], [%2];"
                 ::"r"(dst), "l"(m), "r"(bar), "r"(c2), "r"(c3), "r"(0) : "memory");
}
__device__ __forceinline__ void bulk_g2s(uint32_t dst, const void* src, uint32_t bytes, uint32_t bar) {
    asm volatile("cp.async.bulk.shared::cluster.global.mbarrier::complete_tx::bytes [%0], [%1], %2, [%3];"
                 ::"r"(dst), "l"(src), "r"(bytes), "r"(bar) : "memory");
}
__device__ __forceinline__ void tma4d_prefetch(const CUtensorMap* m, int c2, int c3) {
    asm volatile("cp.async.bulk.prefetch.tensor.4d.L2.global [%0, {%3, %3, %1, %2}];" ::"l"(m), "r"(c2), "r"(c3), "r"(0) : "memory");
}
__device__ __forceinline__ void tma2d_prefetch(const CUtensorMap* m, int c0, int c1) {
    asm volatile("cp.async.bulk.prefetch.tensor.2d.L2.global [%0, {%1, %2}];" ::"l"(m), "r"(c0), "r"(c1) : "memory");
}
__device__ __forceinline__ void fence_async_smem() { asm volatile("fence.proxy.async.shared::cta;" ::: "memory"); }
__device__ __forceinline__ void fence_gpu() { asm volatile("fence.acq_rel.gpu;" ::: "memory"); }
__device__ __forceinline__ float rcp(float x) { float r; asm("rcp.approx.ftz.f32 %0, %1;" : "=f"(r) : "f"(x)); return r; }
__device__ __forceinline__ void bar_sync(int id, int n) { asm volatile("bar.sync %0, %1;" ::"r"(id), "r"(n) : "memory"); }

__device__ __forceinline__ bool bar_or(int id, int n, uint32_t x) {
    uint32_t r;
    asm volatile("{\n.reg .pred p, q;\n.reg .b32 t;\nand.b32 t, %3, 1;\nsetp.ne.u32 p, t, 0;\nbar.red.or.pred q, %1, %2, p;\nselp.u32 %0, 1, 0, q;\n}"
                 : "=r"(r) : "r"(id), "r"(n), "r"(x) : "memory");
    return __any_sync(~0u, r);
}
__device__ __forceinline__ uint32_t or3(uint32_t a, uint32_t b, uint32_t c) {
    uint32_t r; asm("lop3.b32 %0, %1, %2, %3, 0xFE;" : "=r"(r) : "r"(a), "r"(b), "r"(c)); return r;
}
__device__ __forceinline__ uint32_t pack_bf16(float lo, float hi) {
    uint32_t r; asm("cvt.rn.bf16x2.f32 %0, %1, %2;" : "=r"(r) : "f"(hi), "f"(lo)); return r;
}
__device__ __forceinline__ uint32_t add_bf16x2(uint32_t a, uint32_t b) {
    uint32_t r; asm volatile("add.rn.bf16x2 %0, %1, %2;" : "=r"(r) : "r"(a), "r"(b)); return r;
}
__device__ __forceinline__ uint32_t movm(uint32_t a) {
    uint32_t r; asm volatile("movmatrix.sync.aligned.m8n8.trans.b16 %0, %1;" : "=r"(r) : "r"(a)); return r;
}
__device__ __forceinline__ uint32_t orx(uint32_t acc, uint32_t a, uint32_t t) {
    uint32_t r; asm("lop3.b32 %0, %1, %2, %3, 0xF6;" : "=r"(r) : "r"(acc), "r"(a), "r"(t)); return r;
}
__device__ __forceinline__ uint32_t orx2(uint32_t a, uint32_t b, uint32_t t) {
    uint32_t r; asm("lop3.b32 %0, %1, %2, %3, 0x7E;" : "=r"(r) : "r"(a), "r"(b), "r"(t)); return r;
}
__device__ __forceinline__ float ex2(float x) { float r; asm("ex2.approx.ftz.f32 %0, %1;" : "=f"(r) : "f"(x)); return r; }
__device__ __forceinline__ void ldsm4t(uint32_t (&r)[4], uint32_t a) {
    asm volatile("ldmatrix.sync.aligned.m8n8.x4.trans.shared.b16 {%0,%1,%2,%3}, [%4];"
                 : "=r"(r[0]), "=r"(r[1]), "=r"(r[2]), "=r"(r[3]) : "r"(a) : "memory");
}
__device__ __forceinline__ void ldsm4(uint32_t (&r)[4], uint32_t a) {
    asm volatile("ldmatrix.sync.aligned.m8n8.x4.shared.b16 {%0,%1,%2,%3}, [%4];"
                 : "=r"(r[0]), "=r"(r[1]), "=r"(r[2]), "=r"(r[3]) : "r"(a) : "memory");
}
__device__ __forceinline__ void stsm4t(uint32_t a, uint32_t r0, uint32_t r1, uint32_t r2, uint32_t r3) {
    asm volatile("stmatrix.sync.aligned.m8n8.x4.trans.shared.b16 [%0], {%1,%2,%3,%4};"
                 ::"r"(a), "r"(r0), "r"(r1), "r"(r2), "r"(r3) : "memory");
}
__device__ __forceinline__ void stsm4(uint32_t a, uint32_t r0, uint32_t r1, uint32_t r2, uint32_t r3) {
    asm volatile("stmatrix.sync.aligned.m8n8.x4.shared.b16 [%0], {%1,%2,%3,%4};"
                 ::"r"(a), "r"(r0), "r"(r1), "r"(r2), "r"(r3) : "memory");
}
__device__ __forceinline__ void mma16816(float* c, uint32_t a0, uint32_t a1, uint32_t a2, uint32_t a3, uint32_t b0, uint32_t b1) {
    asm volatile("mma.sync.aligned.m16n8k16.row.col.f32.bf16.bf16.f32 {%0,%1,%2,%3}, {%4,%5,%6,%7}, {%8,%9}, {%0,%1,%2,%3};"
                 : "+f"(c[0]), "+f"(c[1]), "+f"(c[2]), "+f"(c[3]) : "r"(a0), "r"(a1), "r"(a2), "r"(a3), "r"(b0), "r"(b1));
}
__device__ __forceinline__ void mma1688(float* c, uint32_t a0, uint32_t a1, uint32_t b0) {
    asm volatile("mma.sync.aligned.m16n8k8.row.col.f32.bf16.bf16.f32 {%0,%1,%2,%3}, {%4,%5}, {%6}, {%0,%1,%2,%3};"
                 : "+f"(c[0]), "+f"(c[1]), "+f"(c[2]), "+f"(c[3]) : "r"(a0), "r"(a1), "r"(b0));
}
__device__ __forceinline__ void sts128(uint32_t a, float x, float y, float z, float w) {
    asm volatile("st.shared.v4.f32 [%0], {%1,%2,%3,%4};" ::"r"(a), "f"(x), "f"(y), "f"(z), "f"(w) : "memory");
}
__device__ __forceinline__ void sts64(uint32_t a, float x, float y) {
    asm volatile("st.shared.v2.f32 [%0], {%1,%2};" ::"r"(a), "f"(x), "f"(y) : "memory");
}
__device__ __forceinline__ void sts32(uint32_t a, uint32_t x) { asm volatile("st.shared.b32 [%0], %1;" ::"r"(a), "r"(x) : "memory"); }
__device__ __forceinline__ void sts128u(uint32_t a, uint4 v) {
    asm volatile("st.shared.v4.b32 [%0], {%1,%2,%3,%4};" ::"r"(a), "r"(v.x), "r"(v.y), "r"(v.z), "r"(v.w) : "memory");
}
__device__ __forceinline__ float4 lds128(uint32_t a) {
    float4 v; asm volatile("ld.shared.v4.f32 {%0,%1,%2,%3}, [%4];" : "=f"(v.x), "=f"(v.y), "=f"(v.z), "=f"(v.w) : "r"(a) : "memory"); return v;
}
__device__ __forceinline__ uint4 lds128u(uint32_t a) {
    uint4 v; asm volatile("ld.shared.v4.b32 {%0,%1,%2,%3}, [%4];" : "=r"(v.x), "=r"(v.y), "=r"(v.z), "=r"(v.w) : "r"(a) : "memory"); return v;
}
__device__ __forceinline__ uint4 lds128v(uint32_t a) {
    uint4 v; asm volatile("ld.volatile.shared.v4.b32 {%0,%1,%2,%3}, [%4];" : "=r"(v.x), "=r"(v.y), "=r"(v.z), "=r"(v.w) : "r"(a) : "memory"); return v;
}
__device__ __forceinline__ void sts64u(uint32_t a, uint2 v) { asm volatile("st.shared.v2.b32 [%0], {%1,%2};" ::"r"(a), "r"(v.x), "r"(v.y) : "memory"); }
__device__ __forceinline__ uint2 lds64u(uint32_t a) {
    uint2 v; asm volatile("ld.shared.v2.b32 {%0,%1}, [%2];" : "=r"(v.x), "=r"(v.y) : "r"(a) : "memory"); return v;
}
__device__ __forceinline__ float2 lds64(uint32_t a) {
    float2 v; asm volatile("ld.shared.v2.f32 {%0,%1}, [%2];" : "=f"(v.x), "=f"(v.y) : "r"(a) : "memory"); return v;
}
__device__ __forceinline__ uint2 ldg_rlx64(const void* p) {
    uint2 v; asm volatile("ld.relaxed.gpu.global.v2.b32 {%0,%1}, [%2];" : "=r"(v.x), "=r"(v.y) : "l"(p) : "memory"); return v;
}
__device__ __forceinline__ uint4 ldg_rlx128(const void* p) {
    uint4 v; asm volatile("ld.relaxed.gpu.global.v4.b32 {%0,%1,%2,%3}, [%4];" : "=r"(v.x), "=r"(v.y), "=r"(v.z), "=r"(v.w) : "l"(p) : "memory"); return v;
}
__device__ __forceinline__ void stg_rlx64(void* p, uint32_t x, uint32_t y) {
    asm volatile("st.relaxed.gpu.global.v2.b32 [%0], {%1,%2};" ::"l"(p), "r"(x), "r"(y) : "memory");
}
__device__ __forceinline__ void stg_rlx128(void* p, uint32_t x, uint32_t y, uint32_t z, uint32_t w) {
    asm volatile("st.relaxed.gpu.global.v4.b32 [%0], {%1,%2,%3,%4};" ::"l"(p), "r"(x), "r"(y), "r"(z), "r"(w) : "memory");
}
__device__ __forceinline__ uint32_t ldg_rlx32(const void* p) {
    uint32_t v; asm volatile("ld.relaxed.gpu.global.b32 %0, [%1];" : "=r"(v) : "l"(p) : "memory"); return v;
}
__device__ __forceinline__ void stg128(void* p, uint32_t x, uint32_t y, uint32_t z, uint32_t w) {
    asm volatile("st.global.v4.b32 [%0], {%1,%2,%3,%4};" ::"l"(p), "r"(x), "r"(y), "r"(z), "r"(w) : "memory");
}
__device__ __forceinline__ uint32_t ld_acquire(const unsigned* p) {
    uint32_t v; asm volatile("ld.acquire.gpu.global.u32 %0, [%1];" : "=r"(v) : "l"(p) : "memory"); return v;
}
__device__ __forceinline__ void red_add_u32(unsigned* p, uint32_t v) {
    asm volatile("red.relaxed.gpu.global.add.u32 [%0], %1;" ::"l"(p), "r"(v) : "memory");
}
__device__ __forceinline__ void wait_counter(const unsigned* p, uint32_t target) {
    uint32_t n = 0;
    while (ld_acquire(p) < target) { if (++n > SPIN_LIMIT) __trap(); }
}

__device__ __forceinline__ void wg_fence() { asm volatile("wgmma.fence.sync.aligned;" ::: "memory"); }
__device__ __forceinline__ void wg_commit() { asm volatile("wgmma.commit_group.sync.aligned;" ::: "memory"); }
template <int N> __device__ __forceinline__ void wg_wait() { asm volatile("wgmma.wait_group.sync.aligned %0;" ::"n"(N) : "memory"); }
__host__ __device__ constexpr uint64_t mkdesc(uint32_t addr, uint32_t lbo, uint32_t sbo, uint32_t swz) {
    return (uint64_t)((addr & 0x3FFFF) >> 4) | ((uint64_t)(lbo >> 4) << 16) | ((uint64_t)(sbo >> 4) << 32) | ((uint64_t)swz << 62);
}
#define F4(d, o) "+f"(d[o]), "+f"(d[o + 1]), "+f"(d[o + 2]), "+f"(d[o + 3])
template <int SC> __device__ __forceinline__ void wg_rs32(float (&d)[16], const uint32_t (&a)[4], uint64_t db) {
    asm volatile("wgmma.mma_async.sync.aligned.m64n32k16.f32.bf16.bf16 "
                 "{%0,%1,%2,%3,%4,%5,%6,%7,%8,%9,%10,%11,%12,%13,%14,%15}, {%16,%17,%18,%19}, %20, %21, 1, 1, 0;"
                 : F4(d, 0), F4(d, 4), F4(d, 8), F4(d, 12)
                 : "r"(a[0]), "r"(a[1]), "r"(a[2]), "r"(a[3]), "l"(db), "n"(SC));
}
template <int SC> __device__ __forceinline__ void wg_rs40(float (&d)[20], const uint32_t (&a)[4], uint64_t db) {
    asm volatile("wgmma.mma_async.sync.aligned.m64n40k16.f32.bf16.bf16 "
                 "{%0,%1,%2,%3,%4,%5,%6,%7,%8,%9,%10,%11,%12,%13,%14,%15,%16,%17,%18,%19}, {%20,%21,%22,%23}, %24, %25, 1, 1, 0;"
                 : F4(d, 0), F4(d, 4), F4(d, 8), F4(d, 12), F4(d, 16)
                 : "r"(a[0]), "r"(a[1]), "r"(a[2]), "r"(a[3]), "l"(db), "n"(SC));
}
template <int SC> __device__ __forceinline__ void wg_ss40(float (&d)[20], uint64_t da, uint64_t db) {
    asm volatile("wgmma.mma_async.sync.aligned.m64n40k16.f32.bf16.bf16 "
                 "{%0,%1,%2,%3,%4,%5,%6,%7,%8,%9,%10,%11,%12,%13,%14,%15,%16,%17,%18,%19}, %20, %21, %22, 1, 1, 1, 0;"
                 : F4(d, 0), F4(d, 4), F4(d, 8), F4(d, 12), F4(d, 16)
                 : "l"(da), "l"(db), "n"(SC));
}
template <int SC> __device__ __forceinline__ void wg_ss8(float (&d)[4], uint64_t da, uint64_t db) {
    asm volatile("wgmma.mma_async.sync.aligned.m64n8k16.f32.bf16.bf16 {%0,%1,%2,%3}, %4, %5, %6, 1, 1, 1, 1;"
                 : F4(d, 0) : "l"(da), "l"(db), "n"(SC));
}

constexpr int DBG_N = 11;
#define LT(st, k, v) do {} while (0)
#define TSI(st) do {} while (0)
#define TS(k) do {} while (0)
#define TSV(k, v) do {} while (0)
#define TSDUMP() do {} while (0)
#define GT(k) do {} while (0)

__device__ __align__(256) uint4 g_fy[2048 * 128];

constexpr uint32_t FG_SIZE = 2 * 32768 + 36864;
constexpr uint32_t FT_F16 = 2 * FG_SIZE, FT_B1F = FT_F16 + 2048, FT_B1I = FT_B1F + 2048, FT_C = FT_B1I + 2048, FT_A8 = FT_C + 2048,
                   FT_TWC = FT_A8 + 512, FT_TWB = FT_TWC + 8192, FT_BAR = FT_TWB + 8192, FFT_SMEM = FT_BAR + 256;
struct FftMaps { CUtensorMap x, y, o, y2, wr, wi; const unsigned char* w[3]; };

__device__ __forceinline__ float2 wroot(int e) {
    float s, c; sincospif((float)(e & 2047) * (-1.f / 1024.f), &s, &c); return make_float2(c, s);
}
__device__ __forceinline__ uint4 afrag(float2 a, float2 b) {
    return make_uint4(pack_bf16(a.x, -a.y), pack_bf16(a.y, a.x), pack_bf16(b.x, -b.y), pack_bf16(b.y, b.x));
}
__device__ __forceinline__ uint4 conjfrag(uint4 v) { return make_uint4(v.x ^ 0x80000000u, v.y ^ 0x8000u, v.z ^ 0x80000000u, v.w ^ 0x8000u); }
__device__ __forceinline__ uint4 negfrag(uint4 v) { return make_uint4(v.x ^ 0x80008000u, v.y ^ 0x80008000u, v.z ^ 0x80008000u, v.w ^ 0x80008000u); }
__device__ __forceinline__ uint32_t comp(const uint4& v, int i) { return i == 0 ? v.x : i == 1 ? v.y : i == 2 ? v.z : v.w; }
__device__ __forceinline__ void setcomp(uint4& v, int i, uint32_t x) { if (i == 0) v.x = x; else if (i == 1) v.y = x; else if (i == 2) v.z = x; else v.w = x; }
__device__ __forceinline__ float2 cmul(float2 a, float2 b) { return make_float2(a.x * b.x - a.y * b.y, a.x * b.y + a.y * b.x); }
__device__ __forceinline__ float2 cmulc(float2 a, float2 b) { return make_float2(a.x * b.x + a.y * b.y, a.y * b.x - a.x * b.y); }

__device__ __forceinline__ uint32_t pack_h2(float2 a) { uint32_t r; asm("cvt.rn.f16x2.f32 %0, %1, %2;" : "=r"(r) : "f"(a.y), "f"(a.x)); return r; }
__device__ __forceinline__ float2 unpack_h2(uint32_t v) {
    float2 r; asm("{\n.reg .b16 l, h;\nmov.b32 {l, h}, %2;\ncvt.f32.f16 %0, l;\ncvt.f32.f16 %1, h;\n}" : "=f"(r.x), "=f"(r.y) : "r"(v)); return r;
}
__device__ __forceinline__ void fft_tables(uint32_t tb, int tid, int nthr) {
    for (int i = tid; i < 128; i += nthr) {
        const int lane = i & 31, q = i >> 5, g = lane >> 2, t = lane & 3, o = 8 * (q >> 1) + g, in = 8 * (q & 1) + 2 * t;
        sts128u(tb + FT_F16 + i * 16, afrag(wroot(128 * o * in), wroot(128 * o * (in + 1))));
        sts128u(tb + FT_B1F + i * 16, afrag(wroot(64 * (1 + 2 * o) * in), wroot(64 * (1 + 2 * o) * (in + 1))));
        sts128u(tb + FT_B1I + i * 16, afrag(wroot(-64 * o * (1 + 2 * in)), wroot(-64 * o * (3 + 2 * in))));
        uint4 v;
        for (int r = 0; r < 4; r++) {
            const float2 a = wroot(128 * (4 * r + t) * (4 * q + (g >> 1)));
            setcomp(v, r, (g & 1) ? pack_bf16(a.y, a.x) : pack_bf16(a.x, -a.y));
        }
        sts128u(tb + FT_C + i * 16, v);
        if (q == 0) sts128u(tb + FT_A8 + lane * 16, afrag(wroot(256 * g * 2 * t), wroot(256 * g * (2 * t + 1))));
    }
    for (int i = tid; i < 512; i += nthr) {
        const int lane = i & 31, r = (i >> 5) & 3, phi = 8 * (i >> 7) + (lane >> 2), c = 4 * r + (lane & 3);
        const float2 a = wroot(4 * c * phi), b = wroot(2 * (phi + 32 * c));
        constexpr float SC = 1.f / (2.f * 2048.f * 512.f);
        sts128(tb + FT_TWC + i * 16, a.x * SC, a.y * SC, b.x, b.y);
    }
    for (int i = tid; i < 512; i += nthr) {
        const int lane = i & 31, r = (i >> 5) & 3, fa = (i >> 7) & 1, hf = i >> 8, c = 8 * (lane & 1) + r;
        const int p0 = fa + 2 * (lane >> 2), p1 = p0 + 16, s0 = (hf && p0) ? 32 - p0 : p0, s1 = hf ? 32 - p1 : p1;
        sts128u(tb + FT_TWB + i * 16, make_uint4(pack_h2(wroot(4 * c * s0)), pack_h2(wroot(4 * (c + 4) * s0)),
                                                 pack_h2(wroot(4 * c * s1)), pack_h2(wroot(4 * (c + 4) * s1))));
    }
}

template <bool TW>
__device__ __forceinline__ void dft16(uint4 (&out)[4], const uint4 (&in)[4], const uint4 (&m)[4], const uint4 (&tw)[4]) {
#pragma unroll
    for (int i = 0; i < 4; i++)
#pragma unroll
        for (int mt = 0; mt < 2; mt++) {
            float c[4] = {0.f, 0.f, 0.f, 0.f};
            mma16816(c, m[2 * mt].x, m[2 * mt].y, m[2 * mt].z, m[2 * mt].w, comp(in[0], i), comp(in[1], i));
            mma16816(c, m[2 * mt + 1].x, m[2 * mt + 1].y, m[2 * mt + 1].z, m[2 * mt + 1].w, comp(in[2], i), comp(in[3], i));
            if (TW) {
                const float2 a = cmul(make_float2(c[0], c[2]), unpack_h2(comp(tw[i], 2 * mt))), b = cmul(make_float2(c[1], c[3]), unpack_h2(comp(tw[i], 2 * mt + 1)));
                setcomp(out[2 * mt], i, pack_bf16(a.x, a.y));
                setcomp(out[2 * mt + 1], i, pack_bf16(b.x, b.y));
            } else {
                setcomp(out[2 * mt], i, pack_bf16(c[0], c[2]));
                setcomp(out[2 * mt + 1], i, pack_bf16(c[1], c[3]));
            }
        }
}
__device__ __forceinline__ void tma_ld4(uint32_t dst, const CUtensorMap* m, int c0, int c1, uint32_t bar) {
    asm volatile("cp.async.bulk.tensor.4d.shared::cluster.global.mbarrier::complete_tx::bytes [%0], [%1, {%3, %4, %5, %5}], [%2];"
                 ::"r"(dst), "l"(m), "r"(bar), "r"(c0), "r"(c1), "r"(0) : "memory");
}
__device__ __forceinline__ void tma_st4(uint32_t src, const CUtensorMap* m, int c0, int c1) {
    asm volatile("cp.async.bulk.tensor.4d.global.shared::cta.bulk_group [%1, {%2, %3, %4, %4}], [%0];" ::"r"(src), "l"(m), "r"(c0), "r"(c1), "r"(0) : "memory");
}
__device__ __forceinline__ void tma_ld3(uint32_t dst, const CUtensorMap* m, int c0, int c1, uint32_t bar) {
    asm volatile("cp.async.bulk.tensor.3d.shared::cluster.global.mbarrier::complete_tx::bytes [%0], [%1, {%3, %4, %5}], [%2];"
                 ::"r"(dst), "l"(m), "r"(bar), "r"(c0), "r"(c1), "r"(0) : "memory");
}
__device__ __forceinline__ void tma_st3(uint32_t src, const CUtensorMap* m, int c0, int c1) {
    asm volatile("cp.async.bulk.tensor.3d.global.shared::cta.bulk_group [%1, {%2, %3, %4}], [%0];" ::"r"(src), "l"(m), "r"(c0), "r"(c1), "r"(0) : "memory");
}
__device__ __forceinline__ void bulk_commit() { asm volatile("cp.async.bulk.commit_group;" ::: "memory"); }
__device__ __forceinline__ void bulk_wait_read() { asm volatile("cp.async.bulk.wait_group.read 0;" ::: "memory"); }
__device__ __forceinline__ void bulk_wait_all() { asm volatile("cp.async.bulk.wait_group 0;" ::: "memory"); }

__device__ __forceinline__ float2 wroot_fast(int e) {
    float s, c; __sincosf((float)(((e + 1024) & 2047) - 1024) * (-3.14159265358979f / 1024.f), &s, &c); return make_float2(c, s);
}
template <bool INV, int NT>
__device__ __forceinline__ void fft_col(int s2, int t0, const CUtensorMap* src, const CUtensorMap* dst, uint32_t gb, uint32_t mb,
                                        int w, int lane, int bar) {
    const int g = lane >> 2, t = lane & 3;
    const bool lead = w == 4 && lane == 0;
    if (NT > 1 && lead)
        for (int i = 0; i < 2; i++) { mbar_expect_tx(mb + 8 * i, 32768); tma_ld4(gb + i * 32768, src, (t0 + i) * 64, s2, mb + 8 * i); }
    uint4 f[4], m[2][4];
#pragma unroll
    for (int i = 0; i < 4; i++) {
        const int o = 8 * (i >> 1) + g, in = 8 * (i & 1) + 2 * t, sg = INV ? -128 : 128;
        f[i] = afrag(wroot_fast(sg * o * in), wroot_fast(sg * o * (in + 1)));
#pragma unroll
        for (int q = 0; q < 2; q++) {
            const int z = 2 * w + q;
            m[q][i] = INV ? afrag(wroot_fast(-(8 * o + s2) * (z + 16 * in)), wroot_fast(-(8 * o + s2) * (z + 16 * in + 16)))
                          : afrag(wroot_fast((z + 16 * o) * (8 * in + s2)), wroot_fast((z + 16 * o) * (8 * in + 8 + s2)));
        }
    }
    const uint32_t r1 = (32 * w + 2 * t) * 128 + ((g ^ (2 * t)) << 4);
    const uint32_t w1 = (32 * w + g) * 128 + (((2 * t) ^ (((w & 3) << 1) | (g & 1))) << 4);
    const uint32_t r2 = (32 * t + 2 * w) * 128 + ((g ^ (2 * t)) << 4);
    const uint32_t w2 = (32 * w + g) * 128 + (((2 * t) ^ g) << 4);
    int bi = 0, ph = 0;
#pragma unroll 1
    for (int it = 0; it < NT; it++) {
        const uint32_t buf = gb + bi * 32768;
        mbar_wait(mb + 8 * bi, ph);
        uint4 in[2][4], out[4];
#pragma unroll
        for (int q = 0; q < 2; q++)
#pragma unroll
            for (int i = 0; i < 4; i++) in[q][i] = lds128u(buf + (r1 ^ ((i & 1) * 0x90)) + (i >> 1) * 1024 + q * 2048);
        __syncwarp();
#pragma unroll
        for (int q = 0; q < 2; q++) {
            if (INV) dft16<false>(out, in[q], m[q], f); else dft16<false>(out, in[q], f, f);
#pragma unroll
            for (int i = 0; i < 4; i++) sts128u(buf + (w1 ^ ((i & 1) << 4)) + (i >> 1) * 1024 + q * 2048, out[i]);
        }
        bar_sync(bar, 256);
#pragma unroll
        for (int q = 0; q < 2; q++)
#pragma unroll
            for (int i = 0; i < 4; i++) in[q][i] = lds128u(buf + (r2 ^ (q * 0x90)) + (i & 1) * 2048 + (i >> 1) * 16384);
        const int bn = bi == 0 ? 2 : bi - 1;
        if (lead && it < NT - 2) { bulk_wait_read(); mbar_expect_tx(mb + 8 * bn, 32768); tma_ld4(gb + bn * 32768, src, (t0 + it + 2) * 64, s2, mb + 8 * bn); }
        bar_sync(bar, 256);
#pragma unroll
        for (int q = 0; q < 2; q++) {
            if (INV) dft16<false>(out, in[q], f, f); else dft16<false>(out, in[q], m[q], f);
#pragma unroll
            for (int i = 0; i < 4; i++) sts128u(buf + (w2 ^ ((i & 1) << 4)) + (i >> 1) * 1024 + q * 2048, out[i]);
        }
        fence_async_smem();
        bar_sync(bar, 256);
        if (NT > 1 && lead) { tma_st4(buf, dst, (t0 + it) * 64, s2); bulk_commit(); }
        if (++bi == 3) { bi = 0; ph ^= 1; }
    }
    if (NT > 1 && lead) bulk_wait_read();
}

__device__ __forceinline__ float ldw(uint32_t a) {
    uint16_t v; asm volatile("ld.shared.u16 %0, [%1];" : "=h"(v) : "r"(a) : "memory");
    return __uint_as_float((uint32_t)v << 16);
}
__device__ __forceinline__ void fft_mid(int grp, const FftMaps& fm, uint32_t tb,
                                        uint32_t gb, uint32_t mb, uint32_t& cnt, int w, int lane, int bar) {
    const int g = lane >> 2, t = lane & 3;
    const bool lead = w == 4 && lane == 0;
    const uint32_t wb = gb + 65536;
#define MID_LOAD(k, c)                                                                                                  \
    { mbar_expect_tx(mb + 8 * ((c) & 1), 32768);                                                                        \
      tma_ld3(gb + ((c) & 1) * 32768, &fm.y2, 0, (k) * 8, mb + 8 * ((c) & 1));                                          \
      tma_ld3(gb + ((c) & 1) * 32768 + 16384, &fm.y2, 0, ((256 - (k)) & 255) * 8, mb + 8 * ((c) & 1)); }
#define MID_LOADW(k)                                                                                                    \
    { mbar_expect_tx(mb + 16, 36864);                                                                                   \
      tma_ld3(wb, &fm.wr, (k) * 513 & ~7, 0, mb + 16); tma_ld3(wb + 9216, &fm.wi, (k) * 513 & ~7, 0, mb + 16);          \
      tma_ld3(wb + 18432, &fm.wr, ((256 - (k)) & 255) * 513 & ~7, 0, mb + 16); tma_ld3(wb + 27648, &fm.wi, ((256 - (k)) & 255) * 513 & ~7, 0, mb + 16); }
    if (lead) { MID_LOAD(grp, cnt); MID_LOADW(grp); }
    const int hB = w >> 2, faB = (w >> 1) & 1, xB = faB;
    const int phi = 8 * (w & 3) + g;
    const uint32_t rA = (8 * w + 2 * t) * 128 + ((g ^ (2 * t)) << 4);
    const uint32_t wA = (8 * w + g) * 128 + (((2 * t) ^ ((g & 1) | ((w & 3) << 1))) << 4);
    const uint32_t oB = (w >> 1) * 8192 + (w & 1) * 512;
    const uint32_t rB = oB + (8 * t + (g >> 2)) * 128 + (((g & 3) ^ ((g >> 2) | (t << 1)) ^ xB) << 4);
    const uint32_t wB = oB + (8 * (g >> 1) + (t >> 1)) * 128 + (((((g & 1) << 2) | (2 * (t & 1))) ^ ((t >> 1) | ((g >> 1) << 1)) ^ xB) << 4);
    const uint32_t wBi = oB + (8 * (g >> 1) + (t >> 1)) * 128 + (((((g & 1) << 2) | (2 * (t & 1))) ^ ((t >> 1) | ((w & 1) << 2))) << 4);
    const int hC = (lane >> 3) & 1, pr = 8 * (w & 3) + (lane & 7), pc = hC ? (32 - pr) & 31 : pr;
    const uint32_t aC = hC * 16384 + (pc & 1) * 8192 + (pc >> 2) * 1024 + (((((pc & 2) << 1) | (lane >> 4)) ^ (((pc >> 2) & 3) << 1) ^ (pc & 1)) << 4);
    const uint32_t g0 = wb + (t >> 1) * 144 + (32 * (t & 1) + phi) * 2, g1 = wb + 18432 + (7 - (t >> 1)) * 144 + (64 - 32 * (t & 1) - phi) * 2;
    const uint32_t wAo = (8 * w + g) * 128 + (((2 * t) ^ g) << 4);
    uint32_t wph = 0;
#pragma unroll 1
    for (int k1 = grp; k1 < 129; k1 += 8, cnt++, wph ^= 1) {
        const uint32_t buf = gb + (cnt & 1) * 32768;
        uint4 in[2][4], m[4], out[4];
        m[0] = m[1] = m[2] = lds128u(tb + FT_A8 + lane * 16);
        m[3] = negfrag(m[0]);
        mbar_wait(mb + 8 * (cnt & 1), (cnt >> 1) & 1);
#pragma unroll
        for (int q = 0; q < 2; q++)
#pragma unroll
            for (int i = 0; i < 4; i++) in[q][i] = lds128u(buf + (rA ^ ((i & 1) * 0x90)) + (i >> 1) * 8192 + q * 16384);
        __syncwarp();
#pragma unroll
        for (int q = 0; q < 2; q++) {
            dft16<false>(out, in[q], m, m);
#pragma unroll
            for (int i = 0; i < 4; i++) sts128u(buf + (wA ^ (((i ^ (i >> 1)) & 1) << 4)) + (i >> 1) * 8192 + q * 16384, out[i]);
        }
        {
            uint4 tw[4];
#pragma unroll
            for (int i = 0; i < 4; i++) {
                m[i] = lds128u(tb + (faB ? FT_B1F : FT_F16) + i * 512 + lane * 16);
                if (hB) { m[i].y ^= 0x80008000u; m[i].w ^= 0x80008000u; }
                tw[i] = lds128u(tb + FT_TWB + (w >> 1) * 2048 + i * 512 + lane * 16);
            }
            bar_sync(bar, 256);
#pragma unroll
            for (int q = 0; q < 2; q++)
#pragma unroll
                for (int i = 0; i < 4; i++) in[q][i] = lds128u(buf + (rB ^ ((i & 1) << 6)) + (i >> 1) * 4096 + q * 256);
            __syncwarp();
#pragma unroll
            for (int q = 0; q < 2; q++) {
                dft16<true>(out, in[q], m, tw);
#pragma unroll
                for (int i = 0; i < 4; i++) sts128u(buf + (wB ^ ((i & 1) << 4)) + (i >> 1) * 4096 + q * 256, out[i]);
            }
        }
        {
            const uint32_t cjm = (g & 1) ? 0x8000u : 0x80000000u;
            float4 tw[4];
#pragma unroll
            for (int i = 0; i < 4; i++) { m[i] = lds128u(tb + FT_C + i * 512 + lane * 16); tw[i] = lds128(tb + FT_TWC + ((w & 3) * 4 + i) * 512 + lane * 16); }
            if (lead && k1 + 8 < 129) { bulk_wait_read(); MID_LOAD(k1 + 8, cnt + 1); }
            __syncwarp();
            mbar_wait(mb + 16, wph);
            const uint32_t o0 = (k1 & 7) * 2, o1 = (-k1 & 7) * 2;
            if (w == 1 && lane < 16) {
                const int k2 = lane & 7, k2p = k1 ? 7 - k2 : (8 - k2) & 7;
                const uint32_t p0 = wb + (lane >> 3) * 9216 + k2 * 1152 + o0, p1 = wb + 18432 + (lane >> 3) * 9216 + k2p * 1152 + o1;
                const float sg = lane < 8 ? 0.5f : -0.5f;
                const uint32_t v = pack_bf16(0.5f * ldw(p0) + sg * ldw(p1), 0.5f * ldw(p1 + 1136) + sg * ldw(p0 + 1136));
                asm volatile("st.shared.u16 [%0], %1;" ::"r"(p0), "h"((uint16_t)v) : "memory");
                asm volatile("st.shared.u16 [%0], %1;" ::"r"(p1 + 1136), "h"((uint16_t)(v >> 16)) : "memory");
                fence_async_smem();
            }
            bar_sync(bar, 256);
#define FFT_CU 1
            constexpr int CU = FFT_CU;
#pragma unroll CU
            for (int q = 0; q < 4; q++) {
                const int k2 = 4 * (w >> 2) + q, k2p = k1 ? 7 - k2 : (8 - k2) & 7, kr = hC ? k2p : k2;
                const uint32_t a0 = buf + (aC ^ ((kr & 1) << 4)) + kr * 128;
                const uint32_t r0 = g0 + k2 * 1152 + o0, r1 = g1 + k2p * 1152 + o1;
                uint32_t x[4], y[4];
                ldsm4(x, a0); ldsm4(y, a0 ^ 32);
                float c[4][4];
#pragma unroll
                for (int i = 0; i < 4; i++) { c[i][0] = c[i][1] = c[i][2] = c[i][3] = 0.f; mma16816(c[i], x[0], x[1], x[2], x[3], m[i].x, m[i].y); }
#pragma unroll
                for (int i = 0; i < 4; i++) mma16816(c[i], y[0], y[1], y[2], y[3], m[i].z, m[i].w);
#pragma unroll
                for (int i = 0; i < 4; i++) {
                    const float2 ga = make_float2(ldw(r0 + i * 288), ldw(r0 + 9216 + i * 288));
                    const float2 gc = make_float2(ldw(r1 - i * 288), ldw(r1 + 9216 - i * 288));
                    const float tc = tw[i].z, ts = tw[i].w;
                    const float* z = c[i];
                    const float2 S = make_float2(ga.x + gc.x, ga.y - gc.y), D = make_float2(ga.x - gc.x, ga.y + gc.y);
                    const float2 u = make_float2(ts * z[0] - tc * z[3], ts * z[1] + tc * z[2]), v = make_float2(ts * z[2] - tc * z[1], ts * z[3] + tc * z[0]);
                    uint32_t* o = (i < 2 ? x : y) + 2 * (i & 1);
                    o[0] = pack_bf16(fmaf(S.x, z[0], fmaf(-S.y, z[1], fmaf(D.x, u.x, -D.y * u.y))), fmaf(S.x, z[1], fmaf(S.y, z[0], fmaf(D.x, u.y, D.y * u.x))));
                    o[1] = pack_bf16(fmaf(S.x, z[2], fmaf(-S.y, z[3], fmaf(-D.x, v.x, D.y * v.y))), fmaf(S.x, z[3], fmaf(S.y, z[2], fmaf(-D.x, v.y, -D.y * v.x))));
                }
#pragma unroll
                for (int i = 0; i < 4; i++) { c[i][0] = c[i][1] = c[i][2] = c[i][3] = 0.f; mma16816(c[i], x[0], x[1], x[2], x[3], m[i].x ^ cjm, m[i].y ^ cjm); }
#pragma unroll
                for (int i = 0; i < 4; i++) mma16816(c[i], y[0], y[1], y[2], y[3], m[i].z ^ cjm, m[i].w ^ cjm);
#pragma unroll
                for (int i = 0; i < 4; i++) {
                    uint32_t* o = (i < 2 ? x : y) + 2 * (i & 1);
                    o[0] = pack_bf16(c[i][0] * tw[i].x + c[i][1] * tw[i].y, c[i][1] * tw[i].x - c[i][0] * tw[i].y);
                    o[1] = pack_bf16(c[i][2] * tw[i].x + c[i][3] * tw[i].y, c[i][2] * tw[i].y - c[i][3] * tw[i].x);
                }
                stsm4(a0, x[0], x[1], x[2], x[3]);
                stsm4(a0 ^ 32, y[0], y[1], y[2], y[3]);
            }
        }
#pragma unroll
        for (int i = 0; i < 4; i++) { m[i] = lds128u(tb + (faB ? FT_B1I : FT_F16) + i * 512 + lane * 16); if (!faB) m[i] = conjfrag(m[i]); }
        bar_sync(bar, 256);
        if (lead && k1 + 8 < 129) MID_LOADW(k1 + 8);
        __syncwarp();
#pragma unroll
        for (int q = 0; q < 2; q++)
#pragma unroll
            for (int i = 0; i < 4; i++) in[q][i] = lds128u(buf + (rB ^ ((i & 1) << 6)) + (i >> 1) * 4096 + q * 256);
        __syncwarp();
#pragma unroll
        for (int q = 0; q < 2; q++) {
            dft16<false>(out, in[q], m, m);
#pragma unroll
            for (int i = 0; i < 4; i++) sts128u(buf + (wBi ^ ((i & 1) << 4) ^ (q << 5)) + (i >> 1) * 4096 + q * 256, out[i]);
        }
        m[0] = m[1] = m[2] = conjfrag(lds128u(tb + FT_A8 + lane * 16));
        m[3] = negfrag(m[0]);
        bar_sync(bar, 256);
#pragma unroll
        for (int q = 0; q < 2; q++)
#pragma unroll
            for (int i = 0; i < 4; i++) in[q][i] = lds128u(buf + (rA ^ ((i & 1) * 0x90)) + (i >> 1) * 8192 + q * 16384);
        __syncwarp();
#pragma unroll
        for (int q = 0; q < 2; q++) {
            dft16<false>(out, in[q], m, m);
#pragma unroll
            for (int i = 0; i < 4; i++) sts128u(buf + (wAo ^ ((i & 1) << 4)) + (i >> 1) * 8192 + q * 16384, out[i]);
        }
        fence_async_smem();
        bar_sync(bar, 256);
        if (lead) {
            tma_st3(buf, &fm.y2, 0, k1 * 8);
            if (k1 & 127) tma_st3(buf + 16384, &fm.y2, 0, (256 - k1) * 8);
            bulk_commit();
        }
    }
    if (lead) bulk_wait_all();
}

__device__ __align__(128) unsigned g_start;
__device__ __align__(128) unsigned g_fbar;
__device__ __align__(128) unsigned g_end;
__device__ __forceinline__ unsigned gbar_arrive(unsigned* c, unsigned inc, unsigned total, int lane) {
    unsigned v = 0;
    if (lane == 0) { asm volatile("fence.proxy.async;" ::: "memory"); fence_gpu(); v = atomicAdd(c, inc); }
    return (__shfl_sync(~0u, v, 0) & ~(total - 1)) + total;
}
__device__ __forceinline__ void gbar_wait(unsigned* c, unsigned target, unsigned ns) {
    uint32_t n = 0;
    while (__any_sync(~0u, (int)(ld_acquire(c) - target) < 0)) { if (ns) __nanosleep(ns); if (++n > SPIN_LIMIT) __trap(); }
    asm volatile("fence.proxy.async;" ::: "memory");
}
__device__ __forceinline__ void fft_rest(int cta, const FftMaps& fm, uint32_t sb, uint32_t opt) {
    const int hi = __shfl_sync(~0u, threadIdx.x >> 8, 0), w = __shfl_sync(~0u, (threadIdx.x >> 5) & 7, 0), lane = threadIdx.x & 31;
    unsigned target = 0;
    if (w == 4) target = gbar_arrive(&g_start, 16, 256, lane);
    if (threadIdx.x < 32) mbar_init(sb + FT_BAR + 8 * threadIdx.x, 1);
    fft_tables(sb, threadIdx.x, 512);
    fence_async_smem();
    __syncthreads();
    const int grp = cta * 2 + hi, bar = 1 + hi;
    const uint32_t gb = sb + hi * FG_SIZE, mb = sb + FT_BAR + hi * 128;
    uint32_t cnt = 0;
    if (w == 4) gbar_wait(&g_start, target, 200);
    if (w == 4) {
        const unsigned char* p = fm.w[2] + (size_t)(lane * 8 + grp) * 16384;
        asm volatile("cp.async.bulk.prefetch.L2.global [%0], %1;" ::"l"(p), "r"(16384) : "memory");
    }
    if (w == 4) {
        const unsigned char* p = fm.w[hi] + (size_t)(cta * 32 + lane) * 16416;
        asm volatile("cp.async.bulk.prefetch.L2.global [%0], %1;" ::"l"(p), "r"(16416) : "memory");
    }
    GT(1);
    fft_mid(grp, fm, sb, gb, mb, cnt, w, lane, bar);
    if (w == 4) gbar_wait(&g_fbar, gbar_arrive(&g_fbar, 1, 8, lane), 200);
    GT(2);
    fft_col<true, 16>(grp, 0, &fm.y, &fm.o, gb, mb + 64, w, lane, bar);
}

__device__ __align__(256) uint4 g_kvq[4 * 32 * 3 * 8 * 2 * 32];
__device__ __align__(256) uint2 g_alpha[2 * 32 * 3 * 8 * 2 * 32];
__device__ __align__(256) uint4 g_red[5 * 32768 / 16];
__device__ __align__(256) uint4 g_stamp[32];
__device__ __align__(256) uint4 g_qst[128 * 2];
__device__ __align__(256) bf16 g_ox[2048 * 4096];
struct Tune { uint32_t d_alpha, d_r, opt, d_q, d_v, spread, extra; };
#define OP_SPLIT 1
#define X_SEQ 24
#define QKW_POS 0
#define XO_POS 0
#define V_SEQ 28
#define X_HALF 0
#define V_KEEP 0
#define STAMP_V 1
#define EXP 0
#define FIN_BAR B_SRDY
#define V_LATE 0
#define R_SPLIT 0
#define OPD_EARLY 1
constexpr int RA = 2;

constexpr uint32_t SM_BASE = 1024;
constexpr uint32_t O_WO = 0;
constexpr uint32_t O_WV = 65536;
constexpr uint32_t O_XB = 131072;
constexpr uint32_t O_MEM = O_XB + 16384;
constexpr uint32_t O_RECV = O_XB + 40960;
constexpr uint32_t O_KVQ = O_RECV + 12288;
constexpr uint32_t O_STG = O_KVQ + 18432;
constexpr uint32_t O_S = O_STG + 8192;
constexpr uint32_t O_P = O_S + 10240;
constexpr uint32_t O_O = O_P + 1536;
constexpr uint32_t O_DBG = O_O + 2048;
constexpr uint32_t O_F1 = 196608;
constexpr uint32_t O_VM = O_F1 + 32768;
constexpr uint32_t O_BAR = 232448 - 512;
constexpr uint32_t MAIN_SMEM = 232448;
static_assert(O_DBG + (DBG_TIMING ? (4 * DBG_N + 1) * 96 : 0) <= O_VM && FFT_SMEM <= MAIN_SMEM && O_VM + 2048 <= O_BAR, "smem");
constexpr int G_ST = 6;
enum { B_W = 0, B_WO = B_W + 12, B_F1, B_XP, B_XFULL, B_RFULL, B_AFULL, B_KVFULL, B_XF1, B_QST, B_RECV, B_GF = B_RECV + 6,
       B_QDONE = B_GF + G_ST, B_KDONE, B_XEMPTY, B_VA, B_X0, B_SRDY, B_OPDONE, B_QX, B_GE, B_XPE = B_GE + G_ST, B_QKW, B_MEM, B_COUNT };

constexpr float SM_SCALE_LOG2 = 0.08838834764831845f * 1.4426950408889634f;
constexpr float MASK_VAL = -1.0e9f / 0.08838834764831845f;

__device__ __forceinline__ uint32_t red_grp(int grp) { return (uint32_t)((grp >> 1) * 1024 + (grp & 1) * 256); }
__host__ __device__ constexpr uint32_t kb_off(int kb) { return (uint32_t)((kb >> 2) * 20480 + (kb & 3) * 1024); }
__host__ __device__ constexpr uint64_t xdesc(int ks) { return mkdesc(SM_BASE + O_XB + kb_off(ks >> 2) + (ks & 3) * 32, 16, 4096, 1); }

__device__ __forceinline__ void x_split(const float* d, uint32_t (&sn)[4], uint32_t (&kp)[4], int kh) {
#pragma unroll
    for (int i = 0; i < 4; i++) {
        const uint32_t lo = pack_bf16(d[2 * i], d[2 * i + 1]), hi = pack_bf16(d[8 + 2 * i], d[8 + 2 * i + 1]);
        sn[i] = kh ? lo : hi; kp[i] = kh ? hi : lo;
    }
}
__device__ __forceinline__ void x_send(int R, const uint32_t (&sn)[4], int sg, int tid, uint32_t sb, uint32_t mate) {
    const uint32_t par = sg & 1;
    const uint32_t bar = O_BAR + 8 * (B_RECV + R * 2) + 8 * par;
    if (tid == 0) mbar_expect_tx(sb + bar, 2048);
    asm volatile("st.async.shared::cluster.mbarrier::complete_tx::bytes.v4.b32 [%0], {%1,%2,%3,%4}, [%5];"
                 ::"r"(mate + O_RECV + (par * 3 + R) * 2048 + tid * 16), "r"(sn[0]), "r"(sn[1]), "r"(sn[2]), "r"(sn[3]), "r"(mate + bar) : "memory");
}
__device__ __forceinline__ void x_wait(int R, int sg, uint32_t sb) {
    mbar_wait_cluster(sb + O_BAR + 8 * (B_RECV + R * 2) + 8 * (sg & 1), (sg >> 1) & 1);
}
template <int R>
__device__ __forceinline__ void x_finish(const uint32_t (&kp)[4], int sg, int h, int mt, int kh, int tid, uint32_t sb) {
    const uint4 r = lds128u(sb + O_RECV + ((sg & 1) * 3 + R) * 2048 + tid * 16);
    uint32_t u0 = add_bf16x2(kp[0], r.x), u1 = add_bf16x2(kp[1], r.y), u2 = add_bf16x2(kp[2], r.z), u3 = add_bf16x2(kp[3], r.w);
    const uint32_t tag = ((sg >> 2) & 1) ^ 1;
    uint4* const hb = &g_kvq[((sg & 3) * 32 + h) * (3 * 512)];
    if (R < 2) {
        const uint32_t m = (tid & 7) ? ~0u : ~1u, t = tag & ~m;
        uint32_t* p = (uint32_t*)hb + (R == 0 ? (kh * 16 + mt) * 64 : 2048 + (mt * 2 + kh) * 128) + (tid & 31);
        asm volatile("{\n.reg .pred p;\nsetp.lt.s32 p, %5, 64;\n@p st.relaxed.gpu.global.b32 [%0], %1;\n@p st.relaxed.gpu.global.b32 [%0+128], %2;\n"
                     "@p st.relaxed.gpu.global.b32 [%0+%6], %3;\n@p st.relaxed.gpu.global.b32 [%0+%7], %4;\n}"
                     ::"l"(p), "r"((u0 & m) | t), "r"((u1 & m) | t), "r"((u2 & m) | t), "r"((u3 & m) | t), "r"(sg),
                       "n"(R == 0 ? 2048 : 256), "n"(R == 0 ? 2176 : 384) : "memory");
    } else {
        asm volatile("{\n.reg .pred p;\nsetp.lt.s32 p, %5, 64;\n@p st.relaxed.gpu.global.v4.b32 [%0], {%1,%2,%3,%4};\n}"
                     ::"l"(hb + R * 512 + (mt * 2 + kh) * 32 + (tid & 31)), "r"((u0 & ~1u) | tag), "r"(u1), "r"(u2), "r"(u3), "r"(sg) : "memory");
    }
}
__device__ __forceinline__ uint32_t tags4(const uint32_t (&r)[4], uint32_t tag) { return orx(orx(orx2(r[0], r[1], tag), r[2], tag), r[3], tag); }

__device__ __forceinline__ uint32_t convert_mem(const unsigned char* redp, int s, int kh, int jj, int w, int lane, uint32_t sb, uint32_t& sf) {
    const uint32_t off = red_grp(jj * 16 + w * 4 + (lane >> 3)), o16 = off + (lane & 7) * 16, o8 = off + 512 + ((lane >> 3) & 1) * 64 + (lane & 7) * 8;
    uint32_t ma = sb + O_MEM + jj * 20480 + (lane >> 4) * 1024 + (lane & 7) * 128 + (((2 * w + ((lane >> 3) & 1)) ^ (lane & 7)) << 4);
    uint32_t a16 = sb + O_STG + o16, a8 = sb + O_STG + o8;
    const uint32_t target = (s & 4) ? 0x42C00000u : 0x42000000u;
    uint32_t n = 0;
    bool redo;
    KEEP2(ma, a16); KEEP2(a8, target);
#pragma unroll 1
    do {
        asm volatile("" : "+r"(n));
        if (n) {
            const unsigned char* pg = redp + (s & 3) * 32768 + __shfl_sync(~0u, kh, 0) * 16384;
            const uint4 x = ldg_rlx128(pg + o16), y = ldg_rlx128(pg + o16 + 128);
            const uint2 z = ldg_rlx64(pg + o8);
            sts128u(a16, x); sts128u(a16 + 128, y); sts64u(a8, z);
            if (n > SPIN_LIMIT) __trap();
        }
        n++;
        mbar_wait(sb + O_BAR + 8 * (R_SPLIT && jj ? B_XF1 : B_RFULL), s & 1);
        const uint4 ra = lds128u(a16), rb = lds128u(a16 + 128);
        const uint2 rc = lds64u(a8);
        stsm4t(ma, ra.x, ra.y, ra.z, __byte_perm(ra.w, rc.x, 0x5410));
        stsm4t(ma + 2048, rb.x, rb.y, rb.z, __byte_perm(rb.w, rc.x, 0x7610));
        redo = __any_sync(~0u, orx(orx2(ra.w, rb.w, target), rc.y, target) > 0xffffu);
    } while (redo);
    if (lane == 0) mbar_arrive(sb + O_BAR + 8 * B_MEM);
    fence_async_smem();
    __syncwarp();
    if (lane == 0) mbar_arrive(sb + O_BAR + 8 * B_QKW);
    return n - 1;
}

#define F16(d, o) F4(d, o), F4(d, o + 4), F4(d, o + 8), F4(d, o + 12)
__device__ __forceinline__ void wg_ss128(float (&d)[64], uint64_t da, uint64_t db, int sc) {
    asm volatile("{\n.reg .pred p;\nsetp.ne.b32 p, %66, 0;\nwgmma.mma_async.sync.aligned.m64n128k16.f32.bf16.bf16 "
                 "{%0,%1,%2,%3,%4,%5,%6,%7,%8,%9,%10,%11,%12,%13,%14,%15,%16,%17,%18,%19,%20,%21,%22,%23,%24,%25,%26,%27,%28,%29,%30,%31,"
                 "%32,%33,%34,%35,%36,%37,%38,%39,%40,%41,%42,%43,%44,%45,%46,%47,%48,%49,%50,%51,%52,%53,%54,%55,%56,%57,%58,%59,%60,%61,%62,%63}, "
                 "%64, %65, p, 1, 1, 1, 1;\n}"
                 : F16(d, 0), F16(d, 16), F16(d, 32), F16(d, 48) : "l"(da), "l"(db), "r"(sc));
}
__device__ __forceinline__ void stg_rlx32(void* p, uint32_t v) { asm volatile("st.relaxed.gpu.global.u32 [%0], %1;" ::"l"(p), "r"(v) : "memory"); }

__global__ void __cluster_dims__(2, 1, 1) __launch_bounds__(512, 1)
rmt_main(const __grid_constant__ CUtensorMap tm_x, const __grid_constant__ CUtensorMap tm_wq, const __grid_constant__ CUtensorMap tm_wk,
         const __grid_constant__ CUtensorMap tm_wv, const __grid_constant__ CUtensorMap tm_wo, const bf16* __restrict__ mem0,
         const Tune tn, const __grid_constant__ FftMaps fm, const __grid_constant__ CUtensorMap tm_o,
         const __grid_constant__ CUtensorMap tm_w2, bf16* __restrict__ out) {
    extern __shared__ __align__(1024) unsigned char smem_raw[];
    const uint32_t sb = smem_u32(smem_raw);
    if ((sb & 0x3FFFF) != SM_BASE) __trap();
    GT(6);
    const int cid = blockIdx.x >> 1, kh = blockIdx.x & 1;
    const int tpc = cid < 4 ? 62 + cid : cid - 4;
    int h, nh;
    if (tpc < 32) { h = (tpc >> 4) * 8 + (tpc & 7); nh = (tpc >> 3) & 1; }
    else if (tpc < 60) { int u = tpc - 32, r = u % 14; h = 16 + (u / 14) * 7 + r % 7; nh = r / 7; }
    else if (tpc < 62) { GT(0); fft_rest((tpc - 60) * 2 + kh, fm, sb, tn.opt); GT(3); return; }
    else { h = 30 + ((tpc - 62) >> 1); nh = tpc & 1; }
    const int j = nh * 2 + kh, role = h * 4 + j;
    const int wgi = __shfl_sync(~0u, threadIdx.x >> 7, 0);
    const int w = __shfl_sync(~0u, (threadIdx.x >> 5) & 3, 0);
    const int tid = threadIdx.x & 127, lane = tid & 31;
#define PIN_IDS() const int tid = __shfl_sync(~0u, threadIdx.x & 127, threadIdx.x & 31), lane = tid & 31
#define OPAQUE_IDS() int tid_ = tid; asm volatile("" : "+r"(tid_)); const int tid = tid_, lane = tid_ & 31; (void)lane
    unsigned char* const redp = (unsigned char*)(((uintptr_t)g_red + 32767) & ~(uintptr_t)32767);
    const uint32_t bars = sb + O_BAR;

    if (threadIdx.x < B_COUNT) {
        const int i = threadIdx.x;
        mbar_init(bars + 8 * i, i == B_XFULL && !X_HALF ? 2 : i < B_QDONE ? 1 : i < B_GE ? 4 : i < B_XPE ? 8 : i < B_QKW ? 12 : 16);
        asm volatile("fence.mbarrier_init.release.cluster;" ::: "memory");
        fence_async_smem();
    } else if (threadIdx.x >= 64 && threadIdx.x < 71) {
        const int i = threadIdx.x - 64;
        const CUtensorMap* m = i == 0 ? &tm_wk : i == 1 ? &tm_wq : i == 2 ? &fm.x : i == 3 ? &tm_x : i == 4 ? &tm_wv : i == 5 ? &tm_wo : &fm.y;
        asm volatile("prefetch.tensormap [%0];" ::"l"(m) : "memory");
    }
    __syncthreads();
    const int wc0 = h * 128 + nh * 64;
#define W_LOAD(i)                                                                                                     \
    if (lane == 0) {                                                                                                  \
        mbar_expect_tx(bars + 8 * (B_W + (i)), 16384);                                                                \
        tma2d(sb + ((i) < 4 ? O_XB : (i) < 8 ? O_WO : O_WV) + ((i) & 3) * 16384, (i) < 4 ? &tm_wk : (i) < 8 ? &tm_wq : &tm_wv, \
              wc0, kh * 512 + ((i) & 3) * 128, bars + 8 * (B_W + (i)));                                               \
    }
#define X_LOAD(dst, sg, u, bar) tma4d(sb + (dst), &tm_x, kh * 8 + (u) * 4, ((sg) & 63) * 4, bars + 8 * (bar))
#define X_REFILL(sg, u) { const int b_ = (X_HALF && (u)) ? B_XF1 : B_XFULL; if (EXP & 1) mbar_arrive(bars + 8 * b_); else { mbar_expect_tx(bars + 8 * b_, 16384); X_LOAD(O_XB + (u) * 20480, sg, u, b_); } }
    const int depth = (tn.opt >> 8) & 15, nearly = 8 + ((tn.opt >> 4) & 7);
    if (wgi == 0 && w == 3) {
        if (lane == 0) {
            mbar_expect_tx(bars + 8 * B_F1, 32768);
            tma_ld4(sb + O_F1, &fm.x, (role & 15) * 64, role >> 4, bars + 8 * B_F1);
        }
#pragma unroll 1
        for (int i = 0; i < nearly; i++) {
            if (i == depth - 2) mbar_wait(bars + 8 * B_F1, 0);
            if (i >= depth) mbar_wait(bars + 8 * (B_W + i - depth), 0);
            W_LOAD(i);
        }
    } else if (wgi == 1 && w == 2 && lane == 0 && role < 4 * (RA + 3)) tma4d_prefetch(&tm_x, j * 4, h * 4);
    GT(7);
    uint32_t mate;
    asm volatile("mapa.shared::cluster.u32 %0, %1, %2;" : "=r"(mate) : "r"(sb), "r"(kh ^ 1));
    if (wgi >= 2) fft_col<false, 1>(role >> 4, role & 15, &fm.x, &fm.y, sb + O_F1, bars + 8 * B_F1, (wgi - 2) * 4 + w, lane, 6);

    if (wgi < 2) {
        asm volatile("setmaxnreg.inc.sync.aligned.u32 176;");
        PIN_IDS();
        uint32_t a[32][4], sf = 0;
        {
            const uint32_t stage = sb + (wgi == 0 ? O_WO : O_XB);
            const uint32_t ad = stage + (((lane >> 4) & 1) * 8 + (lane & 7)) * 128 + (((2 * w + ((lane >> 3) & 1)) ^ (lane & 7)) << 4);
#pragma unroll
            for (int i = 0; i < 4; i++) {
                mbar_wait(bars + 8 * (B_W + 4 * (wgi ^ 1) + i), 0);
#pragma unroll
                for (int ks = 0; ks < 8; ks++) ldsm4t(a[i * 8 + ks], ad + (i * 8 + ks) * 2048);
            }
#pragma unroll
            for (int ks = 0; ks < 32; ks += 2) KEEP2(a[ks][0], a[ks + 1][0]);
            SCHED_FENCE();
            if (lane == 0) mbar_arrive(bars + 8 * (B_QDONE + wgi));
            if (wgi == 0) GT(10); else GT(11);
        }
        asm volatile("barrier.cluster.arrive.relaxed.aligned;" ::: "memory");
        asm volatile("barrier.cluster.wait.acquire.aligned;" ::: "memory");
        uint32_t kp[4];
#define X_PASS(d, dofs)                                                                                    \
        wg_fence();                                                                                        \
        _Pragma("unroll") for (int ks = 0; ks < 32; ks++) { if (ks == 0) wg_rs32<0>(d, a[ks], xdesc(ks) + (dofs)); else wg_rs32<1>(d, a[ks], xdesc(ks) - (ks >> 4) * 256 + (dofs)); } \
        wg_commit();                                                                                       \
        wg_wait<0>();
#define X_FINISH(sg) { if (wgi == 0) x_finish<0>(kp, sg, h, nh * 4 + w, kh, tid, sb); else x_finish<1>(kp, sg, h, nh * 4 + w, kh, tid, sb); }
        mbar_wait(bars + 8 * B_XP, 0);
        if (wgi == 0) GT(8);
#pragma unroll 1
        for (int sg = 0; sg < RA; sg++) {
            float d[16]; uint32_t sn[4];
            X_PASS(d, sg * 2048 - (int)((O_XB - O_WO) >> 4));
            if (sg > 0) {
                if (lane == 0) mbar_arrive(bars + 8 * B_XPE);
                x_wait(wgi, sg - 1, sb); X_FINISH(sg - 1);
            }
            x_split(d, sn, kp, kh);
            x_send(wgi, sn, sg, tid, sb, mate);
        }
        x_wait(wgi, RA - 1, sb); X_FINISH(RA - 1);
        const int lq = wgi == 0 ? 4 : 0;
        const uint32_t xbar = bars + 8 * (wgi ? B_QX : B_OPDONE);
#pragma unroll 1
        for (int s = 0; s < 64; s++) {
            TSI(s);
            uint32_t* ap = (uint32_t*)&g_alpha[((s & 1) * 32 + h) * (3 * 512) + wgi * 512 + ((nh * 4 + w) * 2 + kh) * 32] + lane;
            uint32_t mb0 = sb + O_MEM + (lane & 7) * 128 + (((lane >> 3) ^ (lane & 7)) << 4), mb1 = mb0 ^ 64;
            const uint32_t tag = ((s >> 1) & 1) ^ 1;
            const uint32_t tm = (lane & 7) ? ~0u : ~1u, tt = tag & ~tm;
            {
                float d[16]; uint32_t sn[4];
                mbar_wait(bars + 8 * B_XFULL, s & 1);
                mbar_wait(xbar, s & 1);
                TS(6);
                wg_fence();
#pragma unroll
                for (int ks = 0; ks < 32; ks++) {
                    if (ks == 0) wg_rs32<0>(d, a[ks], xdesc(ks)); else if (!(EXP & 4) || ks >= 8) wg_rs32<1>(d, a[ks], xdesc(ks));
                    if (ks == X_SEQ - 1) wg_commit();
                    if (X_HALF && ks == 15) { mbar_wait(bars + 8 * B_XF1, s & 1); wg_fence(); }
                }
                wg_commit();
                KEEP2(mb0, mb1); KEEPP(ap); KEEP2(tm, tt);
                SCHED_FENCE();
                wg_wait<1>();
                if (tid < lq) mbar_arrive(bars + 8 * B_QX);
                wg_wait<0>();
                TS(7);
                if (lane == 0) mbar_arrive(bars + 8 * B_MEM);
                x_split(d, sn, kp, kh);
                if (!(EXP & 8)) x_send(wgi, sn, s + RA, tid, sb, mate); else { KEEP2(sn[0], sn[1]); KEEP2(sn[2], sn[3]); KEEP2(kp[0], kp[1]); KEEP2(kp[2], kp[3]); }
                TS(4);
            }
            float e[2][4];
#pragma unroll
            for (int i = 0; i < 4; i++) e[0][i] = e[1][i] = 0.f;
            mbar_wait(bars + 8 * B_MEM, s & 1);
            TS(0);
#pragma unroll
            for (int ks = 0; ks < 32; ks += 2) {
                uint32_t b[4];
                ldsm4(b, ((ks & 2) ? mb1 : mb0) + kb_off(ks >> 2));
                mma16816(e[0], a[ks][0], a[ks][1], a[ks][2], a[ks][3], b[0], b[1]);
                mma16816(e[1], a[ks + 1][0], a[ks + 1][1], a[ks + 1][2], a[ks + 1][3], b[2], b[3]);
            }
            TS(2);
            if (QKW_POS == 0) { SCHED_FENCE(); if (lane == 0) mbar_arrive(bars + 8 * B_QKW); }
            stg_rlx32(ap, (pack_bf16(e[0][0] + e[1][0], e[0][1] + e[1][1]) & tm) | tt);
            stg_rlx32(ap + 32, (pack_bf16(e[0][2] + e[1][2], e[0][3] + e[1][3]) & tm) | tt);
            if (QKW_POS == 1 && lane == 0) mbar_arrive(bars + 8 * B_QKW);
            TS(3);
            if (wgi == 1) {
                const uint2* vp = &g_alpha[((s & 1) * 32 + h) * (3 * 512) + 1024 + w * 128 + lane];
                const uint32_t vs = sb + O_VM + tid * 16;
                KEEPP(vp); KEEP2(vs, 0);
                mbar_wait(bars + 8 * B_QST, s & 1);
                uint32_t n, bad;
                asm volatile("ld.shared.u32 %0, [%1];" : "=r"(n) : "r"(bars + 504) : "memory");
                wait_gtime(n + tn.d_v);
                TS(8);
                n = 0;
                do {
                    uint2 va[4];
#pragma unroll
                    for (int i = 0; i < 4; i++) va[i] = ldg_rlx64(vp + i * 32);
                    if (++n > SPIN_LIMIT) __trap();
                    bad = (orx2(va[0].x, va[1].x, tag) | orx2(va[2].x, va[3].x, tag)) & 1;
                    sts128u(vs, make_uint4((add_bf16x2(va[0].x, va[1].x) & ~1u) | ((~s ^ bad) & 1), add_bf16x2(va[0].y, va[1].y),
                                                             add_bf16x2(va[2].x, va[3].x), add_bf16x2(va[2].y, va[3].y)));
                } while (__any_sync(~0u, bad));
                TS(9);
                TSV(16 + w, n - 1);
                LT(s, 4 + w, n - 1);
            }
            if (!(EXP & 8)) {
                x_wait(wgi, s + RA, sb);
                mbar_wait(bars + 8 * FIN_BAR, s & 1);
                X_FINISH(s + RA);
                TS(5);
            }
        }
        sts32(bars + 508, sf);
        TSDUMP();
        asm volatile("bar.arrive 7, 512;" ::: "memory");
        float d[64];
        int st = 0, ph = 0;
#pragma unroll 1
        for (int kt = 0; kt < 64; kt++) {
            mbar_wait(bars + 8 * (B_GF + st), ph);
            if (kt == 0) GT(4);
            const uint64_t da = mkdesc(SM_BASE + st * 32768 + wgi * 8192, 128, 1024, 0), db = mkdesc(SM_BASE + st * 32768 + 16384, 8192, 1024, 1);
            wg_fence();
#pragma unroll
            for (int k = 0; k < 4; k++) wg_ss128(d, da + k * 16, db + k * 128, kt | k);
            wg_commit();
            if (kt > 0) {
                wg_wait<1>();
                if (lane == 0) mbar_arrive(bars + 8 * (B_GE + (st == 0 ? G_ST - 1 : st - 1)));
            }
            if (++st == G_ST) { st = 0; ph ^= 1; }
        }
        wg_wait<0>();
        {
            const uint32_t sl = sb + O_F1 + (wgi * 4 + w) * 4096;
#pragma unroll
            for (int i = 0; i < 8; i++)
                stsm4(sl + (lane & 15) * 256 + (((2 * i + (lane >> 4)) ^ (lane & 7)) << 4), pack_bf16(d[8 * i], d[8 * i + 1]),
                      pack_bf16(d[8 * i + 2], d[8 * i + 3]), pack_bf16(d[8 * i + 4], d[8 * i + 5]), pack_bf16(d[8 * i + 6], d[8 * i + 7]));
            __syncwarp();
            bf16* op = out + (size_t)((role >> 3) * 128 + wgi * 64 + w * 16 + (lane >> 4)) * 2048 + 1024 + (role & 7) * 128 + (lane & 15) * 8;
#pragma unroll
            for (int i = 0; i < 8; i++) {
                const int r = 2 * i + (lane >> 4);
                const uint4 v = lds128u(sl + r * 256 + (((lane & 15) ^ (r & 7)) << 4));
                stg128(op + (size_t)i * 4096, v.x, v.y, v.z, v.w);
            }
        }
        GT(5);
    } else if (wgi == 2) {
        asm volatile("setmaxnreg.dec.sync.aligned.u32 64;");
        PIN_IDS();
        asm volatile("barrier.cluster.arrive.relaxed.aligned;" ::: "memory");
        if (w == 0) {
            mbar_wait(bars + 8 * B_KDONE, 0);
            if (lane == 0) { X_REFILL(RA, 0); X_REFILL(RA, 1); }
            mbar_wait(bars + 8 * B_QDONE, 0);
            if (lane == 0) { mbar_expect_tx(bars + 8 * B_XP, 65536); for (int i = 0; i < 4; i++) X_LOAD(O_WO + i * 16384, i >> 1, i & 1, B_XP); }
#pragma unroll 1
            for (int i = nearly; i < 12; i++) { mbar_wait(bars + 8 * (B_W + i - depth), 0); W_LOAD(i); }
        }
        asm volatile("barrier.cluster.wait.acquire.aligned;" ::: "memory");
#pragma unroll 1
        for (int i = 8; i < 12; i++) mbar_wait(bars + 8 * (B_W + i), 0);
        GT(12);
        uint32_t sf = 0, tref = gtime() - 4000;
        uint32_t* const stp = lane < 8 ? (uint32_t*)g_qst + role * 8 + lane : (uint32_t*)g_stamp + role;
#define STAMP(st) { mbar_wait(bars + 8 * B_MEM, (st) & 1); if (lane < 9) stg_rlx32(stp, gtime()); }
#define V_PASS(d)                                                                                          \
        wg_fence();                                                                                        \
        _Pragma("unroll") for (int ks = 0; ks < 32; ks++) {                                                \
            constexpr uint64_t da0 = mkdesc(SM_BASE + O_WV, 16, 1024, 1);                                  \
            if (ks == 0) wg_ss40<0>(d, da0 + ks * 128, xdesc(ks)); else wg_ss40<1>(d, da0 + ks * 128, xdesc(ks)); \
            if (ks == V_SEQ - 1) wg_commit();                                                              \
        }                                                                                                  \
        wg_commit();                                                                                       \
        if (V_SEQ) wg_wait<1>();                                                                           \
        if (V_SEQ && lane == 0) mbar_arrive(bars + 8 * B_VA);        \
        wg_wait<0>();
        mbar_wait(bars + 8 * B_XP, 0);
        {
            uint32_t kp[4];
#pragma unroll 1
            for (int sg = 0; sg <= RA; sg++) {
                float d[20]; uint32_t sn[4];
                if (sg < RA) {
#pragma unroll
                    for (int i = 0; i < 20; i++) d[i] = 0.f;
#pragma unroll 1
                    for (int kb = 0; kb < 8; kb++) {
                        const uint64_t da = mkdesc(SM_BASE + O_WV, 16, 1024, 1) + kb * 512, db = mkdesc(SM_BASE + O_WO, 16, 4096, 1) + sg * 2048 + (kb >> 2) * 1024 + (kb & 3) * 64;
                        wg_fence();
#pragma unroll
                        for (int i = 0; i < 4; i++) wg_ss40<1>(d, da + i * 128, db + i * 2);
                        wg_commit();
                    }
                    wg_wait<0>();
                }
                if (sg == RA - 1) {
                    if (lane == 0) mbar_arrive(bars + 8 * B_XPE);
                    if (w == 0) {
                        mbar_wait(bars + 8 * B_XPE, 0);
                        GT(9);
                        if (lane == 0) {
                            mbar_expect_tx(bars + 8 * B_WO, 65536);
#pragma unroll
                            for (int i = 0; i < 4; i++) tma2d(sb + O_WO + i * 16384, &tm_wo, j * 256 + i * 64, h * 128, bars + 8 * B_WO);
                        }
                    }
                }
                if (sg > 0) { x_wait(2, sg - 1, sb); x_finish<2>(kp, sg - 1, h, nh * 4 + w, kh, tid, sb); }
                if (sg < RA) { x_split(d, sn, kp, kh); x_send(2, sn, sg, tid, sb, mate); }
            }
        }
        if (STAMP_V && w == 2) STAMP(0);
#pragma unroll 1
        for (int s = 0; s < 64; s++) {
            TSI(s);
            OPAQUE_IDS();
            uint2* ap = &g_alpha[((s & 1) * 32 + h) * (3 * 512) + 1024 + ((nh * 4 + w) * 2 + kh) * 32 + lane];
            KEEPP(ap);
            float d[20];
            mbar_wait(bars + 8 * B_QKW, s & 1);
            TS(0);
            if (s == 0) GT(14);
            V_PASS(d);
            TS(1);
            stg_rlx64(ap, (pack_bf16(d[16], d[17]) & ~1u) | (((s >> 1) & 1) ^ 1), pack_bf16(d[18], d[19]));
            if (lane == 0) mbar_arrive(bars + 8 * B_XEMPTY);
            if (s == 63) break;
            uint32_t sn[4], kp[4];
            x_split(d, sn, kp, kh);
            if (w == 3) {
                uint32_t n = 0, mx;
                do {
                    const uint4 st = ldg_rlx128(&g_stamp[lane]);
                    mx = __reduce_max_sync(~0u, max(max(st.x - tref, st.y - tref), max(st.z - tref, st.w - tref)));
                    if (DBG_TIMING) TSV(14, mx - __reduce_min_sync(~0u, min(min(st.x - tref, st.y - tref), min(st.z - tref, st.w - tref))));
                } while (mx >= 200000u && ++n < 64);
                tref = mx < 200000u ? tref + mx + 1 : gtime();
                TSV(12, clk()); TSV(13, n);
            }
            if (w == 0) {
                mbar_wait(bars + 8 * B_XEMPTY, s & 1);
                mbar_wait(bars + 8 * B_SRDY, s & 1);
                if (lane == 0) { X_REFILL(s + RA + 1, 0); X_REFILL(s + RA + 1, 1); }
            } else if (w == 1) {
                const uint4* hb = &g_kvq[(((s + 1) & 3) * 32 + h) * (3 * 512)];
                if (V_KEEP) { mbar_wait(bars + 8 * B_SRDY, s & 1); wait_clk(clk(), tn.spread); } else mbar_wait(bars + 8 * B_X0, s & 1);
                if (lane == 0) {
                    if (EXP & 2) mbar_arrive(bars + 8 * B_KVFULL); else {
                    mbar_expect_tx(bars + 8 * B_KVFULL, 18432);
                    bulk_g2s(sb + O_KVQ, hb + 512, 16384, bars + 8 * B_KVFULL);
                    bulk_g2s(sb + O_KVQ + 16384, hb + j * 128, 2048, bars + 8 * B_KVFULL);
                    }
                }
            }
            mbar_wait(bars + 8 * B_OPDONE, (s + 1) & 1);
            if (!(EXP & 8)) x_send(2, sn, s + RA, tid, sb, mate); else { KEEP2(sn[0], sn[1]); KEEP2(sn[2], sn[3]); KEEP2(kp[0], kp[1]); KEEP2(kp[2], kp[3]); }
            if (w == 3) {
                wait_gtime(tref + tn.d_r);
                if (lane <= R_SPLIT) {
                    const uint32_t bytes = 16384 >> R_SPLIT, bar = bars + 8 * (lane ? B_XF1 : B_RFULL);
                    mbar_expect_tx(bar, bytes);
                    bulk_g2s(sb + O_STG + lane * 8192, redp + (s & 3) * 32768 + kh * 16384 + lane * 8192, bytes, bar);
                }
                TSV(3, clk());
            }
            if (!V_LATE && !(EXP & 8)) { x_wait(2, s + RA, sb); x_finish<2>(kp, s + RA, h, nh * 4 + w, kh, tid, sb); TS(6); }
            if (DBG_TIMING && w == 0) { mbar_wait(bars + 8 * B_RFULL, s & 1); TS(4); }
            const uint32_t n = convert_mem(redp, s, kh, 0, w, lane, sb, sf); (void)n;
            TS(5);
            TSV(8 + w, n);
            LT(s, 8 + w, n);
            if (STAMP_V && w == 2) STAMP(s + 1);
            if (V_LATE && !(EXP & 8)) { x_wait(2, s + RA, sb); x_finish<2>(kp, s + RA, h, nh * 4 + w, kh, tid, sb); }
        }
        sts32(bars + 508, sf);
        TSDUMP();
        asm volatile("bar.arrive 7, 512;" ::: "memory");
    } else {
        asm volatile("setmaxnreg.dec.sync.aligned.u32 96;");
        PIN_IDS();
        GT(0);
        asm volatile("barrier.cluster.arrive.relaxed.aligned;" ::: "memory");
#define RED_CLEAR(st)                                                                                           \
        if (lane < 16) {                                                                                        \
            const uint32_t cb = ((st) & 4) ? 0x42800000u : 0u;                                                  \
            stg128(redp + ((st) & 3) * 32768 + role * 256 + lane * 16, 0, (role & 2) ? cb : 0u, 0, cb);        \
        }
        if (w == 0) {
            RED_CLEAR(0); RED_CLEAR(1); RED_CLEAR(2);
            if (lane == 0) { tma_st4(sb + O_F1, &fm.y, (role & 15) * 64, role >> 4); bulk_commit(); }
        }
        sts128u(sb + O_VM + tid * 16, make_uint4(0, 0, 0, 0));
        {
            uint4 v[4];
#pragma unroll
            for (int q = 0; q < 4; q++) v[q] = *(const uint4*)(mem0 + ((lane >> 3) + (q & 1) * 4) * 1024 + kh * 512 + (2 * w + (q >> 1)) * 64 + (lane & 7) * 8);
            mbar_wait(bars + 8 * B_KDONE, 0);
#pragma unroll
            for (int q = 0; q < 4; q++) {
                const int row = (lane >> 3) + (q & 1) * 4;
                sts128u(sb + O_MEM + kb_off(2 * w + (q >> 1)) + row * 128 + (((lane & 7) ^ row) << 4), v[q]);
            }
            fence_async_smem();
            __syncwarp();
            if (lane < 2) { mbar_arrive(bars + 8 * B_MEM); mbar_arrive(bars + 8 * B_QKW); }
            if (lane == 0) mbar_arrive(bars + 8 * B_OPDONE);
            if (tid == 0) mbar_arrive(bars + 8 * B_KVFULL);
        }
        asm volatile("barrier.cluster.wait.acquire.aligned;" ::: "memory");
        if (w == 0) {
            if (lane == 0) bulk_wait_all();
            __syncwarp();
            gbar_wait(&g_start, gbar_arrive(&g_start, 1, 256, lane), 0);
            GT(13);
        }
        if (w == 1) {
            mbar_wait(bars + 8 * (B_W + 10), 0);
            uint32_t t = gtime();
#pragma unroll 1
            for (int i = 0; i < 4; i++) { if (lane == 0) tma2d_prefetch(&tm_wo, j * 256 + i * 64, h * 128); t += tn.extra; if (i < 3) wait_gtime(t); }
        }
        bar_sync(1, 128);
        uint32_t sf = 0, xo[4];
#define XO_STORE(st) { uint32_t* op = (uint32_t*)g_ox + ((size_t)((st) * 4 + j) * 4096 + h * 128 + w * 32) * 4 + lane; op[0] = xo[0]; op[32] = xo[1]; op[64] = xo[2]; op[96] = xo[3]; }
#pragma unroll 1
        for (int s = 0; s < 64; s++) {
            TSI(s);
            OPAQUE_IDS();
            uint32_t kf[4][4], qf[4];
            const uint32_t l03 = lane < 4;
            const uint32_t tg = ((s >> 2) & 1) ^ 1;
            {
                const uint32_t ka = sb + O_KVQ + w * 2048 + lane * 16, qa = sb + O_KVQ + 16384 + w * 512 + lane * 16;
                uint32_t n = s == 0;
                bool redo;
#pragma unroll 1
                do {
                    asm volatile("" : "+r"(n));
                    if (n) {
                        const uint4* hb = &g_kvq[((s & 3) * 32 + __shfl_sync(~0u, h, 0)) * (3 * 512)];
                        uint4 x[4], y[4], z;
                        do {
#pragma unroll
                            for (int i = 0; i < 4; i++) { x[i] = ldg_rlx128(hb + 512 + w * 128 + i * 32 + lane); y[i] = ldg_rlx128(hb + 1024 + w * 128 + i * 32 + lane); }
                            z = ldg_rlx128(hb + j * 128 + w * 32 + lane);
                            if (++n > SPIN_LIMIT) __trap();
                        } while (__any_sync(~0u, (orx2(y[0].x, y[1].x, tg) | orx2(y[2].x, y[3].x, tg)) & 1));
#pragma unroll
                        for (int i = 0; i < 4; i++) { sts128u(ka + i * 512, x[i]); sts128u(ka + 8192 + i * 512, y[i]); }
                        sts128u(qa, z);
                        fence_async_smem();
                    }
                    n++;
                    mbar_wait(bars + 8 * B_KVFULL, s & 1);
#pragma unroll
                    for (int i = 0; i < 4; i++) ldsm4t(kf[i], ka + i * 512);
                    ldsm4t(qf, qa);
                    redo = __any_sync(~0u, or3(or3(tags4(kf[0], tg), tags4(kf[1], tg), tags4(kf[2], tg)), tags4(kf[3], tg), tags4(qf, tg)) & l03 & ((EXP & 10) ? s >> 8 : ~0u));
                } while (redo);
                if (w == 0) TSV(22, n - 1);
            }
            TS(9);
            if (s == 0) GT(15);
            if (s > 0) {
                if (XO_POS == 0) XO_STORE(s - 1);
                const uint32_t n = convert_mem(redp, s - 1, kh, 1, w, lane, sb, sf); (void)n;
                TS(11);
                TSV(16 + w, n);
                LT(s - 1, 12 + w, n);
                if (XO_POS == 1) XO_STORE(s - 1);
                if (w == 1 && s < 62) RED_CLEAR(s + 2);
            }
            const uint32_t tag = ((s >> 1) & 1) ^ 1;
            const uint4* ap = (const uint4*)&g_alpha[((s & 1) * 32 + h) * (3 * 512) + w * 128] + lane;
            const uint32_t l16 = sb + lane * 16, l4 = sb + lane * 4;
            const uint32_t sw = l16 + O_S + w * 2560, sr = l4 + O_S + w * 128;
            uint32_t pw = sb + O_P + ((lane >> 1) & 1) * 704 + (2 * w + (lane >> 4)) * 16 + ((lane >> 2) & 3) * 4 + (lane & 1) * 2;
            int lim = (lane & 2) ? 8 * j + 2 * w + (lane >> 4) - 2 * ((lane >> 2) & 3) - (lane & 1) : 64;
            const uint32_t aa = l16 + O_STG + w * 1024;
            unsigned char* pa = redp + (s & 3) * 32768 + red_grp(j * 16 + (tid >> 3));
            unsigned char* pb = pa + 512 + ((lane >> 3) & 1) * 64 + (lane & 7) * 8;
            pa += (lane & 7) * 16;
            KEEPP(pa); KEEPP(pb);
            KEEP2(l16, l4); KEEP2(pw, lim); KEEP2(l03, tag);
            TS(0);
            if (w == 0) {
                const uint32_t* qp = (const uint32_t*)g_qst + h * 32 + lane;
                KEEPP(qp);
                mbar_wait(bars + 8 * B_MEM, s & 1);
                uint32_t tq = gtime() - 1024;
                if (!STAMP_V && lane < 9) stg_rlx32(lane < 8 ? (uint32_t*)g_qst + role * 8 + lane : (uint32_t*)g_stamp + role, tq + 1024);
                wait_clk(clk(), tn.d_q);
                uint32_t n = 0, mx;
                do { mx = __reduce_max_sync(~0u, ldg_rlx32(qp) - tq); } while (mx > 100000u && ++n < 16);
                TSV(13, n);
                LT(s, 2, n);
                tq += mx <= 100000u ? mx : 1024;
                if (lane == 0) { sts32(bars + 504, tq); mbar_arrive(bars + 8 * B_QST); }
                TS(14);
                mbar_wait(bars + 8 * B_QKW, s & 1);
                TS(1);
                wait_gtime(tq + tn.d_alpha);
                if (lane == 0) {
                    mbar_expect_tx(bars + 8 * B_AFULL, 8192);
                    bulk_g2s(sb + O_STG, ap, 8192, bars + 8 * B_AFULL);
                }
                if (s == 0) { mbar_wait(bars + 8 * B_WO, 0); GT(1); }
            }
            {
                uint32_t n = 0;
                bool redo;
#pragma unroll 1
                do {
                    asm volatile("" : "+r"(n));
                    if (n) {
                        uint4 x[4];
#pragma unroll
                        for (int q = 0; q < 4; q++) x[q] = ldg_rlx128(ap + (q >> 1) * 256 + (q & 1) * 32);
#pragma unroll
                        for (int q = 0; q < 4; q++) sts128u(aa + (q >> 1) * 4096 + (q & 1) * 512, x[q]);
                        __syncwarp();
                        if (n > SPIN_LIMIT) __trap();
                    }
                    n++;
                    mbar_wait(bars + 8 * B_AFULL, s & 1);
                    TS(12);
                    if (V_SEQ) mbar_wait(bars + 8 * B_VA, s & 1);
                    uint32_t qa[2][4], ka[2][4];
#pragma unroll
                    for (int u = 0; u < 2; u++) { ldsm4t(qa[u], aa + u * 512); ldsm4t(ka[u], aa + 4096 + u * 512); }
                    float sa[5][4];
#pragma unroll
                    for (int i = 0; i < 5; i++) sa[i][0] = sa[i][1] = sa[i][2] = sa[i][3] = 0.f;
#pragma unroll
                    for (int u = 0; u < 2; u++) {
                        const uint32_t q0 = add_bf16x2(qa[u][0], qa[u][2]), q1 = add_bf16x2(qa[u][1], qa[u][3]);
                        mma16816(sa[1], q0, qf[2 * u], q1, qf[2 * u + 1], kf[2 * u][0], kf[2 * u][1]);
                        mma16816(sa[2], q0, qf[2 * u], q1, qf[2 * u + 1], kf[2 * u][2], kf[2 * u][3]);
                        mma16816(sa[3], q0, qf[2 * u], q1, qf[2 * u + 1], kf[2 * u + 1][0], kf[2 * u + 1][1]);
                        mma16816(sa[4], q0, qf[2 * u], q1, qf[2 * u + 1], kf[2 * u + 1][2], kf[2 * u + 1][3]);
                        const uint32_t k0 = add_bf16x2(ka[u][0], ka[u][2]), k1 = add_bf16x2(ka[u][1], ka[u][3]);
                        mma16816(sa[0], q0, qf[2 * u], q1, qf[2 * u + 1], k0, k1);
                        if (u == 0) SCHED_FENCE();
                    }
                    redo = __any_sync(~0u, (or3(tags4(qa[0], tag), tags4(ka[0], tag), tags4(qa[1], tag)) | tags4(ka[1], tag)) & l03);
#pragma unroll
                    for (int i = 1; i <= 5; i++) sts128(sw + (i % 5) * 512, sa[i % 5][0], sa[i % 5][1], sa[i % 5][2], sa[i % 5][3]);
                } while (redo);
                if (w == 0) TSV(20, n - 1);
                if (n > 1) LT(s, 3, 0x10000 + s);
            }
            TS(2);
            bar_sync(1, 128);
            float sc[5];
            {
                float x[4][5];
#pragma unroll
                for (int q = 0; q < 4; q++)
#pragma unroll
                    for (int n = 0; n < 5; n++) asm volatile("ld.shared.f32 %0, [%1];" : "=f"(x[q][n]) : "r"(sr + q * 2560 + n * 512) : "memory");
#pragma unroll
                for (int n = 0; n < 5; n++) sc[n] = (x[0][n] + x[1][n]) + (x[2][n] + x[3][n]);
            }
            TS(15);
#pragma unroll
            for (int n = 1; n < 5; n++) if (8 * (n - 1) > lim) sc[n] = MASK_VAL;
            float m = fmaxf(fmaxf(fmaxf(sc[0], sc[1]), fmaxf(sc[2], sc[3])), sc[4]);
            m = fmaxf(m, __shfl_xor_sync(~0u, m, 1));
            m = fmaxf(m, __shfl_xor_sync(~0u, m, 4));
            m = fmaxf(m, __shfl_xor_sync(~0u, m, 8));
            SCHED_FENCE();
            uint4 vf[4];
#pragma unroll
            for (int i = 0; i < 4; i++) vf[i] = lds128u(l16 + O_KVQ + 8192 + w * 2048 + i * 512);
            m *= -SM_SCALE_LOG2;
#pragma unroll
            for (int n = 0; n < 5; n++) {
                const uint32_t pv = pack_bf16(ex2(fmaf(sc[n], SM_SCALE_LOG2, m)), 0.f);
                asm volatile("st.shared.u16 [%0], %1;" ::"r"(pw + n * 128), "h"((uint16_t)pv) : "memory");
            }
            if (V_KEEP) { KEEP2(vf[0].x, vf[1].x); KEEP2(vf[2].x, vf[3].x); SCHED_FENCE(); }
            bar_sync(1, 128);
            TS(3);
            if (lane == 0) mbar_arrive(bars + 8 * B_SRDY);
            float ox[2][4], sm[4], sx[4], cc[4][4];
#pragma unroll 1
            for (uint32_t nv = 0;; nv++) {
                uint32_t pf[4], p0, px[4], px0;
                ldsm4(pf, l16 + O_P + 128);
                ldsm4(px, l16 + O_P + 128 + 704);
                asm volatile("ld.shared.u32 %0, [%1];" : "=r"(p0) : "r"(l4 + O_P) : "memory");
                asm volatile("ld.shared.u32 %0, [%1];" : "=r"(px0) : "r"(l4 + O_P + 704) : "memory");
                float o[2][4];
#pragma unroll
                for (int i = 0; i < 4; i++) o[0][i] = o[1][i] = ox[0][i] = ox[1][i] = sm[i] = sx[i] = 0.f;
                constexpr uint32_t ONE2 = 0x3f803f80u;
                mma1688(sm, ONE2, ONE2, p0);
                mma1688(sx, ONE2, ONE2, px0);
#pragma unroll
                for (int c = 0; c < 2; c++) {
#pragma unroll
                    for (int u = 0; u < 2; u++) mma16816(o[u], vf[2 * u + c].x, vf[2 * u + c].y, vf[2 * u + c].z, vf[2 * u + c].w, pf[2 * c], pf[2 * c + 1]);
#pragma unroll
                    for (int u = 0; u < 2; u++) mma16816(ox[u], vf[2 * u + c].x, vf[2 * u + c].y, vf[2 * u + c].z, vf[2 * u + c].w, px[2 * c], px[2 * c + 1]);
                    mma16816(sm, ONE2, ONE2, ONE2, ONE2, pf[2 * c], pf[2 * c + 1]);
                    mma16816(sx, ONE2, ONE2, ONE2, ONE2, px[2 * c], px[2 * c + 1]);
                }
                const uint32_t vbad = orx(orx(orx2(vf[0].x, vf[1].x, tg), vf[2].x, tg), vf[3].x, tg);
                uint4 vm;
                {
                    uint32_t n = 0;
                    bool redo;
#pragma unroll 1
                    do {
                        vm = lds128v(l16 + O_VM + w * 512);
                        float o2[2][4];
#pragma unroll
                        for (int i = 0; i < 4; i++) { o2[0][i] = o[0][i]; o2[1][i] = o[1][i]; }
                        mma1688(o2[0], vm.x, vm.y, p0);
                        mma1688(o2[1], vm.z, vm.w, p0);
                        redo = __any_sync(~0u, ((vm.x ^ ~s) & 1) && ++n < SPIN_LIMIT);
                        const uint32_t oa = l4 + O_O + w * 512;
                        sts32(oa, pack_bf16(o2[0][0], o2[0][1]));
                        sts32(oa + 128, pack_bf16(o2[0][2], o2[0][3]));
                        sts32(oa + 256, pack_bf16(o2[1][0], o2[1][1]));
                        sts32(oa + 384, pack_bf16(o2[1][2], o2[1][3]));
                    } while (redo);
                    if (w == 0) TSV(21, n);
                }
                TS(4);
                fence_async_smem();
                mma1688(ox[0], vm.x, vm.y, px0);
                mma1688(ox[1], vm.z, vm.w, px0);
                sm[0] = rcp(sm[0]); sm[1] = rcp(sm[1]);
                bar_sync(1, 128);
                if (!V_KEEP && lane == 0 && nv == 0) mbar_arrive(bars + 8 * B_X0);
                TS(5);
#define OP_ISSUE(t0, t1)                                                                                       \
                wg_fence();                                                                                    \
                _Pragma("unroll") for (int ks = 0; ks < 8; ks++)                                               \
                    _Pragma("unroll") for (int t = t0; t < t1; t++) {                                          \
                        constexpr uint64_t da0 = mkdesc(SM_BASE + O_WO, 16, 1024, 1), db0 = mkdesc(SM_BASE + O_O, 128, 128, 0); \
                        if (ks == 0) wg_ss8<0>(cc[t], da0 + t * 1024, db0); else wg_ss8<1>(cc[t], da0 + t * 1024 + ks * 128, db0 + ks * 16); \
                    }                                                                                          \
                wg_commit();
                OP_ISSUE(0, (OP_SPLIT ? 2 : 4));
                if (!bar_or(1, 128, vbad & ((EXP & 10) ? s >> 8 : ~0u))) break;
                wg_wait<0>();
                const uint4* vp = &g_kvq[((s & 3) * 32 + h) * (3 * 512) + 1024 + w * 128 + __shfl_sync(~0u, lane, lane)];
#pragma unroll
                for (int i = 0; i < 4; i++) vf[i] = ldg_rlx128(vp + i * 32);
                if (nv > SPIN_LIMIT) __trap();
                bar_sync(1, 128);
            }
            {
                const float i0 = sm[0], i1 = sm[1];
#pragma unroll
                for (int hf = 0; hf < 2; hf++) {
                    if (hf == 0 || OP_SPLIT) wg_wait<0>();
                    if (hf == 0) TS(6);
                    if (OPD_EARLY && hf == OP_SPLIT && lane == 0) mbar_arrive(bars + 8 * B_OPDONE);
                    asm volatile("red.relaxed.gpu.global.add.noftz.v4.bf16x2 [%0], {%1,%2,%3,%4};" ::"l"(pa + hf * 128),
                                 "r"(pack_bf16(cc[2 * hf][0] * i0, cc[2 * hf][1] * i1)), "r"(pack_bf16(cc[2 * hf][2] * i0, cc[2 * hf][3] * i1)),
                                 "r"(pack_bf16(cc[2 * hf + 1][0] * i0, cc[2 * hf + 1][1] * i1)), "r"(pack_bf16(cc[2 * hf + 1][2] * i0, 1.f)) : "memory");
                    if (OP_SPLIT && hf == 0) { SCHED_FENCE(); OP_ISSUE(2, 4); }
                }
                asm volatile("red.relaxed.gpu.global.add.noftz.v2.bf16x2 [%0], {%1,%2};" ::"l"(pb), "r"(pack_bf16(cc[1][3] * i1, cc[3][3] * i1)), "r"(0x3f800000u) : "memory");
                if (!OPD_EARLY && lane == 0) mbar_arrive(bars + 8 * B_OPDONE);
                SCHED_FENCE();
                TS(7);
            }
            {
                const float ix0 = rcp(sx[0]), ix1 = rcp(sx[1]);
                xo[0] = pack_bf16(ox[0][0] * ix0, ox[0][1] * ix1); xo[1] = pack_bf16(ox[0][2] * ix0, ox[0][3] * ix1);
                xo[2] = pack_bf16(ox[1][0] * ix0, ox[1][1] * ix1); xo[3] = pack_bf16(ox[1][2] * ix0, ox[1][3] * ix1);
                if (XO_POS == 2) XO_STORE(s);
            }
            TS(8);
            if (w == 2) { LT(s, 0, gtime()); LT(s, 1, clk()); }
            if (s == 0) GT(2);
        }
        if (XO_POS < 2) XO_STORE(63);
        GT(3);
        sts32(bars + 508, sf);
        TSDUMP();
        bar_sync(7, 512);
        const int m0 = (role >> 3) * 16, nb = (role & 7) * 2;
#define W2_LOAD(st, kt) { mbar_expect_tx(bars + 8 * (B_GF + (st)), 32768); tma3d(sb + (st) * 32768 + 16384, &tm_w2, 0, (kt) * 64, nb, bars + 8 * (B_GF + (st))); }
        if (w == 1 && lane == 0) {
            fence_async_smem();
#pragma unroll 1
            for (int kt = 0; kt < G_ST; kt++) W2_LOAD(kt, kt);
        }
        if (w == 0) {
            gbar_wait(&g_end, gbar_arrive(&g_end, 1, 128, lane), 0);
            int st = 0, ph = 1;
#pragma unroll 1
            for (int kt = 0; kt < 64; kt++) {
                if (kt >= G_ST) mbar_wait(bars + 8 * (B_GE + st), ph);
                if (lane == 0) {
                    if (kt >= G_ST) W2_LOAD(st, kt);
                    tma2d(sb + st * 32768, &tm_o, kt * 128, m0, bars + 8 * (B_GF + st));
                }
                if (++st == G_ST) { st = 0; ph ^= 1; }
            }
        }
    }
}

typedef CUresult (*EncodeFn)(CUtensorMap*, CUtensorMapDataType, cuuint32_t, void*, const cuuint64_t*, const cuuint64_t*,
                             const cuuint32_t*, const cuuint32_t*, CUtensorMapInterleave, CUtensorMapSwizzle,
                             CUtensorMapL2promotion, CUtensorMapFloatOOBfill);

static void make_map(EncodeFn fn, CUtensorMap* m, const void* p, uint64_t cols, uint64_t rows, uint32_t bc, uint32_t br) {
    cuuint64_t dims[2] = {cols, rows}, strides[1] = {cols * 2};
    cuuint32_t box[2] = {bc, br}, es[2] = {1, 1};
    fn(m, CU_TENSOR_MAP_DATA_TYPE_BFLOAT16, 2, (void*)p, dims, strides, box, es, CU_TENSOR_MAP_INTERLEAVE_NONE,
       CU_TENSOR_MAP_SWIZZLE_128B, CU_TENSOR_MAP_L2_PROMOTION_L2_128B, CU_TENSOR_MAP_FLOAT_OOB_FILL_NONE);
}

static Tune h_tune = {480, 1920, 16 * 2 + 256 * 4, 100, 960, 300, 600};

extern "C" void kernel_launch(void* const* d_in, const int* in_sizes, int n_in, void* d_out, int out_size) {
    static bool init = false;
    static FftMaps fm;
    static CUtensorMap tm_x, tm_wq, tm_wk, tm_wv, tm_wo, tm_o, tm_wo2;
    if (!init) {
        void* fp = nullptr; cudaDriverEntryPointQueryResult qr;
        cudaGetDriverEntryPoint("cuTensorMapEncodeTiled", &fp, cudaEnableDefault, &qr);
        EncodeFn fn = (EncodeFn)fp;
        void* ox = nullptr; cudaGetSymbolAddress(&ox, g_ox);
        {
            cuuint64_t dims[4] = {64, 8, 16, 256}, strides[3] = {2048, 128, 16384};
            cuuint32_t box[4] = {64, 8, 4, 4}, es[4] = {1, 1, 1, 1};
            fn(&tm_x, CU_TENSOR_MAP_DATA_TYPE_BFLOAT16, 4, d_in[3], dims, strides, box, es, CU_TENSOR_MAP_INTERLEAVE_NONE,
               CU_TENSOR_MAP_SWIZZLE_128B, CU_TENSOR_MAP_L2_PROMOTION_L2_128B, CU_TENSOR_MAP_FLOAT_OOB_FILL_NONE);
        }
        void* fy = nullptr; cudaGetSymbolAddress(&fy, g_fy);
        for (int i = 0; i < 3; i++) {
            const cuuint64_t pitch = i == 2 ? 4096 : 2048;
            cuuint64_t dims[4] = {1024, 8, 16, 16}, strides[3] = {pitch, 128 * pitch, 8 * pitch};
            cuuint32_t box[4] = {64, 1, 16, 16}, es[4] = {1, 1, 1, 1};
            fn(i == 0 ? &fm.x : i == 1 ? &fm.y : &fm.o, CU_TENSOR_MAP_DATA_TYPE_BFLOAT16, 4, i == 0 ? d_in[0] : i == 1 ? fy : d_out, dims, strides, box, es,
               CU_TENSOR_MAP_INTERLEAVE_NONE, CU_TENSOR_MAP_SWIZZLE_128B, CU_TENSOR_MAP_L2_PROMOTION_L2_256B, CU_TENSOR_MAP_FLOAT_OOB_FILL_NONE);
        }
        {
            cuuint64_t dims[3] = {64, 2048, 16}, strides[2] = {2048, 128};
            cuuint32_t box[3] = {64, 8, 16}, es[3] = {1, 1, 1};
            fn(&fm.y2, CU_TENSOR_MAP_DATA_TYPE_BFLOAT16, 3, fy, dims, strides, box, es, CU_TENSOR_MAP_INTERLEAVE_NONE,
               CU_TENSOR_MAP_SWIZZLE_128B, CU_TENSOR_MAP_L2_PROMOTION_L2_128B, CU_TENSOR_MAP_FLOAT_OOB_FILL_NONE);
        }
        for (int i = 0; i < 2; i++) {
            cuuint64_t dims[3] = {256 * 513 - 448, 8, 8}, strides[2] = {128, 256 * 1026};
            cuuint32_t box[3] = {72, 8, 8}, es[3] = {1, 1, 1};
            fn(i ? &fm.wi : &fm.wr, CU_TENSOR_MAP_DATA_TYPE_BFLOAT16, 3, d_in[1 + i], dims, strides, box, es, CU_TENSOR_MAP_INTERLEAVE_NONE,
               CU_TENSOR_MAP_SWIZZLE_NONE, CU_TENSOR_MAP_L2_PROMOTION_L2_128B, CU_TENSOR_MAP_FLOAT_OOB_FILL_NONE);
        }
        fm.w[0] = (const unsigned char*)d_in[1]; fm.w[1] = (const unsigned char*)d_in[2]; fm.w[2] = (const unsigned char*)d_in[3];
        make_map(fn, &tm_wq, d_in[5], 4096, 1024, 64, 128);
        make_map(fn, &tm_wk, d_in[6], 4096, 1024, 64, 128);
        make_map(fn, &tm_wv, d_in[7], 4096, 1024, 64, 128);
        make_map(fn, &tm_wo, d_in[8], 1024, 4096, 64, 128);
        {
            cuuint64_t dims[2] = {8192, 256}, strides[1] = {65536};
            cuuint32_t box[2] = {128, 16}, es[2] = {1, 1};
            fn(&tm_o, CU_TENSOR_MAP_DATA_TYPE_UINT64, 2, ox, dims, strides, box, es, CU_TENSOR_MAP_INTERLEAVE_NONE,
               CU_TENSOR_MAP_SWIZZLE_NONE, CU_TENSOR_MAP_L2_PROMOTION_L2_128B, CU_TENSOR_MAP_FLOAT_OOB_FILL_NONE);
        }
        {
            cuuint64_t dims[3] = {64, 4096, 16}, strides[2] = {2048, 128};
            cuuint32_t box[3] = {64, 64, 2}, es[3] = {1, 1, 1};
            fn(&tm_wo2, CU_TENSOR_MAP_DATA_TYPE_BFLOAT16, 3, d_in[8], dims, strides, box, es, CU_TENSOR_MAP_INTERLEAVE_NONE,
               CU_TENSOR_MAP_SWIZZLE_128B, CU_TENSOR_MAP_L2_PROMOTION_L2_128B, CU_TENSOR_MAP_FLOAT_OOB_FILL_NONE);
        }
        cudaFuncSetAttribute(rmt_main, cudaFuncAttributeMaxDynamicSharedMemorySize, MAIN_SMEM);
        init = true;
    }
    rmt_main<<<132, 512, MAIN_SMEM>>>(tm_x, tm_wq, tm_wk, tm_wv, tm_wo, (const bf16*)d_in[4], h_tune, fm, tm_o, tm_wo2, (bf16*)d_out);
}
```

```cpp
#include <cuda_runtime.h>
#include <cuda_bf16.h>
#include <cuda.h>
#include <stdint.h>

typedef __nv_bfloat16 bf16;

#define DBG_TIMING 0

#define SPIN_LIMIT (1u << 22)

__device__ __forceinline__ uint32_t smem_u32(const void* p) { return (uint32_t)__cvta_generic_to_shared(p); }
__device__ __forceinline__ uint32_t clk() { uint32_t c; asm volatile("mov.u32 %0, %%clock;" : "=r"(c)::"memory"); return c; }
#define SCHED_FENCE() sf ^= (uint32_t)clock64()
#define KEEP2(a, b) asm volatile("lop3.b32 %0, %0, %1, %2, 0x96;" : "+r"(sf) : "r"((uint32_t)(a)), "r"((uint32_t)(b)))
#define KEEPP(p) KEEP2((uintptr_t)(p), (uintptr_t)(p) >> 32)
__device__ __forceinline__ uint32_t gtime() { uint32_t c; asm volatile("mov.u32 %0, %%globaltimer_lo;" : "=r"(c)::"memory"); return c; }
__device__ __forceinline__ uint32_t gtime64() { uint64_t c; asm volatile("mov.u64 %0, %%globaltimer;" : "=l"(c)::"memory"); return (uint32_t)c; }
__device__ __forceinline__ void wait_clk(uint32_t t0, uint32_t d) {
    asm volatile("{\n.reg .pred p;\n.reg .s32 t;\n.reg .b64 c;\nWL:\nmov.u64 c, %%clock64;\ncvt.u32.u64 t, c;\nsub.s32 t, t, %0;\nsetp.lt.s32 p, t, 0;\n@p bra.uni WL;\n}" ::"r"(t0 + d) : "memory");
}
__device__ __forceinline__ void wait_gtime(uint32_t t1) {
    asm volatile("{\n.reg .pred p;\n.reg .s32 t;\n.reg .b64 c;\nWL:\nmov.u64 c, %%globaltimer;\ncvt.u32.u64 t, c;\nsub.s32 t, t, %0;\nsetp.lt.s32 p, t, 0;\n@p bra.uni WL;\n}" ::"r"(t1) : "memory");
}

__device__ __forceinline__ void mbar_init(uint32_t bar, uint32_t cnt) {
    asm volatile("mbarrier.init.shared::cta.b64 [%0], %1;" ::"r"(bar), "r"(cnt) : "memory");
}
__device__ __forceinline__ void mbar_arrive(uint32_t bar) {
    asm volatile("mbarrier.arrive.shared::cta.b64 _, [%0];" ::"r"(bar) : "memory");
}
__device__ __forceinline__ void mbar_expect_tx(uint32_t bar, uint32_t bytes) {
    asm volatile("mbarrier.arrive.expect_tx.shared::cta.b64 _, [%0], %1;" ::"r"(bar), "r"(bytes) : "memory");
}
__device__ __forceinline__ void mbar_wait(uint32_t bar, uint32_t parity) {
    asm volatile(
        "{\n.reg .pred p, q;\n.reg .u32 n;\nmov.u32 n, 0;\n"
        "WL:\nmbarrier.try_wait.parity.shared::cta.b64 p, [%0], %1;\n"
        "add.u32 n, n, 1;\nsetp.gt.u32 q, n, %2;\n@q trap;\n@!p bra.uni WL;\n}" ::"r"(bar), "r"(parity), "n"(SPIN_LIMIT) : "memory");
}
__device__ __forceinline__ void mbar_wait_cluster(uint32_t bar, uint32_t parity) {
    asm volatile(
        "{\n.reg .pred p, q;\n.reg .u32 n;\nmov.u32 n, 0;\n"
        "WL:\nmbarrier.try_wait.parity.acquire.cluster.shared::cta.b64 p, [%0], %1;\n"
        "add.u32 n, n, 1;\nsetp.gt.u32 q, n, %2;\n@q trap;\n@!p bra.uni WL;\n}" ::"r"(bar), "r"(parity), "n"(SPIN_LIMIT) : "memory");
}
__device__ __forceinline__ void tma2d(uint32_t dst, const CUtensorMap* m, int c0, int c1, uint32_t bar) {
    asm volatile("cp.async.bulk.tensor.2d.shared::cluster.global.mbarrier::complete_tx::bytes [%0], [%1, {%3, %4}], [%2];"
                 ::"r"(dst), "l"(m), "r"(bar), "r"(c0), "r"(c1) : "memory");
}
__device__ __forceinline__ void tma3d(uint32_t dst, const CUtensorMap* m, int c0, int c1, int c2, uint32_t bar) {
    asm volatile("cp.async.bulk.tensor.3d.shared::cluster.global.mbarrier::complete_tx::bytes [%0], [%1, {%3, %4, %5}], [%2];"
                 ::"r"(dst), "l"(m), "r"(bar), "r"(c0), "r"(c1), "r"(c2) : "memory");
}
__device__ __forceinline__ void tma4d(uint32_t dst, const CUtensorMap* m, int c2, int c3, uint32_t bar) {
    asm volatile("cp.async.bulk.tensor.4d.shared::cluster.global.mbarrier::complete_tx::bytes [%0], [%1, {%5, %5, %3, %4}], [%2];"
                 ::"r"(dst), "l"(m), "r"(bar), "r"(c2), "r"(c3), "r"(0) : "memory");
}
__device__ __forceinline__ void bulk_g2s(uint32_t dst, const void* src, uint32_t bytes, uint32_t bar) {
    asm volatile("cp.async.bulk.shared::cluster.global.mbarrier::complete_tx::bytes [%0], [%1], %2, [%3];"
                 ::"r"(dst), "l"(src), "r"(bytes), "r"(bar) : "memory");
}
__device__ __forceinline__ void tma4d_prefetch(const CUtensorMap* m, int c2, int c3) {
    asm volatile("cp.async.bulk.prefetch.tensor.4d.L2.global [%0, {%3, %3, %1, %2}];" ::"l"(m), "r"(c2), "r"(c3), "r"(0) : "memory");
}
__device__ __forceinline__ void tma2d_prefetch(const CUtensorMap* m, int c0, int c1) {
    asm volatile("cp.async.bulk.prefetch.tensor.2d.L2.global [%0, {%1, %2}];" ::"l"(m), "r"(c0), "r"(c1) : "memory");
}
__device__ __forceinline__ void fence_async_smem() { asm volatile("fence.proxy.async.shared::cta;" ::: "memory"); }
__device__ __forceinline__ void fence_gpu() { asm volatile("fence.acq_rel.gpu;" ::: "memory"); }
__device__ __forceinline__ float rcp(float x) { float r; asm("rcp.approx.ftz.f32 %0, %1;" : "=f"(r) : "f"(x)); return r; }
__device__ __forceinline__ void bar_sync(int id, int n) { asm volatile("bar.sync %0, %1;" ::"r"(id), "r"(n) : "memory"); }

__device__ __forceinline__ bool bar_or(int id, int n, uint32_t x) {
    uint32_t r;
    asm volatile("{\n.reg .pred p, q;\n.reg .b32 t;\nand.b32 t, %3, 1;\nsetp.ne.u32 p, t, 0;\nbar.red.or.pred q, %1, %2, p;\nselp.u32 %0, 1, 0, q;\n}"
                 : "=r"(r) : "r"(id), "r"(n), "r"(x) : "memory");
    return __any_sync(~0u, r);
}
__device__ __forceinline__ uint32_t or3(uint32_t a, uint32_t b, uint32_t c) {
    uint32_t r; asm("lop3.b32 %0, %1, %2, %3, 0xFE;" : "=r"(r) : "r"(a), "r"(b), "r"(c)); return r;
}
__device__ __forceinline__ uint32_t pack_bf16(float lo, float hi) {
    uint32_t r; asm("cvt.rn.bf16x2.f32 %0, %1, %2;" : "=r"(r) : "f"(hi), "f"(lo)); return r;
}
__device__ __forceinline__ uint32_t add_bf16x2(uint32_t a, uint32_t b) {
    uint32_t r; asm volatile("add.rn.bf16x2 %0, %1, %2;" : "=r"(r) : "r"(a), "r"(b)); return r;
}
__device__ __forceinline__ uint32_t movm(uint32_t a) {
    uint32_t r; asm volatile("movmatrix.sync.aligned.m8n8.trans.b16 %0, %1;" : "=r"(r) : "r"(a)); return r;
}
__device__ __forceinline__ uint32_t orx(uint32_t acc, uint32_t a, uint32_t t) {
    uint32_t r; asm("lop3.b32 %0, %1, %2, %3, 0xF6;" : "=r"(r) : "r"(acc), "r"(a), "r"(t)); return r;
}
__device__ __forceinline__ uint32_t orx2(uint32_t a, uint32_t b, uint32_t t) {
    uint32_t r; asm("lop3.b32 %0, %1, %2, %3, 0x7E;" : "=r"(r) : "r"(a), "r"(b), "r"(t)); return r;
}
__device__ __forceinline__ float ex2(float x) { float r; asm("ex2.approx.ftz.f32 %0, %1;" : "=f"(r) : "f"(x)); return r; }
__device__ __forceinline__ void ldsm4t(uint32_t (&r)[4], uint32_t a) {
    asm volatile("ldmatrix.sync.aligned.m8n8.x4.trans.shared.b16 {%0,%1,%2,%3}, [%4];"
                 : "=r"(r[0]), "=r"(r[1]), "=r"(r[2]), "=r"(r[3]) : "r"(a) : "memory");
}
__device__ __forceinline__ void ldsm4(uint32_t (&r)[4], uint32_t a) {
    asm volatile("ldmatrix.sync.aligned.m8n8.x4.shared.b16 {%0,%1,%2,%3}, [%4];"
                 : "=r"(r[0]), "=r"(r[1]), "=r"(r[2]), "=r"(r[3]) : "r"(a) : "memory");
}
__device__ __forceinline__ void stsm4t(uint32_t a, uint32_t r0, uint32_t r1, uint32_t r2, uint32_t r3) {
    asm volatile("stmatrix.sync.aligned.m8n8.x4.trans.shared.b16 [%0], {%1,%2,%3,%4};"
                 ::"r"(a), "r"(r0), "r"(r1), "r"(r2), "r"(r3) : "memory");
}
__device__ __forceinline__ void stsm4(uint32_t a, uint32_t r0, uint32_t r1, uint32_t r2, uint32_t r3) {
    asm volatile("stmatrix.sync.aligned.m8n8.x4.shared.b16 [%0], {%1,%2,%3,%4};"
                 ::"r"(a), "r"(r0), "r"(r1), "r"(r2), "r"(r3) : "memory");
}
__device__ __forceinline__ void mma16816(float* c, uint32_t a0, uint32_t a1, uint32_t a2, uint32_t a3, uint32_t b0, uint32_t b1) {
    asm volatile("mma.sync.aligned.m16n8k16.row.col.f32.bf16.bf16.f32 {%0,%1,%2,%3}, {%4,%5,%6,%7}, {%8,%9}, {%0,%1,%2,%3};"
                 : "+f"(c[0]), "+f"(c[1]), "+f"(c[2]), "+f"(c[3]) : "r"(a0), "r"(a1), "r"(a2), "r"(a3), "r"(b0), "r"(b1));
}
__device__ __forceinline__ void mma1688(float* c, uint32_t a0, uint32_t a1, uint32_t b0) {
    asm volatile("mma.sync.aligned.m16n8k8.row.col.f32.bf16.bf16.f32 {%0,%1,%2,%3}, {%4,%5}, {%6}, {%0,%1,%2,%3};"
                 : "+f"(c[0]), "+f"(c[1]), "+f"(c[2]), "+f"(c[3]) : "r"(a0), "r"(a1), "r"(b0));
}
__device__ __forceinline__ void sts128(uint32_t a, float x, float y, float z, float w) {
    asm volatile("st.shared.v4.f32 [%0], {%1,%2,%3,%4};" ::"r"(a), "f"(x), "f"(y), "f"(z), "f"(w) : "memory");
}
__device__ __forceinline__ void sts64(uint32_t a, float x, float y) {
    asm volatile("st.shared.v2.f32 [%0], {%1,%2};" ::"r"(a), "f"(x), "f"(y) : "memory");
}
__device__ __forceinline__ void sts32(uint32_t a, uint32_t x) { asm volatile("st.shared.b32 [%0], %1;" ::"r"(a), "r"(x) : "memory"); }
__device__ __forceinline__ void sts128u(uint32_t a, uint4 v) {
    asm volatile("st.shared.v4.b32 [%0], {%1,%2,%3,%4};" ::"r"(a), "r"(v.x), "r"(v.y), "r"(v.z), "r"(v.w) : "memory");
}
__device__ __forceinline__ float4 lds128(uint32_t a) {
    float4 v; asm volatile("ld.shared.v4.f32 {%0,%1,%2,%3}, [%4];" : "=f"(v.x), "=f"(v.y), "=f"(v.z), "=f"(v.w) : "r"(a) : "memory"); return v;
}
__device__ __forceinline__ uint4 lds128u(uint32_t a) {
    uint4 v; asm volatile("ld.shared.v4.b32 {%0,%1,%2,%3}, [%4];" : "=r"(v.x), "=r"(v.y), "=r"(v.z), "=r"(v.w) : "r"(a) : "memory"); return v;
}
__device__ __forceinline__ uint4 lds128v(uint32_t a) {
    uint4 v; asm volatile("ld.volatile.shared.v4.b32 {%0,%1,%2,%3}, [%4];" : "=r"(v.x), "=r"(v.y), "=r"(v.z), "=r"(v.w) : "r"(a) : "memory"); return v;
}
__device__ __forceinline__ void sts64u(uint32_t a, uint2 v) { asm volatile("st.shared.v2.b32 [%0], {%1,%2};" ::"r"(a), "r"(v.x), "r"(v.y) : "memory"); }
__device__ __forceinline__ uint2 lds64u(uint32_t a) {
    uint2 v; asm volatile("ld.shared.v2.b32 {%0,%1}, [%2];" : "=r"(v.x), "=r"(v.y) : "r"(a) : "memory"); return v;
}
__device__ __forceinline__ float2 lds64(uint32_t a) {
    float2 v; asm volatile("ld.shared.v2.f32 {%0,%1}, [%2];" : "=f"(v.x), "=f"(v.y) : "r"(a) : "memory"); return v;
}
__device__ __forceinline__ uint2 ldg_rlx64(const void* p) {
    uint2 v; asm volatile("ld.relaxed.gpu.global.v2.b32 {%0,%1}, [%2];" : "=r"(v.x), "=r"(v.y) : "l"(p) : "memory"); return v;
}
__device__ __forceinline__ uint4 ldg_rlx128(const void* p) {
    uint4 v; asm volatile("ld.relaxed.gpu.global.v4.b32 {%0,%1,%2,%3}, [%4];" : "=r"(v.x), "=r"(v.y), "=r"(v.z), "=r"(v.w) : "l"(p) : "memory"); return v;
}
__device__ __forceinline__ void stg_rlx64(void* p, uint32_t x, uint32_t y) {
    asm volatile("st.relaxed.gpu.global.v2.b32 [%0], {%1,%2};" ::"l"(p), "r"(x), "r"(y) : "memory");
}
__device__ __forceinline__ void stg_rlx128(void* p, uint32_t x, uint32_t y, uint32_t z, uint32_t w) {
    asm volatile("st.relaxed.gpu.global.v4.b32 [%0], {%1,%2,%3,%4};" ::"l"(p), "r"(x), "r"(y), "r"(z), "r"(w) : "memory");
}
__device__ __forceinline__ uint32_t ldg_rlx32(const void* p) {
    uint32_t v; asm volatile("ld.relaxed.gpu.global.b32 %0, [%1];" : "=r"(v) : "l"(p) : "memory"); return v;
}
__device__ __forceinline__ void stg128(void* p, uint32_t x, uint32_t y, uint32_t z, uint32_t w) {
    asm volatile("st.global.v4.b32 [%0], {%1,%2,%3,%4};" ::"l"(p), "r"(x), "r"(y), "r"(z), "r"(w) : "memory");
}
__device__ __forceinline__ uint32_t ld_acquire(const unsigned* p) {
    uint32_t v; asm volatile("ld.acquire.gpu.global.u32 %0, [%1];" : "=r"(v) : "l"(p) : "memory"); return v;
}
__device__ __forceinline__ void red_add_u32(unsigned* p, uint32_t v) {
    asm volatile("red.relaxed.gpu.global.add.u32 [%0], %1;" ::"l"(p), "r"(v) : "memory");
}
__device__ __forceinline__ void wait_counter(const unsigned* p, uint32_t target) {
    uint32_t n = 0;
    while (ld_acquire(p) < target) { if (++n > SPIN_LIMIT) __trap(); }
}

__device__ __forceinline__ void wg_fence() { asm volatile("wgmma.fence.sync.aligned;" ::: "memory"); }
__device__ __forceinline__ void wg_commit() { asm volatile("wgmma.commit_group.sync.aligned;" ::: "memory"); }
template <int N> __device__ __forceinline__ void wg_wait() { asm volatile("wgmma.wait_group.sync.aligned %0;" ::"n"(N) : "memory"); }
__host__ __device__ constexpr uint64_t mkdesc(uint32_t addr, uint32_t lbo, uint32_t sbo, uint32_t swz) {
    return (uint64_t)((addr & 0x3FFFF) >> 4) | ((uint64_t)(lbo >> 4) << 16) | ((uint64_t)(sbo >> 4) << 32) | ((uint64_t)swz << 62);
}
#define F4(d, o) "+f"(d[o]), "+f"(d[o + 1]), "+f"(d[o + 2]), "+f"(d[o + 3])
template <int SC> __device__ __forceinline__ void wg_rs32(float (&d)[16], const uint32_t (&a)[4], uint64_t db) {
    asm volatile("wgmma.mma_async.sync.aligned.m64n32k16.f32.bf16.bf16 "
                 "{%0,%1,%2,%3,%4,%5,%6,%7,%8,%9,%10,%11,%12,%13,%14,%15}, {%16,%17,%18,%19}, %20, %21, 1, 1, 0;"
                 : F4(d, 0), F4(d, 4), F4(d, 8), F4(d, 12)
                 : "r"(a[0]), "r"(a[1]), "r"(a[2]), "r"(a[3]), "l"(db), "n"(SC));
}
template <int SC> __device__ __forceinline__ void wg_rs40(float (&d)[20], const uint32_t (&a)[4], uint64_t db) {
    asm volatile("wgmma.mma_async.sync.aligned.m64n40k16.f32.bf16.bf16 "
                 "{%0,%1,%2,%3,%4,%5,%6,%7,%8,%9,%10,%11,%12,%13,%14,%15,%16,%17,%18,%19}, {%20,%21,%22,%23}, %24, %25, 1, 1, 0;"
                 : F4(d, 0), F4(d, 4), F4(d, 8), F4(d, 12), F4(d, 16)
                 : "r"(a[0]), "r"(a[1]), "r"(a[2]), "r"(a[3]), "l"(db), "n"(SC));
}
template <int SC> __device__ __forceinline__ void wg_ss40(float (&d)[20], uint64_t da, uint64_t db) {
    asm volatile("wgmma.mma_async.sync.aligned.m64n40k16.f32.bf16.bf16 "
                 "{%0,%1,%2,%3,%4,%5,%6,%7,%8,%9,%10,%11,%12,%13,%14,%15,%16,%17,%18,%19}, %20, %21, %22, 1, 1, 1, 0;"
                 : F4(d, 0), F4(d, 4), F4(d, 8), F4(d, 12), F4(d, 16)
                 : "l"(da), "l"(db), "n"(SC));
}
template <int SC> __device__ __forceinline__ void wg_ss8(float (&d)[4], uint64_t da, uint64_t db) {
    asm volatile("wgmma.mma_async.sync.aligned.m64n8k16.f32.bf16.bf16 {%0,%1,%2,%3}, %4, %5, %6, 1, 1, 1, 1;"
                 : F4(d, 0) : "l"(da), "l"(db), "n"(SC));
}

constexpr int DBG_N = 11;
#define LT(st, k, v) do {} while (0)
#define TSI(st) do {} while (0)
#define TS(k) do {} while (0)
#define TSV(k, v) do {} while (0)
#define TSDUMP() do {} while (0)
#define GT(k) do {} while (0)

__device__ __align__(256) uint4 g_fy[2048 * 128];

constexpr uint32_t FG_SIZE = 2 * 32768 + 36864;
constexpr uint32_t FT_F16 = 2 * FG_SIZE, FT_B1F = FT_F16 + 2048, FT_B1I = FT_B1F + 2048, FT_C = FT_B1I + 2048, FT_A8 = FT_C + 2048,
                   FT_TWC = FT_A8 + 512, FT_TWB = FT_TWC + 8192, FT_BAR = FT_TWB + 8192, FFT_SMEM = FT_BAR + 256;
struct FftMaps { CUtensorMap x, y, o, y2, wr, wi; const unsigned char* w[3]; };

__device__ __forceinline__ float2 wroot(int e) {
    float s, c; sincospif((float)(e & 2047) * (-1.f / 1024.f), &s, &c); return make_float2(c, s);
}
__device__ __forceinline__ uint4 afrag(float2 a, float2 b) {
    return make_uint4(pack_bf16(a.x, -a.y), pack_bf16(a.y, a.x), pack_bf16(b.x, -b.y), pack_bf16(b.y, b.x));
}
__device__ __forceinline__ uint4 conjfrag(uint4 v) { return make_uint4(v.x ^ 0x80000000u, v.y ^ 0x8000u, v.z ^ 0x80000000u, v.w ^ 0x8000u); }
__device__ __forceinline__ uint4 negfrag(uint4 v) { return make_uint4(v.x ^ 0x80008000u, v.y ^ 0x80008000u, v.z ^ 0x80008000u, v.w ^ 0x80008000u); }
__device__ __forceinline__ uint32_t comp(const uint4& v, int i) { return i == 0 ? v.x : i == 1 ? v.y : i == 2 ? v.z : v.w; }
__device__ __forceinline__ void setcomp(uint4& v, int i, uint32_t x) { if (i == 0) v.x = x; else if (i == 1) v.y = x; else if (i == 2) v.z = x; else v.w = x; }
__device__ __forceinline__ float2 cmul(float2 a, float2 b) { return make_float2(a.x * b.x - a.y * b.y, a.x * b.y + a.y * b.x); }
__device__ __forceinline__ float2 cmulc(float2 a, float2 b) { return make_float2(a.x * b.x + a.y * b.y, a.y * b.x - a.x * b.y); }

__device__ __forceinline__ uint32_t pack_h2(float2 a) { uint32_t r; asm("cvt.rn.f16x2.f32 %0, %1, %2;" : "=r"(r) : "f"(a.y), "f"(a.x)); return r; }
__device__ __forceinline__ float2 unpack_h2(uint32_t v) {
    float2 r; asm("{\n.reg .b16 l, h;\nmov.b32 {l, h}, %2;\ncvt.f32.f16 %0, l;\ncvt.f32.f16 %1, h;\n}" : "=f"(r.x), "=f"(r.y) : "r"(v)); return r;
}
__device__ __forceinline__ void fft_tables(uint32_t tb, int tid, int nthr) {
    for (int i = tid; i < 128; i += nthr) {
        const int lane = i & 31, q = i >> 5, g = lane >> 2, t = lane & 3, o = 8 * (q >> 1) + g, in = 8 * (q & 1) + 2 * t;
        sts128u(tb + FT_F16 + i * 16, afrag(wroot(128 * o * in), wroot(128 * o * (in + 1))));
        sts128u(tb + FT_B1F + i * 16, afrag(wroot(64 * (1 + 2 * o) * in), wroot(64 * (1 + 2 * o) * (in + 1))));
        sts128u(tb + FT_B1I + i * 16, afrag(wroot(-64 * o * (1 + 2 * in)), wroot(-64 * o * (3 + 2 * in))));
        uint4 v;
        for (int r = 0; r < 4; r++) {
            const float2 a = wroot(128 * (4 * r + t) * (4 * q + (g >> 1)));
            setcomp(v, r, (g & 1) ? pack_bf16(a.y, a.x) : pack_bf16(a.x, -a.y));
        }
        sts128u(tb + FT_C + i * 16, v);
        if (q == 0) sts128u(tb + FT_A8 + lane * 16, afrag(wroot(256 * g * 2 * t), wroot(256 * g * (2 * t + 1))));
    }
    for (int i = tid; i < 512; i += nthr) {
        const int lane = i & 31, r = (i >> 5) & 3, phi = 8 * (i >> 7) + (lane >> 2), c = 4 * r + (lane & 3);
        const float2 a = wroot(4 * c * phi), b = wroot(2 * (phi + 32 * c));
        constexpr float SC = 1.f / (2.f * 2048.f * 512.f);
        sts128(tb + FT_TWC + i * 16, a.x * SC, a.y * SC, b.x, b.y);
    }
    for (int i = tid; i < 512; i += nthr) {
        const int lane = i & 31, r = (i >> 5) & 3, fa = (i >> 7) & 1, hf = i >> 8, c = 8 * (lane & 1) + r;
        const int p0 = fa + 2 * (lane >> 2), p1 = p0 + 16, s0 = (hf && p0) ? 32 - p0 : p0, s1 = hf ? 32 - p1 : p1;
        sts128u(tb + FT_TWB + i * 16, make_uint4(pack_h2(wroot(4 * c * s0)), pack_h2(wroot(4 * (c + 4) * s0)),
                                                 pack_h2(wroot(4 * c * s1)), pack_h2(wroot(4 * (c + 4) * s1))));
    }
}

template <bool TW>
__device__ __forceinline__ void dft16(uint4 (&out)[4], const uint4 (&in)[4], const uint4 (&m)[4], const uint4 (&tw)[4]) {
#pragma unroll
    for (int i = 0; i < 4; i++)
#pragma unroll
        for (int mt = 0; mt < 2; mt++) {
            float c[4] = {0.f, 0.f, 0.f, 0.f};
            mma16816(c, m[2 * mt].x, m[2 * mt].y, m[2 * mt].z, m[2 * mt].w, comp(in[0], i), comp(in[1], i));
            mma16816(c, m[2 * mt + 1].x, m[2 * mt + 1].y, m[2 * mt + 1].z, m[2 * mt + 1].w, comp(in[2], i), comp(in[3], i));
            if (TW) {
                const float2 a = cmul(make_float2(c[0], c[2]), unpack_h2(comp(tw[i], 2 * mt))), b = cmul(make_float2(c[1], c[3]), unpack_h2(comp(tw[i], 2 * mt + 1)));
                setcomp(out[2 * mt], i, pack_bf16(a.x, a.y));
                setcomp(out[2 * mt + 1], i, pack_bf16(b.x, b.y));
            } else {
                setcomp(out[2 * mt], i, pack_bf16(c[0], c[2]));
                setcomp(out[2 * mt + 1], i, pack_bf16(c[1], c[3]));
            }
        }
}
__device__ __forceinline__ void tma_ld4(uint32_t dst, const CUtensorMap* m, int c0, int c1, uint32_t bar) {
    asm volatile("cp.async.bulk.tensor.4d.shared::cluster.global.mbarrier::complete_tx::bytes [%0], [%1, {%3, %4, %5, %5}], [%2];"
                 ::"r"(dst), "l"(m), "r"(bar), "r"(c0), "r"(c1), "r"(0) : "memory");
}
__device__ __forceinline__ void tma_st4(uint32_t src, const CUtensorMap* m, int c0, int c1) {
    asm volatile("cp.async.bulk.tensor.4d.global.shared::cta.bulk_group [%1, {%2, %3, %4, %4}], [%0];" ::"r"(src), "l"(m), "r"(c0), "r"(c1), "r"(0) : "memory");
}
__device__ __forceinline__ void tma_ld3(uint32_t dst, const CUtensorMap* m, int c0, int c1, uint32_t bar) {
    asm volatile("cp.async.bulk.tensor.3d.shared::cluster.global.mbarrier::complete_tx::bytes [%0], [%1, {%3, %4, %5}], [%2];"
                 ::"r"(dst), "l"(m), "r"(bar), "r"(c0), "r"(c1), "r"(0) : "memory");
}
__device__ __forceinline__ void tma_st3(uint32_t src, const CUtensorMap* m, int c0, int c1) {
    asm volatile("cp.async.bulk.tensor.3d.global.shared::cta.bulk_group [%1, {%2, %3, %4}], [%0];" ::"r"(src), "l"(m), "r"(c0), "r"(c1), "r"(0) : "memory");
}
__device__ __forceinline__ void bulk_commit() { asm volatile("cp.async.bulk.commit_group;" ::: "memory"); }
__device__ __forceinline__ void bulk_wait_read() { asm volatile("cp.async.bulk.wait_group.read 0;" ::: "memory"); }
__device__ __forceinline__ void bulk_wait_all() { asm volatile("cp.async.bulk.wait_group 0;" ::: "memory"); }

__device__ __forceinline__ float2 wroot_fast(int e) {
    float s, c; __sincosf((float)(((e + 1024) & 2047) - 1024) * (-3.14159265358979f / 1024.f), &s, &c); return make_float2(c, s);
}
template <bool INV, int NT>
__device__ __forceinline__ void fft_col(int s2, int t0, const CUtensorMap* src, const CUtensorMap* dst, uint32_t gb, uint32_t mb,
                                        int w, int lane, int bar) {
    const int g = lane >> 2, t = lane & 3;
    const bool lead = w == 4 && lane == 0;
    if (NT > 1 && lead)
        for (int i = 0; i < 2; i++) { mbar_expect_tx(mb + 8 * i, 32768); tma_ld4(gb + i * 32768, src, (t0 + i) * 64, s2, mb + 8 * i); }
    uint4 f[4], m[2][4];
#pragma unroll
    for (int i = 0; i < 4; i++) {
        const int o = 8 * (i >> 1) + g, in = 8 * (i & 1) + 2 * t, sg = INV ? -128 : 128;
        f[i] = afrag(wroot_fast(sg * o * in), wroot_fast(sg * o * (in + 1)));
#pragma unroll
        for (int q = 0; q < 2; q++) {
            const int z = 2 * w + q;
            m[q][i] = INV ? afrag(wroot_fast(-(8 * o + s2) * (z + 16 * in)), wroot_fast(-(8 * o + s2) * (z + 16 * in + 16)))
                          : afrag(wroot_fast((z + 16 * o) * (8 * in + s2)), wroot_fast((z + 16 * o) * (8 * in + 8 + s2)));
        }
    }
    const uint32_t r1 = (32 * w + 2 * t) * 128 + ((g ^ (2 * t)) << 4);
    const uint32_t w1 = (32 * w + g) * 128 + (((2 * t) ^ (((w & 3) << 1) | (g & 1))) << 4);
    const uint32_t r2 = (32 * t + 2 * w) * 128 + ((g ^ (2 * t)) << 4);
    const uint32_t w2 = (32 * w + g) * 128 + (((2 * t) ^ g) << 4);
    int bi = 0, ph = 0;
#pragma unroll 1
    for (int it = 0; it < NT; it++) {
        const uint32_t buf = gb + bi * 32768;
        mbar_wait(mb + 8 * bi, ph);
        uint4 in[2][4], out[4];
#pragma unroll
        for (int q = 0; q < 2; q++)
#pragma unroll
            for (int i = 0; i < 4; i++) in[q][i] = lds128u(buf + (r1 ^ ((i & 1) * 0x90)) + (i >> 1) * 1024 + q * 2048);
        __syncwarp();
#pragma unroll
        for (int q = 0; q < 2; q++) {
            if (INV) dft16<false>(out, in[q], m[q], f); else dft16<false>(out, in[q], f, f);
#pragma unroll
            for (int i = 0; i < 4; i++) sts128u(buf + (w1 ^ ((i & 1) << 4)) + (i >> 1) * 1024 + q * 2048, out[i]);
        }
        bar_sync(bar, 256);
#pragma unroll
        for (int q = 0; q < 2; q++)
#pragma unroll
            for (int i = 0; i < 4; i++) in[q][i] = lds128u(buf + (r2 ^ (q * 0x90)) + (i & 1) * 2048 + (i >> 1) * 16384);
        const int bn = bi == 0 ? 2 : bi - 1;
        if (lead && it < NT - 2) { bulk_wait_read(); mbar_expect_tx(mb + 8 * bn, 32768); tma_ld4(gb + bn * 32768, src, (t0 + it + 2) * 64, s2, mb + 8 * bn); }
        bar_sync(bar, 256);
#pragma unroll
        for (int q = 0; q < 2; q++) {
            if (INV) dft16<false>(out, in[q], f, f); else dft16<false>(out, in[q], m[q], f);
#pragma unroll
            for (int i = 0; i < 4; i++) sts128u(buf + (w2 ^ ((i & 1) << 4)) + (i >> 1) * 1024 + q * 2048, out[i]);
        }
        fence_async_smem();
        bar_sync(bar, 256);
        if (NT > 1 && lead) { tma_st4(buf, dst, (t0 + it) * 64, s2); bulk_commit(); }
        if (++bi == 3) { bi = 0; ph ^= 1; }
    }
    if (NT > 1 && lead) bulk_wait_read();
}

__device__ __forceinline__ float ldw(uint32_t a) {
    uint16_t v; asm volatile("ld.shared.u16 %0, [%1];" : "=h"(v) : "r"(a) : "memory");
    return __uint_as_float((uint32_t)v << 16);
}
__device__ __forceinline__ void fft_mid(int grp, const FftMaps& fm, uint32_t tb,
                                        uint32_t gb, uint32_t mb, uint32_t& cnt, int w, int lane, int bar) {
    const int g = lane >> 2, t = lane & 3;
    const bool lead = w == 4 && lane == 0;
    const uint32_t wb = gb + 65536;
#define MID_LOAD(k, c)                                                                                                  \
    { mbar_expect_tx(mb + 8 * ((c) & 1), 32768);                                                                        \
      tma_ld3(gb + ((c) & 1) * 32768, &fm.y2, 0, (k) * 8, mb + 8 * ((c) & 1));                                          \
      tma_ld3(gb + ((c) & 1) * 32768 + 16384, &fm.y2, 0, ((256 - (k)) & 255) * 8, mb + 8 * ((c) & 1)); }
#define MID_LOADW(k)                                                                                                    \
    { mbar_expect_tx(mb + 16, 36864);                                                                                   \
      tma_ld3(wb, &fm.wr, (k) * 513 & ~7, 0, mb + 16); tma_ld3(wb + 9216, &fm.wi, (k) * 513 & ~7, 0, mb + 16);          \
      tma_ld3(wb + 18432, &fm.wr, ((256 - (k)) & 255) * 513 & ~7, 0, mb + 16); tma_ld3(wb + 27648, &fm.wi, ((256 - (k)) & 255) * 513 & ~7, 0, mb + 16); }
    if (lead) { MID_LOAD(grp, cnt); MID_LOADW(grp); }
    const int hB = w >> 2, faB = (w >> 1) & 1, xB = faB;
    const int phi = 8 * (w & 3) + g;
    const uint32_t rA = (8 * w + 2 * t) * 128 + ((g ^ (2 * t)) << 4);
    const uint32_t wA = (8 * w + g) * 128 + (((2 * t) ^ ((g & 1) | ((w & 3) << 1))) << 4);
    const uint32_t oB = (w >> 1) * 8192 + (w & 1) * 512;
    const uint32_t rB = oB + (8 * t + (g >> 2)) * 128 + (((g & 3) ^ ((g >> 2) | (t << 1)) ^ xB) << 4);
    const uint32_t wB = oB + (8 * (g >> 1) + (t >> 1)) * 128 + (((((g & 1) << 2) | (2 * (t & 1))) ^ ((t >> 1) | ((g >> 1) << 1)) ^ xB) << 4);
    const uint32_t wBi = oB + (8 * (g >> 1) + (t >> 1)) * 128 + (((((g & 1) << 2) | (2 * (t & 1))) ^ ((t >> 1) | ((w & 1) << 2))) << 4);
    const int hC = (lane >> 3) & 1, pr = 8 * (w & 3) + (lane & 7), pc = hC ? (32 - pr) & 31 : pr;
    const uint32_t aC = hC * 16384 + (pc & 1) * 8192 + (pc >> 2) * 1024 + (((((pc & 2) << 1) | (lane >> 4)) ^ (((pc >> 2) & 3) << 1) ^ (pc & 1)) << 4);
    const uint32_t g0 = wb + (t >> 1) * 144 + (32 * (t & 1) + phi) * 2, g1 = wb + 18432 + (7 - (t >> 1)) * 144 + (64 - 32 * (t & 1) - phi) * 2;
    const uint32_t wAo = (8 * w + g) * 128 + (((2 * t) ^ g) << 4);
    uint32_t wph = 0;
#pragma unroll 1
    for (int k1 = grp; k1 < 129; k1 += 8, cnt++, wph ^= 1) {
        const uint32_t buf = gb + (cnt & 1) * 32768;
        uint4 in[2][4], m[4], out[4];
        m[0] = m[1] = m[2] = lds128u(tb + FT_A8 + lane * 16);
        m[3] = negfrag(m[0]);
        mbar_wait(mb + 8 * (cnt & 1), (cnt >> 1) & 1);
#pragma unroll
        for (int q = 0; q < 2; q++)
#pragma unroll
            for (int i = 0; i < 4; i++) in[q][i] = lds128u(buf + (rA ^ ((i & 1) * 0x90)) + (i >> 1) * 8192 + q * 16384);
        __syncwarp();
#pragma unroll
        for (int q = 0; q < 2; q++) {
            dft16<false>(out, in[q], m, m);
#pragma unroll
            for (int i = 0; i < 4; i++) sts128u(buf + (wA ^ (((i ^ (i >> 1)) & 1) << 4)) + (i >> 1) * 8192 + q * 16384, out[i]);
        }
        {
            uint4 tw[4];
#pragma unroll
            for (int i = 0; i < 4; i++) {
                m[i] = lds128u(tb + (faB ? FT_B1F : FT_F16) + i * 512 + lane * 16);
                if (hB) { m[i].y ^= 0x80008000u; m[i].w ^= 0x80008000u; }
                tw[i] = lds128u(tb + FT_TWB + (w >> 1) * 2048 + i * 512 + lane * 16);
            }
            bar_sync(bar, 256);
#pragma unroll
            for (int q = 0; q < 2; q++)
#pragma unroll
                for (int i = 0; i < 4; i++) in[q][i] = lds128u(buf + (rB ^ ((i & 1) << 6)) + (i >> 1) * 4096 + q * 256);
            __syncwarp();
#pragma unroll
            for (int q = 0; q < 2; q++) {
                dft16<true>(out, in[q], m, tw);
#pragma unroll
                for (int i = 0; i < 4; i++) sts128u(buf + (wB ^ ((i & 1) << 4)) + (i >> 1) * 4096 + q * 256, out[i]);
            }
        }
        {
            const uint32_t cjm = (g & 1) ? 0x8000u : 0x80000000u;
            float4 tw[4];
#pragma unroll
            for (int i = 0; i < 4; i++) { m[i] = lds128u(tb + FT_C + i * 512 + lane * 16); tw[i] = lds128(tb + FT_TWC + ((w & 3) * 4 + i) * 512 + lane * 16); }
            if (lead && k1 + 8 < 129) { bulk_wait_read(); MID_LOAD(k1 + 8, cnt + 1); }
            __syncwarp();
            mbar_wait(mb + 16, wph);
            const uint32_t o0 = (k1 & 7) * 2, o1 = (-k1 & 7) * 2;
            if (w == 1 && lane < 16) {
                const int k2 = lane & 7, k2p = k1 ? 7 - k2 : (8 - k2) & 7;
                const uint32_t p0 = wb + (lane >> 3) * 9216 + k2 * 1152 + o0, p1 = wb + 18432 + (lane >> 3) * 9216 + k2p * 1152 + o1;
                const float sg = lane < 8 ? 0.5f : -0.5f;
                const uint32_t v = pack_bf16(0.5f * ldw(p0) + sg * ldw(p1), 0.5f * ldw(p1 + 1136) + sg * ldw(p0 + 1136));
                asm volatile("st.shared.u16 [%0], %1;" ::"r"(p0), "h"((uint16_t)v) : "memory");
                asm volatile("st.shared.u16 [%0], %1;" ::"r"(p1 + 1136), "h"((uint16_t)(v >> 16)) : "memory");
                fence_async_smem();
            }
            bar_sync(bar, 256);
#define FFT_CU 1
            constexpr int CU = FFT_CU;
#pragma unroll CU
            for (int q = 0; q < 4; q++) {
                const int k2 = 4 * (w >> 2) + q, k2p = k1 ? 7 - k2 : (8 - k2) & 7, kr = hC ? k2p : k2;
                const uint32_t a0 = buf + (aC ^ ((kr & 1) << 4)) + kr * 128;
                const uint32_t r0 = g0 + k2 * 1152 + o0, r1 = g1 + k2p * 1152 + o1;
                uint32_t x[4], y[4];
                ldsm4(x, a0); ldsm4(y, a0 ^ 32);
                float c[4][4];
#pragma unroll
                for (int i = 0; i < 4; i++) { c[i][0] = c[i][1] = c[i][2] = c[i][3] = 0.f; mma16816(c[i], x[0], x[1], x[2], x[3], m[i].x, m[i].y); }
#pragma unroll
                for (int i = 0; i < 4; i++) mma16816(c[i], y[0], y[1], y[2], y[3], m[i].z, m[i].w);
#pragma unroll
                for (int i = 0; i < 4; i++) {
                    const float2 ga = make_float2(ldw(r0 + i * 288), ldw(r0 + 9216 + i * 288));
                    const float2 gc = make_float2(ldw(r1 - i * 288), ldw(r1 + 9216 - i * 288));
                    const float tc = tw[i].z, ts = tw[i].w;
                    const float* z = c[i];
                    const float2 S = make_float2(ga.x + gc.x, ga.y - gc.y), D = make_float2(ga.x - gc.x, ga.y + gc.y);
                    const float2 u = make_float2(ts * z[0] - tc * z[3], ts * z[1] + tc * z[2]), v = make_float2(ts * z[2] - tc * z[1], ts * z[3] + tc * z[0]);
                    uint32_t* o = (i < 2 ? x : y) + 2 * (i & 1);
                    o[0] = pack_bf16(fmaf(S.x, z[0], fmaf(-S.y, z[1], fmaf(D.x, u.x, -D.y * u.y))), fmaf(S.x, z[1], fmaf(S.y, z[0], fmaf(D.x, u.y, D.y * u.x))));
                    o[1] = pack_bf16(fmaf(S.x, z[2], fmaf(-S.y, z[3], fmaf(-D.x, v.x, D.y * v.y))), fmaf(S.x, z[3], fmaf(S.y, z[2], fmaf(-D.x, v.y, -D.y * v.x))));
                }
#pragma unroll
                for (int i = 0; i < 4; i++) { c[i][0] = c[i][1] = c[i][2] = c[i][3] = 0.f; mma16816(c[i], x[0], x[1], x[2], x[3], m[i].x ^ cjm, m[i].y ^ cjm); }
#pragma unroll
                for (int i = 0; i < 4; i++) mma16816(c[i], y[0], y[1], y[2], y[3], m[i].z ^ cjm, m[i].w ^ cjm);
#pragma unroll
                for (int i = 0; i < 4; i++) {
                    uint32_t* o = (i < 2 ? x : y) + 2 * (i & 1);
                    o[0] = pack_bf16(c[i][0] * tw[i].x + c[i][1] * tw[i].y, c[i][1] * tw[i].x - c[i][0] * tw[i].y);
                    o[1] = pack_bf16(c[i][2] * tw[i].x + c[i][3] * tw[i].y, c[i][2] * tw[i].y - c[i][3] * tw[i].x);
                }
                stsm4(a0, x[0], x[1], x[2], x[3]);
                stsm4(a0 ^ 32, y[0], y[1], y[2], y[3]);
            }
        }
#pragma unroll
        for (int i = 0; i < 4; i++) { m[i] = lds128u(tb + (faB ? FT_B1I : FT_F16) + i * 512 + lane * 16); if (!faB) m[i] = conjfrag(m[i]); }
        bar_sync(bar, 256);
        if (lead && k1 + 8 < 129) MID_LOADW(k1 + 8);
        __syncwarp();
#pragma unroll
        for (int q = 0; q < 2; q++)
#pragma unroll
            for (int i = 0; i < 4; i++) in[q][i] = lds128u(buf + (rB ^ ((i & 1) << 6)) + (i >> 1) * 4096 + q * 256);
        __syncwarp();
#pragma unroll
        for (int q = 0; q < 2; q++) {
            dft16<false>(out, in[q], m, m);
#pragma unroll
            for (int i = 0; i < 4; i++) sts128u(buf + (wBi ^ ((i & 1) << 4) ^ (q << 5)) + (i >> 1) * 4096 + q * 256, out[i]);
        }
        m[0] = m[1] = m[2] = conjfrag(lds128u(tb + FT_A8 + lane * 16));
        m[3] = negfrag(m[0]);
        bar_sync(bar, 256);
#pragma unroll
        for (int q = 0; q < 2; q++)
#pragma unroll
            for (int i = 0; i < 4; i++) in[q][i] = lds128u(buf + (rA ^ ((i & 1) * 0x90)) + (i >> 1) * 8192 + q * 16384);
        __syncwarp();
#pragma unroll
        for (int q = 0; q < 2; q++) {
            dft16<false>(out, in[q], m, m);
#pragma unroll
            for (int i = 0; i < 4; i++) sts128u(buf + (wAo ^ ((i & 1) << 4)) + (i >> 1) * 8192 + q * 16384, out[i]);
        }
        fence_async_smem();
        bar_sync(bar, 256);
        if (lead) {
            tma_st3(buf, &fm.y2, 0, k1 * 8);
            if (k1 & 127) tma_st3(buf + 16384, &fm.y2, 0, (256 - k1) * 8);
            bulk_commit();
        }
    }
    if (lead) bulk_wait_all();
}

__device__ __align__(128) unsigned g_start;
__device__ __align__(128) unsigned g_fbar;
__device__ __align__(128) unsigned g_end;
__device__ __forceinline__ unsigned gbar_arrive(unsigned* c, unsigned inc, unsigned total, int lane) {
    unsigned v = 0;
    if (lane == 0) { asm volatile("fence.proxy.async;" ::: "memory"); fence_gpu(); v = atomicAdd(c, inc); }
    return (__shfl_sync(~0u, v, 0) & ~(total - 1)) + total;
}
__device__ __forceinline__ void gbar_wait(unsigned* c, unsigned target, unsigned ns) {
    uint32_t n = 0;
    while (__any_sync(~0u, (int)(ld_acquire(c) - target) < 0)) { if (ns) __nanosleep(ns); if (++n > SPIN_LIMIT) __trap(); }
    asm volatile("fence.proxy.async;" ::: "memory");
}
__device__ __forceinline__ void fft_rest(int cta, const FftMaps& fm, uint32_t sb, uint32_t opt) {
    const int hi = __shfl_sync(~0u, threadIdx.x >> 8, 0), w = __shfl_sync(~0u, (threadIdx.x >> 5) & 7, 0), lane = threadIdx.x & 31;
    unsigned target = 0;
    if (w == 4) target = gbar_arrive(&g_start, 16, 256, lane);
    if (threadIdx.x < 32) mbar_init(sb + FT_BAR + 8 * threadIdx.x, 1);
    fft_tables(sb, threadIdx.x, 512);
    fence_async_smem();
    __syncthreads();
    const int grp = cta * 2 + hi, bar = 1 + hi;
    const uint32_t gb = sb + hi * FG_SIZE, mb = sb + FT_BAR + hi * 128;
    uint32_t cnt = 0;
    if (w == 4) gbar_wait(&g_start, target, 200);
    if (w == 4) {
        const unsigned char* p = fm.w[2] + (size_t)(lane * 8 + grp) * 16384;
        asm volatile("cp.async.bulk.prefetch.L2.global [%0], %1;" ::"l"(p), "r"(16384) : "memory");
    }
    if (w == 4) {
        const unsigned char* p = fm.w[hi] + (size_t)(cta * 32 + lane) * 16416;
        asm volatile("cp.async.bulk.prefetch.L2.global [%0], %1;" ::"l"(p), "r"(16416) : "memory");
    }
    GT(1);
    fft_mid(grp, fm, sb, gb, mb, cnt, w, lane, bar);
    if (w == 4) gbar_wait(&g_fbar, gbar_arrive(&g_fbar, 1, 8, lane), 200);
    GT(2);
    fft_col<true, 16>(grp, 0, &fm.y, &fm.o, gb, mb + 64, w, lane, bar);
}

__device__ __align__(256) uint4 g_kvq[4 * 32 * 3 * 8 * 2 * 32];
__device__ __align__(256) uint2 g_alpha[2 * 32 * 3 * 8 * 2 * 32];
__device__ __align__(256) uint4 g_red[5 * 32768 / 16];
__device__ __align__(256) uint4 g_stamp[32];
__device__ __align__(256) uint4 g_qst[128 * 2];
__device__ __align__(256) bf16 g_ox[2048 * 4096];
struct Tune { uint32_t d_alpha, d_r, opt, d_q, d_v, spread, extra; };
#define OP_SPLIT 1
#define X_SEQ 24
#define QKW_POS 0
#define XO_POS 0
#define V_SEQ 28
#define X_HALF 0
#define V_KEEP 0
#define STAMP_V 1
#define EXP 0
#define FIN_BAR B_SRDY
#define V_LATE 0
#define R_SPLIT 1
#define PV_MODE 0
#define OPD_EARLY 1
constexpr int RA = 2;

constexpr uint32_t SM_BASE = 1024;
constexpr uint32_t O_WO = 0;
constexpr uint32_t O_WV = 65536;
constexpr uint32_t O_XB = 131072;
constexpr uint32_t O_MEM = O_XB + 16384;
constexpr uint32_t O_RECV = O_XB + 40960;
constexpr uint32_t O_KVQ = O_RECV + 12288;
constexpr uint32_t O_STG = O_KVQ + 18432;
constexpr uint32_t O_S = O_STG + 8192;
constexpr uint32_t O_P = O_S + 10240;
constexpr uint32_t O_O = O_P + 1536;
constexpr uint32_t O_DBG = O_O + 2048;
constexpr uint32_t O_F1 = 196608;
constexpr uint32_t O_VM = O_F1 + 32768;
constexpr uint32_t O_BAR = 232448 - 512;
constexpr uint32_t MAIN_SMEM = 232448;
static_assert(O_DBG + (DBG_TIMING ? (4 * DBG_N + 1) * 96 : 0) <= O_VM && FFT_SMEM <= MAIN_SMEM && O_VM + 2048 <= O_BAR, "smem");
constexpr int G_ST = 6;
enum { B_W = 0, B_WO = B_W + 12, B_F1, B_XP, B_XFULL, B_RFULL, B_AFULL, B_KVFULL, B_XF1, B_QST, B_RECV, B_GF = B_RECV + 6,
       B_QDONE = B_GF + G_ST, B_KDONE, B_XEMPTY, B_VA, B_X0, B_SRDY, B_OPDONE, B_QX, B_GE, B_XPE = B_GE + G_ST, B_QKW, B_MEM, B_COUNT };

constexpr float SM_SCALE_LOG2 = 0.08838834764831845f * 1.4426950408889634f;
constexpr float MASK_VAL = -1.0e9f / 0.08838834764831845f;

__device__ __forceinline__ uint32_t red_grp(int grp) { return (uint32_t)((grp >> 1) * 1024 + (grp & 1) * 256); }
__host__ __device__ constexpr uint32_t kb_off(int kb) { return (uint32_t)((kb >> 2) * 20480 + (kb & 3) * 1024); }
__host__ __device__ constexpr uint64_t xdesc(int ks) { return mkdesc(SM_BASE + O_XB + kb_off(ks >> 2) + (ks & 3) * 32, 16, 4096, 1); }

__device__ __forceinline__ void x_split(const float* d, uint32_t (&sn)[4], uint32_t (&kp)[4], int kh) {
#pragma unroll
    for (int i = 0; i < 4; i++) {
        const uint32_t lo = pack_bf16(d[2 * i], d[2 * i + 1]), hi = pack_bf16(d[8 + 2 * i], d[8 + 2 * i + 1]);
        sn[i] = kh ? lo : hi; kp[i] = kh ? hi : lo;
    }
}
__device__ __forceinline__ void x_send(int R, const uint32_t (&sn)[4], int sg, int tid, uint32_t sb, uint32_t mate) {
    const uint32_t par = sg & 1;
    const uint32_t bar = O_BAR + 8 * (B_RECV + R * 2) + 8 * par;
    if (tid == 0) mbar_expect_tx(sb + bar, 2048);
    asm volatile("st.async.shared::cluster.mbarrier::complete_tx::bytes.v4.b32 [%0], {%1,%2,%3,%4}, [%5];"
                 ::"r"(mate + O_RECV + (par * 3 + R) * 2048 + tid * 16), "r"(sn[0]), "r"(sn[1]), "r"(sn[2]), "r"(sn[3]), "r"(mate + bar) : "memory");
}
__device__ __forceinline__ void x_wait(int R, int sg, uint32_t sb) {
    mbar_wait_cluster(sb + O_BAR + 8 * (B_RECV + R * 2) + 8 * (sg & 1), (sg >> 1) & 1);
}
template <int R>
__device__ __forceinline__ void x_finish(const uint32_t (&kp)[4], int sg, int h, int mt, int kh, int tid, uint32_t sb) {
    const uint4 r = lds128u(sb + O_RECV + ((sg & 1) * 3 + R) * 2048 + tid * 16);
    uint32_t u0 = add_bf16x2(kp[0], r.x), u1 = add_bf16x2(kp[1], r.y), u2 = add_bf16x2(kp[2], r.z), u3 = add_bf16x2(kp[3], r.w);
    const uint32_t tag = ((sg >> 2) & 1) ^ 1;
    uint4* const hb = &g_kvq[((sg & 3) * 32 + h) * (3 * 512)];
    if (R < 2) {
        const uint32_t m = (tid & 7) ? ~0u : ~1u, t = tag & ~m;
        uint32_t* p = (uint32_t*)hb + (R == 0 ? (kh * 16 + mt) * 64 : 2048 + (mt * 2 + kh) * 128) + (tid & 31);
        asm volatile("{\n.reg .pred p;\nsetp.lt.s32 p, %5, 64;\n@p st.relaxed.gpu.global.b32 [%0], %1;\n@p st.relaxed.gpu.global.b32 [%0+128], %2;\n"
                     "@p st.relaxed.gpu.global.b32 [%0+%6], %3;\n@p st.relaxed.gpu.global.b32 [%0+%7], %4;\n}"
                     ::"l"(p), "r"((u0 & m) | t), "r"((u1 & m) | t), "r"((u2 & m) | t), "r"((u3 & m) | t), "r"(sg),
                       "n"(R == 0 ? 2048 : 256), "n"(R == 0 ? 2176 : 384) : "memory");
    } else {
        asm volatile("{\n.reg .pred p;\nsetp.lt.s32 p, %5, 64;\n@p st.relaxed.gpu.global.v4.b32 [%0], {%1,%2,%3,%4};\n}"
                     ::"l"(hb + R * 512 + (mt * 2 + kh) * 32 + (tid & 31)), "r"((u0 & ~1u) | tag), "r"(u1), "r"(u2), "r"(u3), "r"(sg) : "memory");
    }
}
__device__ __forceinline__ uint32_t tags4(const uint32_t (&r)[4], uint32_t tag) { return orx(orx(orx2(r[0], r[1], tag), r[2], tag), r[3], tag); }

__device__ __forceinline__ uint32_t convert_mem(const unsigned char* redp, int s, int kh, int jj, int w, int lane, uint32_t sb, uint32_t& sf) {
    const uint32_t off = red_grp(jj * 16 + w * 4 + (lane >> 3)), o16 = off + (lane & 7) * 16, o8 = off + 512 + ((lane >> 3) & 1) * 64 + (lane & 7) * 8;
    uint32_t ma = sb + O_MEM + jj * 20480 + (lane >> 4) * 1024 + (lane & 7) * 128 + (((2 * w + ((lane >> 3) & 1)) ^ (lane & 7)) << 4);
    uint32_t a16 = sb + O_STG + o16, a8 = sb + O_STG + o8;
    const uint32_t target = (s & 4) ? 0x42C00000u : 0x42000000u;
    uint32_t n = 0;
    bool redo;
    KEEP2(ma, a16); KEEP2(a8, target);
#pragma unroll 1
    do {
        asm volatile("" : "+r"(n));
        if (n) {
            const unsigned char* pg = redp + (s & 3) * 32768 + __shfl_sync(~0u, kh, 0) * 16384;
            const uint4 x = ldg_rlx128(pg + o16), y = ldg_rlx128(pg + o16 + 128);
            const uint2 z = ldg_rlx64(pg + o8);
            sts128u(a16, x); sts128u(a16 + 128, y); sts64u(a8, z);
            if (n > SPIN_LIMIT) __trap();
        }
        n++;
        mbar_wait(sb + O_BAR + 8 * (R_SPLIT && jj ? B_XF1 : B_RFULL), s & 1);
        const uint4 ra = lds128u(a16), rb = lds128u(a16 + 128);
        const uint2 rc = lds64u(a8);
        stsm4t(ma, ra.x, ra.y, ra.z, __byte_perm(ra.w, rc.x, 0x5410));
        stsm4t(ma + 2048, rb.x, rb.y, rb.z, __byte_perm(rb.w, rc.x, 0x7610));
        redo = __any_sync(~0u, orx(orx2(ra.w, rb.w, target), rc.y, target) > 0xffffu);
    } while (redo);
    if (lane == 0) mbar_arrive(sb + O_BAR + 8 * B_MEM);
    fence_async_smem();
    __syncwarp();
    if (lane == 0) mbar_arrive(sb + O_BAR + 8 * B_QKW);
    return n - 1;
}

#define F16(d, o) F4(d, o), F4(d, o + 4), F4(d, o + 8), F4(d, o + 12)
__device__ __forceinline__ void wg_ss128(float (&d)[64], uint64_t da, uint64_t db, int sc) {
    asm volatile("{\n.reg .pred p;\nsetp.ne.b32 p, %66, 0;\nwgmma.mma_async.sync.aligned.m64n128k16.f32.bf16.bf16 "
                 "{%0,%1,%2,%3,%4,%5,%6,%7,%8,%9,%10,%11,%12,%13,%14,%15,%16,%17,%18,%19,%20,%21,%22,%23,%24,%25,%26,%27,%28,%29,%30,%31,"
                 "%32,%33,%34,%35,%36,%37,%38,%39,%40,%41,%42,%43,%44,%45,%46,%47,%48,%49,%50,%51,%52,%53,%54,%55,%56,%57,%58,%59,%60,%61,%62,%63}, "
                 "%64, %65, p, 1, 1, 1, 1;\n}"
                 : F16(d, 0), F16(d, 16), F16(d, 32), F16(d, 48) : "l"(da), "l"(db), "r"(sc));
}
__device__ __forceinline__ void stg_rlx32(void* p, uint32_t v) { asm volatile("st.relaxed.gpu.global.u32 [%0], %1;" ::"l"(p), "r"(v) : "memory"); }

__global__ void __cluster_dims__(2, 1, 1) __launch_bounds__(512, 1)
rmt_main(const __grid_constant__ CUtensorMap tm_x, const __grid_constant__ CUtensorMap tm_wq, const __grid_constant__ CUtensorMap tm_wk,
         const __grid_constant__ CUtensorMap tm_wv, const __grid_constant__ CUtensorMap tm_wo, const bf16* __restrict__ mem0,
         const Tune tn, const __grid_constant__ FftMaps fm, const __grid_constant__ CUtensorMap tm_o,
         const __grid_constant__ CUtensorMap tm_w2, bf16* __restrict__ out) {
    extern __shared__ __align__(1024) unsigned char smem_raw[];
    const uint32_t sb = smem_u32(smem_raw);
    if ((sb & 0x3FFFF) != SM_BASE) __trap();
    GT(6);
    const int cid = blockIdx.x >> 1, kh = blockIdx.x & 1;
    const int tpc = cid < 4 ? 62 + cid : cid - 4;
    int h, nh;
    if (tpc < 32) { h = (tpc >> 4) * 8 + (tpc & 7); nh = (tpc >> 3) & 1; }
    else if (tpc < 60) { int u = tpc - 32, r = u % 14; h = 16 + (u / 14) * 7 + r % 7; nh = r / 7; }
    else if (tpc < 62) { GT(0); fft_rest((tpc - 60) * 2 + kh, fm, sb, tn.opt); GT(3); return; }
    else { h = 30 + ((tpc - 62) >> 1); nh = tpc & 1; }
    const int j = nh * 2 + kh, role = h * 4 + j;
    const int wgi = __shfl_sync(~0u, threadIdx.x >> 7, 0);
    const int w = __shfl_sync(~0u, (threadIdx.x >> 5) & 3, 0);
    const int tid = threadIdx.x & 127, lane = tid & 31;
#define PIN_IDS() const int tid = __shfl_sync(~0u, threadIdx.x & 127, threadIdx.x & 31), lane = tid & 31
#define OPAQUE_IDS() int tid_ = tid; asm volatile("" : "+r"(tid_)); const int tid = tid_, lane = tid_ & 31; (void)lane
    unsigned char* const redp = (unsigned char*)(((uintptr_t)g_red + 32767) & ~(uintptr_t)32767);
    const uint32_t bars = sb + O_BAR;

    if (threadIdx.x < B_COUNT) {
        const int i = threadIdx.x;
        mbar_init(bars + 8 * i, i == B_XFULL && !X_HALF ? 2 : i < B_QDONE ? 1 : i < B_GE ? 4 : i < B_XPE ? 8 : i < B_QKW ? 12 : 16);
        asm volatile("fence.mbarrier_init.release.cluster;" ::: "memory");
        fence_async_smem();
    } else if (threadIdx.x >= 64 && threadIdx.x < 71) {
        const int i = threadIdx.x - 64;
        const CUtensorMap* m = i == 0 ? &tm_wk : i == 1 ? &tm_wq : i == 2 ? &fm.x : i == 3 ? &tm_x : i == 4 ? &tm_wv : i == 5 ? &tm_wo : &fm.y;
        asm volatile("prefetch.tensormap [%0];" ::"l"(m) : "memory");
    }
    __syncthreads();
    const int wc0 = h * 128 + nh * 64;
#define W_LOAD(i)                                                                                                     \
    if (lane == 0) {                                                                                                  \
        mbar_expect_tx(bars + 8 * (B_W + (i)), 16384);                                                                \
        tma2d(sb + ((i) < 4 ? O_XB : (i) < 8 ? O_WO : O_WV) + ((i) & 3) * 16384, (i) < 4 ? &tm_wk : (i) < 8 ? &tm_wq : &tm_wv, \
              wc0, kh * 512 + ((i) & 3) * 128, bars + 8 * (B_W + (i)));                                               \
    }
#define X_LOAD(dst, sg, u, bar) tma4d(sb + (dst), &tm_x, kh * 8 + (u) * 4, ((sg) & 63) * 4, bars + 8 * (bar))
#define X_REFILL(sg, u) { const int b_ = (X_HALF && (u)) ? B_XF1 : B_XFULL; if (EXP & 1) mbar_arrive(bars + 8 * b_); else { mbar_expect_tx(bars + 8 * b_, 16384); X_LOAD(O_XB + (u) * 20480, sg, u, b_); } }
    const int depth = (tn.opt >> 8) & 15, nearly = 8 + ((tn.opt >> 4) & 7);
    if (wgi == 0 && w == 3) {
        if (lane == 0) {
            mbar_expect_tx(bars + 8 * B_F1, 32768);
            tma_ld4(sb + O_F1, &fm.x, (role & 15) * 64, role >> 4, bars + 8 * B_F1);
        }
#pragma unroll 1
        for (int i = 0; i < nearly; i++) {
            if (i == depth - 2) mbar_wait(bars + 8 * B_F1, 0);
            if (i >= depth) mbar_wait(bars + 8 * (B_W + i - depth), 0);
            W_LOAD(i);
        }
    } else if (wgi == 1 && w == 2 && lane == 0 && role < 4 * (RA + 3)) tma4d_prefetch(&tm_x, j * 4, h * 4);
    GT(7);
    uint32_t mate;
    asm volatile("mapa.shared::cluster.u32 %0, %1, %2;" : "=r"(mate) : "r"(sb), "r"(kh ^ 1));
    if (wgi >= 2) fft_col<false, 1>(role >> 4, role & 15, &fm.x, &fm.y, sb + O_F1, bars + 8 * B_F1, (wgi - 2) * 4 + w, lane, 6);

    if (wgi < 2) {
        asm volatile("setmaxnreg.inc.sync.aligned.u32 176;");
        PIN_IDS();
        uint32_t a[32][4], sf = 0;
        {
            const uint32_t stage = sb + (wgi == 0 ? O_WO : O_XB);
            const uint32_t ad = stage + (((lane >> 4) & 1) * 8 + (lane & 7)) * 128 + (((2 * w + ((lane >> 3) & 1)) ^ (lane & 7)) << 4);
#pragma unroll
            for (int i = 0; i < 4; i++) {
                mbar_wait(bars + 8 * (B_W + 4 * (wgi ^ 1) + i), 0);
#pragma unroll
                for (int ks = 0; ks < 8; ks++) ldsm4t(a[i * 8 + ks], ad + (i * 8 + ks) * 2048);
            }
#pragma unroll
            for (int ks = 0; ks < 32; ks += 2) KEEP2(a[ks][0], a[ks + 1][0]);
            SCHED_FENCE();
            if (lane == 0) mbar_arrive(bars + 8 * (B_QDONE + wgi));
            if (wgi == 0) GT(10); else GT(11);
        }
        asm volatile("barrier.cluster.arrive.relaxed.aligned;" ::: "memory");
        asm volatile("barrier.cluster.wait.acquire.aligned;" ::: "memory");
        uint32_t kp[4];
#define X_PASS(d, dofs)                                                                                    \
        wg_fence();                                                                                        \
        _Pragma("unroll") for (int ks = 0; ks < 32; ks++) { if (ks == 0) wg_rs32<0>(d, a[ks], xdesc(ks) + (dofs)); else wg_rs32<1>(d, a[ks], xdesc(ks) - (ks >> 4) * 256 + (dofs)); } \
        wg_commit();                                                                                       \
        wg_wait<0>();
#define X_FINISH(sg) { if (wgi == 0) x_finish<0>(kp, sg, h, nh * 4 + w, kh, tid, sb); else x_finish<1>(kp, sg, h, nh * 4 + w, kh, tid, sb); }
        mbar_wait(bars + 8 * B_XP, 0);
        if (wgi == 0) GT(8);
#pragma unroll 1
        for (int sg = 0; sg < RA; sg++) {
            float d[16]; uint32_t sn[4];
            X_PASS(d, sg * 2048 - (int)((O_XB - O_WO) >> 4));
            if (sg > 0) {
                if (lane == 0) mbar_arrive(bars + 8 * B_XPE);
                x_wait(wgi, sg - 1, sb); X_FINISH(sg - 1);
            }
            x_split(d, sn, kp, kh);
            x_send(wgi, sn, sg, tid, sb, mate);
        }
        x_wait(wgi, RA - 1, sb); X_FINISH(RA - 1);
        const int lq = wgi == 0 ? 4 : 0;
        const uint32_t xbar = bars + 8 * (wgi ? B_QX : B_OPDONE);
#pragma unroll 1
        for (int s = 0; s < 64; s++) {
            TSI(s);
            uint32_t* ap = (uint32_t*)&g_alpha[((s & 1) * 32 + h) * (3 * 512) + wgi * 512 + ((nh * 4 + w) * 2 + kh) * 32] + lane;
            uint32_t mb0 = sb + O_MEM + (lane & 7) * 128 + (((lane >> 3) ^ (lane & 7)) << 4), mb1 = mb0 ^ 64;
            const uint32_t tag = ((s >> 1) & 1) ^ 1;
            const uint32_t tm = (lane & 7) ? ~0u : ~1u, tt = tag & ~tm;
            {
                float d[16]; uint32_t sn[4];
                mbar_wait(bars + 8 * B_XFULL, s & 1);
                mbar_wait(xbar, s & 1);
                TS(6);
                wg_fence();
#pragma unroll
                for (int ks = 0; ks < 32; ks++) {
                    if (ks == 0) wg_rs32<0>(d, a[ks], xdesc(ks)); else if (!(EXP & 4) || ks >= 8) wg_rs32<1>(d, a[ks], xdesc(ks));
                    if (ks == X_SEQ - 1) wg_commit();
                    if (X_HALF && ks == 15) { mbar_wait(bars + 8 * B_XF1, s & 1); wg_fence(); }
                }
                wg_commit();
                KEEP2(mb0, mb1); KEEPP(ap); KEEP2(tm, tt);
                SCHED_FENCE();
                wg_wait<1>();
                if (tid < lq) mbar_arrive(bars + 8 * B_QX);
                wg_wait<0>();
                TS(7);
                if (lane == 0) mbar_arrive(bars + 8 * B_MEM);
                x_split(d, sn, kp, kh);
                if (!(EXP & 8)) x_send(wgi, sn, s + RA, tid, sb, mate); else { KEEP2(sn[0], sn[1]); KEEP2(sn[2], sn[3]); KEEP2(kp[0], kp[1]); KEEP2(kp[2], kp[3]); }
                TS(4);
            }
            float e[2][4];
#pragma unroll
            for (int i = 0; i < 4; i++) e[0][i] = e[1][i] = 0.f;
            mbar_wait(bars + 8 * B_MEM, s & 1);
            TS(0);
#pragma unroll
            for (int ks = 0; ks < 32; ks += 2) {
                uint32_t b[4];
                ldsm4(b, ((ks & 2) ? mb1 : mb0) + kb_off(ks >> 2));
                mma16816(e[0], a[ks][0], a[ks][1], a[ks][2], a[ks][3], b[0], b[1]);
                mma16816(e[1], a[ks + 1][0], a[ks + 1][1], a[ks + 1][2], a[ks + 1][3], b[2], b[3]);
            }
            TS(2);
            if (QKW_POS == 0) { SCHED_FENCE(); if (lane == 0) mbar_arrive(bars + 8 * B_QKW); }
            stg_rlx32(ap, (pack_bf16(e[0][0] + e[1][0], e[0][1] + e[1][1]) & tm) | tt);
            stg_rlx32(ap + 32, (pack_bf16(e[0][2] + e[1][2], e[0][3] + e[1][3]) & tm) | tt);
            if (QKW_POS == 1 && lane == 0) mbar_arrive(bars + 8 * B_QKW);
            TS(3);
            if (wgi == 1) {
                const uint2* vp = &g_alpha[((s & 1) * 32 + h) * (3 * 512) + 1024 + w * 128 + lane];
                const uint32_t vs = sb + O_VM + tid * 16;
                KEEPP(vp); KEEP2(vs, 0);
                mbar_wait(bars + 8 * B_QST, s & 1);
                uint32_t n, bad;
                asm volatile("ld.shared.u32 %0, [%1];" : "=r"(n) : "r"(bars + 504) : "memory");
                wait_gtime(n + tn.d_v);
                TS(8);
                n = 0;
                do {
                    uint2 va[4];
#pragma unroll
                    for (int i = 0; i < 4; i++) va[i] = ldg_rlx64(vp + i * 32);
                    if (++n > SPIN_LIMIT) __trap();
                    bad = (orx2(va[0].x, va[1].x, tag) | orx2(va[2].x, va[3].x, tag)) & 1;
                    sts128u(vs, make_uint4((add_bf16x2(va[0].x, va[1].x) & ~1u) | ((~s ^ bad) & 1), add_bf16x2(va[0].y, va[1].y),
                                                             add_bf16x2(va[2].x, va[3].x), add_bf16x2(va[2].y, va[3].y)));
                } while (__any_sync(~0u, bad));
                TS(9);
                TSV(16 + w, n - 1);
                LT(s, 4 + w, n - 1);
            }
            if (!(EXP & 8)) {
                x_wait(wgi, s + RA, sb);
                mbar_wait(bars + 8 * FIN_BAR, s & 1);
                X_FINISH(s + RA);
                TS(5);
            }
        }
        sts32(bars + 508, sf);
        TSDUMP();
        asm volatile("bar.arrive 7, 512;" ::: "memory");
        float d[64];
        int st = 0, ph = 0;
#pragma unroll 1
        for (int kt = 0; kt < 64; kt++) {
            mbar_wait(bars + 8 * (B_GF + st), ph);
            if (kt == 0) GT(4);
            const uint64_t da = mkdesc(SM_BASE + st * 32768 + wgi * 8192, 128, 1024, 0), db = mkdesc(SM_BASE + st * 32768 + 16384, 8192, 1024, 1);
            wg_fence();
#pragma unroll
            for (int k = 0; k < 4; k++) wg_ss128(d, da + k * 16, db + k * 128, kt | k);
            wg_commit();
            if (kt > 0) {
                wg_wait<1>();
                if (lane == 0) mbar_arrive(bars + 8 * (B_GE + (st == 0 ? G_ST - 1 : st - 1)));
            }
            if (++st == G_ST) { st = 0; ph ^= 1; }
        }
        wg_wait<0>();
        {
            const uint32_t sl = sb + O_F1 + (wgi * 4 + w) * 4096;
#pragma unroll
            for (int i = 0; i < 8; i++)
                stsm4(sl + (lane & 15) * 256 + (((2 * i + (lane >> 4)) ^ (lane & 7)) << 4), pack_bf16(d[8 * i], d[8 * i + 1]),
                      pack_bf16(d[8 * i + 2], d[8 * i + 3]), pack_bf16(d[8 * i + 4], d[8 * i + 5]), pack_bf16(d[8 * i + 6], d[8 * i + 7]));
            __syncwarp();
            bf16* op = out + (size_t)((role >> 3) * 128 + wgi * 64 + w * 16 + (lane >> 4)) * 2048 + 1024 + (role & 7) * 128 + (lane & 15) * 8;
#pragma unroll
            for (int i = 0; i < 8; i++) {
                const int r = 2 * i + (lane >> 4);
                const uint4 v = lds128u(sl + r * 256 + (((lane & 15) ^ (r & 7)) << 4));
                stg128(op + (size_t)i * 4096, v.x, v.y, v.z, v.w);
            }
        }
        GT(5);
    } else if (wgi == 2) {
        asm volatile("setmaxnreg.dec.sync.aligned.u32 64;");
        PIN_IDS();
        asm volatile("barrier.cluster.arrive.relaxed.aligned;" ::: "memory");
        if (w == 0) {
            mbar_wait(bars + 8 * B_KDONE, 0);
            if (lane == 0) { X_REFILL(RA, 0); X_REFILL(RA, 1); }
            mbar_wait(bars + 8 * B_QDONE, 0);
            if (lane == 0) { mbar_expect_tx(bars + 8 * B_XP, 65536); for (int i = 0; i < 4; i++) X_LOAD(O_WO + i * 16384, i >> 1, i & 1, B_XP); }
#pragma unroll 1
            for (int i = nearly; i < 12; i++) { mbar_wait(bars + 8 * (B_W + i - depth), 0); W_LOAD(i); }
        }
        asm volatile("barrier.cluster.wait.acquire.aligned;" ::: "memory");
#pragma unroll 1
        for (int i = 8; i < 12; i++) mbar_wait(bars + 8 * (B_W + i), 0);
        GT(12);
        uint32_t sf = 0, tref = gtime() - 4000;
        uint32_t* const stp = lane < 8 ? (uint32_t*)g_qst + role * 8 + lane : (uint32_t*)g_stamp + role;
#define STAMP(st) { mbar_wait(bars + 8 * B_MEM, (st) & 1); if (lane < 9) stg_rlx32(stp, gtime()); }
#define V_PASS(d)                                                                                          \
        wg_fence();                                                                                        \
        _Pragma("unroll") for (int ks = 0; ks < 32; ks++) {                                                \
            constexpr uint64_t da0 = mkdesc(SM_BASE + O_WV, 16, 1024, 1);                                  \
            if (ks == 0) wg_ss40<0>(d, da0 + ks * 128, xdesc(ks)); else wg_ss40<1>(d, da0 + ks * 128, xdesc(ks)); \
            if (ks == V_SEQ - 1) wg_commit();                                                              \
        }                                                                                                  \
        wg_commit();                                                                                       \
        if (V_SEQ) wg_wait<1>();                                                                           \
        if (V_SEQ && lane == 0) mbar_arrive(bars + 8 * B_VA);        \
        wg_wait<0>();
        mbar_wait(bars + 8 * B_XP, 0);
        {
            uint32_t kp[4];
#pragma unroll 1
            for (int sg = 0; sg <= RA; sg++) {
                float d[20]; uint32_t sn[4];
                if (sg < RA) {
#pragma unroll
                    for (int i = 0; i < 20; i++) d[i] = 0.f;
#pragma unroll 1
                    for (int kb = 0; kb < 8; kb++) {
                        const uint64_t da = mkdesc(SM_BASE + O_WV, 16, 1024, 1) + kb * 512, db = mkdesc(SM_BASE + O_WO, 16, 4096, 1) + sg * 2048 + (kb >> 2) * 1024 + (kb & 3) * 64;
                        wg_fence();
#pragma unroll
                        for (int i = 0; i < 4; i++) wg_ss40<1>(d, da + i * 128, db + i * 2);
                        wg_commit();
                    }
                    wg_wait<0>();
                }
                if (sg == RA - 1) {
                    if (lane == 0) mbar_arrive(bars + 8 * B_XPE);
                    if (w == 0) {
                        mbar_wait(bars + 8 * B_XPE, 0);
                        GT(9);
                        if (lane == 0) {
                            mbar_expect_tx(bars + 8 * B_WO, 65536);
#pragma unroll
                            for (int i = 0; i < 4; i++) tma2d(sb + O_WO + i * 16384, &tm_wo, j * 256 + i * 64, h * 128, bars + 8 * B_WO);
                        }
                    }
                }
                if (sg > 0) { x_wait(2, sg - 1, sb); x_finish<2>(kp, sg - 1, h, nh * 4 + w, kh, tid, sb); }
                if (sg < RA) { x_split(d, sn, kp, kh); x_send(2, sn, sg, tid, sb, mate); }
            }
        }
        if (STAMP_V && w == 2) STAMP(0);
#pragma unroll 1
        for (int s = 0; s < 64; s++) {
            TSI(s);
            OPAQUE_IDS();
            uint2* ap = &g_alpha[((s & 1) * 32 + h) * (3 * 512) + 1024 + ((nh * 4 + w) * 2 + kh) * 32 + lane];
            KEEPP(ap);
            float d[20];
            mbar_wait(bars + 8 * B_QKW, s & 1);
            TS(0);
            if (s == 0) GT(14);
            V_PASS(d);
            TS(1);
            stg_rlx64(ap, (pack_bf16(d[16], d[17]) & ~1u) | (((s >> 1) & 1) ^ 1), pack_bf16(d[18], d[19]));
            if (lane == 0) mbar_arrive(bars + 8 * B_XEMPTY);
            if (s == 63) break;
            uint32_t sn[4], kp[4];
            x_split(d, sn, kp, kh);
            if (w == 3) {
                uint32_t n = 0, mx;
                do {
                    const uint4 st = ldg_rlx128(&g_stamp[lane]);
                    mx = __reduce_max_sync(~0u, max(max(st.x - tref, st.y - tref), max(st.z - tref, st.w - tref)));
                    if (DBG_TIMING) TSV(14, mx - __reduce_min_sync(~0u, min(min(st.x - tref, st.y - tref), min(st.z - tref, st.w - tref))));
                } while (mx >= 200000u && ++n < 64);
                tref = mx < 200000u ? tref + mx + 1 : gtime();
                TSV(12, clk()); TSV(13, n);
            }
            if (w == 0) {
                mbar_wait(bars + 8 * B_XEMPTY, s & 1);
                mbar_wait(bars + 8 * B_SRDY, s & 1);
                if (lane == 0) { X_REFILL(s + RA + 1, 0); X_REFILL(s + RA + 1, 1); }
            } else if (w == 1) {
                const uint4* hb = &g_kvq[(((s + 1) & 3) * 32 + h) * (3 * 512)];
                if (V_KEEP) { mbar_wait(bars + 8 * B_SRDY, s & 1); wait_clk(clk(), tn.spread); } else mbar_wait(bars + 8 * B_X0, s & 1);
                if (lane == 0) {
                    if (EXP & 2) mbar_arrive(bars + 8 * B_KVFULL); else {
                    mbar_expect_tx(bars + 8 * B_KVFULL, 18432);
                    bulk_g2s(sb + O_KVQ, hb + 512, 16384, bars + 8 * B_KVFULL);
                    bulk_g2s(sb + O_KVQ + 16384, hb + j * 128, 2048, bars + 8 * B_KVFULL);
                    }
                }
            }
            mbar_wait(bars + 8 * B_OPDONE, (s + 1) & 1);
            if (!(EXP & 8)) x_send(2, sn, s + RA, tid, sb, mate); else { KEEP2(sn[0], sn[1]); KEEP2(sn[2], sn[3]); KEEP2(kp[0], kp[1]); KEEP2(kp[2], kp[3]); }
            if (w == 3) {
                wait_gtime(tref + tn.d_r);
                if (lane <= R_SPLIT) {
                    const uint32_t bytes = 16384 >> R_SPLIT, bar = bars + 8 * (lane ? B_XF1 : B_RFULL);
                    mbar_expect_tx(bar, bytes);
                    bulk_g2s(sb + O_STG + lane * 8192, redp + (s & 3) * 32768 + kh * 16384 + lane * 8192, bytes, bar);
                }
                TSV(3, clk());
            }
            if (!V_LATE && !(EXP & 8)) { x_wait(2, s + RA, sb); x_finish<2>(kp, s + RA, h, nh * 4 + w, kh, tid, sb); TS(6); }
            if (DBG_TIMING && w == 0) { mbar_wait(bars + 8 * B_RFULL, s & 1); TS(4); }
            const uint32_t n = convert_mem(redp, s, kh, 0, w, lane, sb, sf); (void)n;
            TS(5);
            TSV(8 + w, n);
            LT(s, 8 + w, n);
            if (STAMP_V && w == 2) STAMP(s + 1);
            if (V_LATE && !(EXP & 8)) { x_wait(2, s + RA, sb); x_finish<2>(kp, s + RA, h, nh * 4 + w, kh, tid, sb); }
        }
        sts32(bars + 508, sf);
        TSDUMP();
        asm volatile("bar.arrive 7, 512;" ::: "memory");
    } else {
        asm volatile("setmaxnreg.dec.sync.aligned.u32 96;");
        PIN_IDS();
        GT(0);
        asm volatile("barrier.cluster.arrive.relaxed.aligned;" ::: "memory");
#define RED_CLEAR(st)                                                                                           \
        if (lane < 16) {                                                                                        \
            const uint32_t cb = ((st) & 4) ? 0x42800000u : 0u;                                                  \
            stg128(redp + ((st) & 3) * 32768 + role * 256 + lane * 16, 0, (role & 2) ? cb : 0u, 0, cb);        \
        }
        if (w == 0) {
            RED_CLEAR(0); RED_CLEAR(1); RED_CLEAR(2);
            if (lane == 0) { tma_st4(sb + O_F1, &fm.y, (role & 15) * 64, role >> 4); bulk_commit(); }
        }
        sts128u(sb + O_VM + tid * 16, make_uint4(0, 0, 0, 0));
        {
            uint4 v[4];
#pragma unroll
            for (int q = 0; q < 4; q++) v[q] = *(const uint4*)(mem0 + ((lane >> 3) + (q & 1) * 4) * 1024 + kh * 512 + (2 * w + (q >> 1)) * 64 + (lane & 7) * 8);
            mbar_wait(bars + 8 * B_KDONE, 0);
#pragma unroll
            for (int q = 0; q < 4; q++) {
                const int row = (lane >> 3) + (q & 1) * 4;
                sts128u(sb + O_MEM + kb_off(2 * w + (q >> 1)) + row * 128 + (((lane & 7) ^ row) << 4), v[q]);
            }
            fence_async_smem();
            __syncwarp();
            if (lane < 2) { mbar_arrive(bars + 8 * B_MEM); mbar_arrive(bars + 8 * B_QKW); }
            if (lane == 0) mbar_arrive(bars + 8 * B_OPDONE);
            if (tid == 0) mbar_arrive(bars + 8 * B_KVFULL);
        }
        asm volatile("barrier.cluster.wait.acquire.aligned;" ::: "memory");
        if (w == 0) {
            if (lane == 0) bulk_wait_all();
            __syncwarp();
            gbar_wait(&g_start, gbar_arrive(&g_start, 1, 256, lane), 0);
            GT(13);
        }
        if (w == 1) {
            mbar_wait(bars + 8 * (B_W + 10), 0);
            uint32_t t = gtime();
#pragma unroll 1
            for (int i = 0; i < 4; i++) { if (lane == 0) tma2d_prefetch(&tm_wo, j * 256 + i * 64, h * 128); t += tn.extra; if (i < 3) wait_gtime(t); }
        }
        bar_sync(1, 128);
        uint32_t sf = 0, xo[4];
#define XO_STORE(st) { uint32_t* op = (uint32_t*)g_ox + ((size_t)((st) * 4 + j) * 4096 + h * 128 + w * 32) * 4 + lane; op[0] = xo[0]; op[32] = xo[1]; op[64] = xo[2]; op[96] = xo[3]; }
#pragma unroll 1
        for (int s = 0; s < 64; s++) {
            TSI(s);
            OPAQUE_IDS();
            uint32_t kf[4][4], qf[4];
            const uint32_t l03 = lane < 4;
            const uint32_t tg = ((s >> 2) & 1) ^ 1;
            {
                const uint32_t ka = sb + O_KVQ + w * 2048 + lane * 16, qa = sb + O_KVQ + 16384 + w * 512 + lane * 16;
                uint32_t n = s == 0;
                bool redo;
#pragma unroll 1
                do {
                    asm volatile("" : "+r"(n));
                    if (n) {
                        const uint4* hb = &g_kvq[((s & 3) * 32 + __shfl_sync(~0u, h, 0)) * (3 * 512)];
                        uint4 x[4], y[4], z;
                        do {
#pragma unroll
                            for (int i = 0; i < 4; i++) { x[i] = ldg_rlx128(hb + 512 + w * 128 + i * 32 + lane); y[i] = ldg_rlx128(hb + 1024 + w * 128 + i * 32 + lane); }
                            z = ldg_rlx128(hb + j * 128 + w * 32 + lane);
                            if (++n > SPIN_LIMIT) __trap();
                        } while (__any_sync(~0u, (orx2(y[0].x, y[1].x, tg) | orx2(y[2].x, y[3].x, tg)) & 1));
#pragma unroll
                        for (int i = 0; i < 4; i++) { sts128u(ka + i * 512, x[i]); sts128u(ka + 8192 + i * 512, y[i]); }
                        sts128u(qa, z);
                        fence_async_smem();
                    }
                    n++;
                    mbar_wait(bars + 8 * B_KVFULL, s & 1);
#pragma unroll
                    for (int i = 0; i < 4; i++) ldsm4t(kf[i], ka + i * 512);
                    ldsm4t(qf, qa);
                    redo = __any_sync(~0u, or3(or3(tags4(kf[0], tg), tags4(kf[1], tg), tags4(kf[2], tg)), tags4(kf[3], tg), tags4(qf, tg)) & l03 & ((EXP & 10) ? s >> 8 : ~0u));
                } while (redo);
                if (w == 0) TSV(22, n - 1);
            }
            TS(9);
            if (s == 0) GT(15);
            if (s > 0) {
                if (XO_POS == 0) XO_STORE(s - 1);
                const uint32_t n = convert_mem(redp, s - 1, kh, 1, w, lane, sb, sf); (void)n;
                TS(11);
                TSV(16 + w, n);
                LT(s - 1, 12 + w, n);
                if (XO_POS == 1) XO_STORE(s - 1);
                if (w == 1 && s < 62) RED_CLEAR(s + 2);
            }
            const uint32_t tag = ((s >> 1) & 1) ^ 1;
            const uint4* ap = (const uint4*)&g_alpha[((s & 1) * 32 + h) * (3 * 512) + w * 128] + lane;
            const uint32_t l16 = sb + lane * 16, l4 = sb + lane * 4;
            const uint32_t sw = l16 + O_S + w * 2560, sr = l4 + O_S + w * 128;
            uint32_t pw = sb + O_P + ((lane >> 1) & 1) * 704 + (2 * w + (lane >> 4)) * 16 + ((lane >> 2) & 3) * 4 + (lane & 1) * 2;
            int lim = (lane & 2) ? 8 * j + 2 * w + (lane >> 4) - 2 * ((lane >> 2) & 3) - (lane & 1) : 64;
            const uint32_t aa = l16 + O_STG + w * 1024;
            unsigned char* pa = redp + (s & 3) * 32768 + red_grp(j * 16 + (tid >> 3));
            unsigned char* pb = pa + 512 + ((lane >> 3) & 1) * 64 + (lane & 7) * 8;
            pa += (lane & 7) * 16;
            KEEPP(pa); KEEPP(pb);
            KEEP2(l16, l4); KEEP2(pw, lim); KEEP2(sr, 0); KEEP2(l03, tag);
            TS(0);
            if (w == 0) {
                const uint32_t* qp = (const uint32_t*)g_qst + h * 32 + lane;
                KEEPP(qp);
                mbar_wait(bars + 8 * B_MEM, s & 1);
                uint32_t tq = gtime() - 1024;
                if (!STAMP_V && lane < 9) stg_rlx32(lane < 8 ? (uint32_t*)g_qst + role * 8 + lane : (uint32_t*)g_stamp + role, tq + 1024);
                wait_clk(clk(), tn.d_q);
                uint32_t n = 0, mx;
                do { mx = __reduce_max_sync(~0u, ldg_rlx32(qp) - tq); } while (mx > 100000u && ++n < 16);
                TSV(13, n);
                LT(s, 2, n);
                tq += mx <= 100000u ? mx : 1024;
                if (lane == 0) { sts32(bars + 504, tq); mbar_arrive(bars + 8 * B_QST); }
                TS(14);
                mbar_wait(bars + 8 * B_QKW, s & 1);
                TS(1);
                wait_gtime(tq + tn.d_alpha);
                if (lane == 0) {
                    mbar_expect_tx(bars + 8 * B_AFULL, 8192);
                    bulk_g2s(sb + O_STG, ap, 8192, bars + 8 * B_AFULL);
                }
                if (s == 0) { mbar_wait(bars + 8 * B_WO, 0); GT(1); }
            }
            {
                uint32_t n = 0;
                bool redo;
#pragma unroll 1
                do {
                    asm volatile("" : "+r"(n));
                    if (n) {
                        uint4 x[4];
#pragma unroll
                        for (int q = 0; q < 4; q++) x[q] = ldg_rlx128(ap + (q >> 1) * 256 + (q & 1) * 32);
#pragma unroll
                        for (int q = 0; q < 4; q++) sts128u(aa + (q >> 1) * 4096 + (q & 1) * 512, x[q]);
                        __syncwarp();
                        if (n > SPIN_LIMIT) __trap();
                    }
                    n++;
                    mbar_wait(bars + 8 * B_AFULL, s & 1);
                    TS(12);
                    if (V_SEQ) mbar_wait(bars + 8 * B_VA, s & 1);
                    uint32_t qa[2][4], ka[2][4];
#pragma unroll
                    for (int u = 0; u < 2; u++) { ldsm4t(qa[u], aa + u * 512); ldsm4t(ka[u], aa + 4096 + u * 512); }
                    float sa[5][4];
#pragma unroll
                    for (int i = 0; i < 5; i++) sa[i][0] = sa[i][1] = sa[i][2] = sa[i][3] = 0.f;
#pragma unroll
                    for (int u = 0; u < 2; u++) {
                        const uint32_t q0 = add_bf16x2(qa[u][0], qa[u][2]), q1 = add_bf16x2(qa[u][1], qa[u][3]);
                        mma16816(sa[1], q0, qf[2 * u], q1, qf[2 * u + 1], kf[2 * u][0], kf[2 * u][1]);
                        mma16816(sa[2], q0, qf[2 * u], q1, qf[2 * u + 1], kf[2 * u][2], kf[2 * u][3]);
                        mma16816(sa[3], q0, qf[2 * u], q1, qf[2 * u + 1], kf[2 * u + 1][0], kf[2 * u + 1][1]);
                        mma16816(sa[4], q0, qf[2 * u], q1, qf[2 * u + 1], kf[2 * u + 1][2], kf[2 * u + 1][3]);
                        const uint32_t k0 = add_bf16x2(ka[u][0], ka[u][2]), k1 = add_bf16x2(ka[u][1], ka[u][3]);
                        mma16816(sa[0], q0, qf[2 * u], q1, qf[2 * u + 1], k0, k1);
                        if (u == 0) SCHED_FENCE();
                    }
                    redo = __any_sync(~0u, (or3(tags4(qa[0], tag), tags4(ka[0], tag), tags4(qa[1], tag)) | tags4(ka[1], tag)) & l03);
#pragma unroll
                    for (int i = 1; i <= 5; i++) sts128(sw + (i % 5) * 512, sa[i % 5][0], sa[i % 5][1], sa[i % 5][2], sa[i % 5][3]);
                } while (redo);
                if (w == 0) TSV(20, n - 1);
                if (n > 1) LT(s, 3, 0x10000 + s);
            }
            TS(2);
            bar_sync(1, 128);
            float sc[5];
            {
                float x[4][5];
#pragma unroll
                for (int q = 0; q < 4; q++)
#pragma unroll
                    for (int n = 0; n < 5; n++) asm volatile("ld.shared.f32 %0, [%1];" : "=f"(x[q][n]) : "r"(sr + q * 2560 + n * 512) : "memory");
#pragma unroll
                for (int n = 0; n < 5; n++) sc[n] = (x[0][n] + x[1][n]) + (x[2][n] + x[3][n]);
            }
            TS(15);
#pragma unroll
            for (int n = 1; n < 5; n++) if (8 * (n - 1) > lim) sc[n] = MASK_VAL;
            float m = fmaxf(fmaxf(fmaxf(sc[0], sc[1]), fmaxf(sc[2], sc[3])), sc[4]);
            m = fmaxf(m, __shfl_xor_sync(~0u, m, 1));
            m = fmaxf(m, __shfl_xor_sync(~0u, m, 4));
            m = fmaxf(m, __shfl_xor_sync(~0u, m, 8));
            SCHED_FENCE();
            uint4 vf[4];
#pragma unroll
            for (int i = 0; i < 4; i++) vf[i] = lds128u(l16 + O_KVQ + 8192 + w * 2048 + i * 512);
            m *= -SM_SCALE_LOG2;
#pragma unroll
            for (int n = 0; n < 5; n++) {
                const uint32_t pv = pack_bf16(ex2(fmaf(sc[n], SM_SCALE_LOG2, m)), 0.f);
                asm volatile("st.shared.u16 [%0], %1;" ::"r"(pw + n * 128), "h"((uint16_t)pv) : "memory");
            }
            if (V_KEEP) { KEEP2(vf[0].x, vf[1].x); KEEP2(vf[2].x, vf[3].x); SCHED_FENCE(); }
            bar_sync(1, 128);
            TS(3);
            if (lane == 0) mbar_arrive(bars + 8 * B_SRDY);
            float ox[2][4], sm[4], sx[4], cc[4][4];
#pragma unroll 1
            for (uint32_t nv = 0;; nv++) {
                uint32_t pf[4], p0, px[4], px0;
                ldsm4(pf, l16 + O_P + 128);
                ldsm4(px, l16 + O_P + 128 + 704);
                asm volatile("ld.shared.u32 %0, [%1];" : "=r"(p0) : "r"(l4 + O_P) : "memory");
                asm volatile("ld.shared.u32 %0, [%1];" : "=r"(px0) : "r"(l4 + O_P + 704) : "memory");
                float o[2][4];
#pragma unroll
                for (int i = 0; i < 4; i++) o[0][i] = o[1][i] = ox[0][i] = ox[1][i] = sm[i] = sx[i] = 0.f;
                constexpr uint32_t ONE2 = 0x3f803f80u;
                mma1688(sm, ONE2, ONE2, p0);
                mma1688(sx, ONE2, ONE2, px0);
#pragma unroll
                for (int c = 0; c < 2; c++) {
#pragma unroll
                    for (int u = 0; u < 2; u++) mma16816(o[u], vf[2 * u + c].x, vf[2 * u + c].y, vf[2 * u + c].z, vf[2 * u + c].w, pf[2 * c], pf[2 * c + 1]);
#pragma unroll
                    for (int u = 0; u < 2; u++) mma16816(ox[u], vf[2 * u + c].x, vf[2 * u + c].y, vf[2 * u + c].z, vf[2 * u + c].w, px[2 * c], px[2 * c + 1]);
                    mma16816(sm, ONE2, ONE2, ONE2, ONE2, pf[2 * c], pf[2 * c + 1]);
                    mma16816(sx, ONE2, ONE2, ONE2, ONE2, px[2 * c], px[2 * c + 1]);
                }
                const uint32_t vbad = orx(orx(orx2(vf[0].x, vf[1].x, tg), vf[2].x, tg), vf[3].x, tg);
                uint4 vm;
                {
                    uint32_t n = 0;
                    bool redo;
#pragma unroll 1
                    do {
                        vm = lds128v(l16 + O_VM + w * 512);
                        float o2[2][4];
#pragma unroll
                        for (int i = 0; i < 4; i++) { o2[0][i] = o[0][i]; o2[1][i] = o[1][i]; }
                        mma1688(o2[0], vm.x, vm.y, p0);
                        mma1688(o2[1], vm.z, vm.w, p0);
                        redo = __any_sync(~0u, ((vm.x ^ ~s) & 1) && ++n < SPIN_LIMIT);
                        const uint32_t oa = l4 + O_O + w * 512;
                        sts32(oa, pack_bf16(o2[0][0], o2[0][1]));
                        sts32(oa + 128, pack_bf16(o2[0][2], o2[0][3]));
                        sts32(oa + 256, pack_bf16(o2[1][0], o2[1][1]));
                        sts32(oa + 384, pack_bf16(o2[1][2], o2[1][3]));
                    } while (redo);
                    if (w == 0) TSV(21, n);
                }
                TS(4);
                fence_async_smem();
                mma1688(ox[0], vm.x, vm.y, px0);
                mma1688(ox[1], vm.z, vm.w, px0);
                sm[0] = rcp(sm[0]); sm[1] = rcp(sm[1]);
                bar_sync(1, 128);
                if (!V_KEEP && lane == 0 && nv == 0) mbar_arrive(bars + 8 * B_X0);
                TS(5);
#define OP_ISSUE(t0, t1)                                                                                       \
                wg_fence();                                                                                    \
                _Pragma("unroll") for (int ks = 0; ks < 8; ks++)                                               \
                    _Pragma("unroll") for (int t = t0; t < t1; t++) {                                          \
                        constexpr uint64_t da0 = mkdesc(SM_BASE + O_WO, 16, 1024, 1), db0 = mkdesc(SM_BASE + O_O, 128, 128, 0); \
                        if (ks == 0) wg_ss8<0>(cc[t], da0 + t * 1024, db0); else wg_ss8<1>(cc[t], da0 + t * 1024 + ks * 128, db0 + ks * 16); \
                    }                                                                                          \
                wg_commit();
                OP_ISSUE(0, (OP_SPLIT ? 2 : 4));
                if (!bar_or(1, 128, vbad & ((EXP & 10) ? s >> 8 : ~0u))) break;
                wg_wait<0>();
                const uint4* vq = &g_kvq[((s & 3) * 32 + h) * (3 * 512) + 1024 + w * 128 + __shfl_sync(~0u, lane, lane)];
#pragma unroll
                for (int i = 0; i < 4; i++) { vf[i] = ldg_rlx128(vq + i * 32); }
                KEEP2(vf[0].x, vf[1].x); KEEP2(vf[2].x, vf[3].x);
                SCHED_FENCE();
                if (nv > SPIN_LIMIT) __trap();
                bar_sync(1, 128);
            }
            {
                const float i0 = sm[0], i1 = sm[1];
#pragma unroll
                for (int hf = 0; hf < 2; hf++) {
                    if (hf == 0 || OP_SPLIT) wg_wait<0>();
                    if (hf == 0) TS(6);
                    if (OPD_EARLY && hf == OP_SPLIT && lane == 0) mbar_arrive(bars + 8 * B_OPDONE);
                    asm volatile("red.relaxed.gpu.global.add.noftz.v4.bf16x2 [%0], {%1,%2,%3,%4};" ::"l"(pa + hf * 128),
                                 "r"(pack_bf16(cc[2 * hf][0] * i0, cc[2 * hf][1] * i1)), "r"(pack_bf16(cc[2 * hf][2] * i0, cc[2 * hf][3] * i1)),
                                 "r"(pack_bf16(cc[2 * hf + 1][0] * i0, cc[2 * hf + 1][1] * i1)), "r"(pack_bf16(cc[2 * hf + 1][2] * i0, 1.f)) : "memory");
                    if (OP_SPLIT && hf == 0) { SCHED_FENCE(); OP_ISSUE(2, 4); }
                }
                asm volatile("red.relaxed.gpu.global.add.noftz.v2.bf16x2 [%0], {%1,%2};" ::"l"(pb), "r"(pack_bf16(cc[1][3] * i1, cc[3][3] * i1)), "r"(0x3f800000u) : "memory");
                if (!OPD_EARLY && lane == 0) mbar_arrive(bars + 8 * B_OPDONE);
                SCHED_FENCE();
                TS(7);
            }
            {
                const float ix0 = rcp(sx[0]), ix1 = rcp(sx[1]);
                xo[0] = pack_bf16(ox[0][0] * ix0, ox[0][1] * ix1); xo[1] = pack_bf16(ox[0][2] * ix0, ox[0][3] * ix1);
                xo[2] = pack_bf16(ox[1][0] * ix0, ox[1][1] * ix1); xo[3] = pack_bf16(ox[1][2] * ix0, ox[1][3] * ix1);
                if (XO_POS == 2) XO_STORE(s);
            }
            TS(8);
            if (w == 2) { LT(s, 0, gtime()); LT(s, 1, clk()); }
            if (s == 0) GT(2);
        }
        if (XO_POS < 2) XO_STORE(63);
        GT(3);
        sts32(bars + 508, sf);
        TSDUMP();
        bar_sync(7, 512);
        const int m0 = (role >> 3) * 16, nb = (role & 7) * 2;
#define W2_LOAD(st, kt) { mbar_expect_tx(bars + 8 * (B_GF + (st)), 32768); tma3d(sb + (st) * 32768 + 16384, &tm_w2, 0, (kt) * 64, nb, bars + 8 * (B_GF + (st))); }
        if (w == 1 && lane == 0) {
            fence_async_smem();
#pragma unroll 1
            for (int kt = 0; kt < G_ST; kt++) W2_LOAD(kt, kt);
        }
        if (w == 0) {
            gbar_wait(&g_end, gbar_arrive(&g_end, 1, 128, lane), 0);
            int st = 0, ph = 1;
#pragma unroll 1
            for (int kt = 0; kt < 64; kt++) {
                if (kt >= G_ST) mbar_wait(bars + 8 * (B_GE + st), ph);
                if (lane == 0) {
                    if (kt >= G_ST) W2_LOAD(st, kt);
                    tma2d(sb + st * 32768, &tm_o, kt * 128, m0, bars + 8 * (B_GF + st));
                }
                if (++st == G_ST) { st = 0; ph ^= 1; }
            }
        }
    }
}

typedef CUresult (*EncodeFn)(CUtensorMap*, CUtensorMapDataType, cuuint32_t, void*, const cuuint64_t*, const cuuint64_t*,
                             const cuuint32_t*, const cuuint32_t*, CUtensorMapInterleave, CUtensorMapSwizzle,
                             CUtensorMapL2promotion, CUtensorMapFloatOOBfill);

static void make_map(EncodeFn fn, CUtensorMap* m, const void* p, uint64_t cols, uint64_t rows, uint32_t bc, uint32_t br) {
    cuuint64_t dims[2] = {cols, rows}, strides[1] = {cols * 2};
    cuuint32_t box[2] = {bc, br}, es[2] = {1, 1};
    fn(m, CU_TENSOR_MAP_DATA_TYPE_BFLOAT16, 2, (void*)p, dims, strides, box, es, CU_TENSOR_MAP_INTERLEAVE_NONE,
       CU_TENSOR_MAP_SWIZZLE_128B, CU_TENSOR_MAP_L2_PROMOTION_L2_128B, CU_TENSOR_MAP_FLOAT_OOB_FILL_NONE);
}

static Tune h_tune = {480, 1920, 16 * 2 + 256 * 4, 100, 960, 300, 600};

extern "C" void kernel_launch(void* const* d_in, const int* in_sizes, int n_in, void* d_out, int out_size) {
    static bool init = false;
    static FftMaps fm;
    static CUtensorMap tm_x, tm_wq, tm_wk, tm_wv, tm_wo, tm_o, tm_wo2;
    if (!init) {
        void* fp = nullptr; cudaDriverEntryPointQueryResult qr;
        cudaGetDriverEntryPoint("cuTensorMapEncodeTiled", &fp, cudaEnableDefault, &qr);
        EncodeFn fn = (EncodeFn)fp;
        void* ox = nullptr; cudaGetSymbolAddress(&ox, g_ox);
        {
            cuuint64_t dims[4] = {64, 8, 16, 256}, strides[3] = {2048, 128, 16384};
            cuuint32_t box[4] = {64, 8, 4, 4}, es[4] = {1, 1, 1, 1};
            fn(&tm_x, CU_TENSOR_MAP_DATA_TYPE_BFLOAT16, 4, d_in[3], dims, strides, box, es, CU_TENSOR_MAP_INTERLEAVE_NONE,
               CU_TENSOR_MAP_SWIZZLE_128B, CU_TENSOR_MAP_L2_PROMOTION_L2_128B, CU_TENSOR_MAP_FLOAT_OOB_FILL_NONE);
        }
        void* fy = nullptr; cudaGetSymbolAddress(&fy, g_fy);
        for (int i = 0; i < 3; i++) {
            const cuuint64_t pitch = i == 2 ? 4096 : 2048;
            cuuint64_t dims[4] = {1024, 8, 16, 16}, strides[3] = {pitch, 128 * pitch, 8 * pitch};
            cuuint32_t box[4] = {64, 1, 16, 16}, es[4] = {1, 1, 1, 1};
            fn(i == 0 ? &fm.x : i == 1 ? &fm.y : &fm.o, CU_TENSOR_MAP_DATA_TYPE_BFLOAT16, 4, i == 0 ? d_in[0] : i == 1 ? fy : d_out, dims, strides, box, es,
               CU_TENSOR_MAP_INTERLEAVE_NONE, CU_TENSOR_MAP_SWIZZLE_128B, CU_TENSOR_MAP_L2_PROMOTION_L2_256B, CU_TENSOR_MAP_FLOAT_OOB_FILL_NONE);
        }
        {
            cuuint64_t dims[3] = {64, 2048, 16}, strides[2] = {2048, 128};
            cuuint32_t box[3] = {64, 8, 16}, es[3] = {1, 1, 1};
            fn(&fm.y2, CU_TENSOR_MAP_DATA_TYPE_BFLOAT16, 3, fy, dims, strides, box, es, CU_TENSOR_MAP_INTERLEAVE_NONE,
               CU_TENSOR_MAP_SWIZZLE_128B, CU_TENSOR_MAP_L2_PROMOTION_L2_128B, CU_TENSOR_MAP_FLOAT_OOB_FILL_NONE);
        }
        for (int i = 0; i < 2; i++) {
            cuuint64_t dims[3] = {256 * 513 - 448, 8, 8}, strides[2] = {128, 256 * 1026};
            cuuint32_t box[3] = {72, 8, 8}, es[3] = {1, 1, 1};
            fn(i ? &fm.wi : &fm.wr, CU_TENSOR_MAP_DATA_TYPE_BFLOAT16, 3, d_in[1 + i], dims, strides, box, es, CU_TENSOR_MAP_INTERLEAVE_NONE,
               CU_TENSOR_MAP_SWIZZLE_NONE, CU_TENSOR_MAP_L2_PROMOTION_L2_128B, CU_TENSOR_MAP_FLOAT_OOB_FILL_NONE);
        }
        fm.w[0] = (const unsigned char*)d_in[1]; fm.w[1] = (const unsigned char*)d_in[2]; fm.w[2] = (const unsigned char*)d_in[3];
        make_map(fn, &tm_wq, d_in[5], 4096, 1024, 64, 128);
        make_map(fn, &tm_wk, d_in[6], 4096, 1024, 64, 128);
        make_map(fn, &tm_wv, d_in[7], 4096, 1024, 64, 128);
        make_map(fn, &tm_wo, d_in[8], 1024, 4096, 64, 128);
        {
            cuuint64_t dims[2] = {8192, 256}, strides[1] = {65536};
            cuuint32_t box[2] = {128, 16}, es[2] = {1, 1};
            fn(&tm_o, CU_TENSOR_MAP_DATA_TYPE_UINT64, 2, ox, dims, strides, box, es, CU_TENSOR_MAP_INTERLEAVE_NONE,
               CU_TENSOR_MAP_SWIZZLE_NONE, CU_TENSOR_MAP_L2_PROMOTION_L2_128B, CU_TENSOR_MAP_FLOAT_OOB_FILL_NONE);
        }
        {
            cuuint64_t dims[3] = {64, 4096, 16}, strides[2] = {2048, 128};
            cuuint32_t box[3] = {64, 64, 2}, es[3] = {1, 1, 1};
            fn(&tm_wo2, CU_TENSOR_MAP_DATA_TYPE_BFLOAT16, 3, d_in[8], dims, strides, box, es, CU_TENSOR_MAP_INTERLEAVE_NONE,
               CU_TENSOR_MAP_SWIZZLE_128B, CU_TENSOR_MAP_L2_PROMOTION_L2_128B, CU_TENSOR_MAP_FLOAT_OOB_FILL_NONE);
        }
        cudaFuncSetAttribute(rmt_main, cudaFuncAttributeMaxDynamicSharedMemorySize, MAIN_SMEM);
        init = true;
    }
    rmt_main<<<132, 512, MAIN_SMEM>>>(tm_x, tm_wq, tm_wk, tm_wv, tm_wo, (const bf16*)d_in[4], h_tune, fm, tm_o, tm_wo2, (bf16*)d_out);
}
```

```cpp
#include <cuda_runtime.h>
#include <cuda_bf16.h>
#include <cuda.h>
#include <stdint.h>

typedef __nv_bfloat16 bf16;

#define DBG_TIMING 0

#define SPIN_LIMIT (1u << 22)

__device__ __forceinline__ uint32_t smem_u32(const void* p) { return (uint32_t)__cvta_generic_to_shared(p); }
__device__ __forceinline__ uint32_t clk() { uint32_t c; asm volatile("mov.u32 %0, %%clock;" : "=r"(c)::"memory"); return c; }
#define SCHED_FENCE() sf ^= (uint32_t)clock64()
#define KEEP2(a, b) asm volatile("lop3.b32 %0, %0, %1, %2, 0x96;" : "+r"(sf) : "r"((uint32_t)(a)), "r"((uint32_t)(b)))
#define KEEPP(p) KEEP2((uintptr_t)(p), (uintptr_t)(p) >> 32)
__device__ __forceinline__ uint32_t gtime() { uint32_t c; asm volatile("mov.u32 %0, %%globaltimer_lo;" : "=r"(c)::"memory"); return c; }
__device__ __forceinline__ uint32_t gtime64() { uint64_t c; asm volatile("mov.u64 %0, %%globaltimer;" : "=l"(c)::"memory"); return (uint32_t)c; }
__device__ __forceinline__ void wait_clk(uint32_t t0, uint32_t d) {
    asm volatile("{\n.reg .pred p;\n.reg .s32 t;\n.reg .b64 c;\nWL:\nmov.u64 c, %%clock64;\ncvt.u32.u64 t, c;\nsub.s32 t, t, %0;\nsetp.lt.s32 p, t, 0;\n@p bra.uni WL;\n}" ::"r"(t0 + d) : "memory");
}
__device__ __forceinline__ void wait_gtime(uint32_t t1) {
    asm volatile("{\n.reg .pred p;\n.reg .s32 t;\n.reg .b64 c;\nWL:\nmov.u64 c, %%globaltimer;\ncvt.u32.u64 t, c;\nsub.s32 t, t, %0;\nsetp.lt.s32 p, t, 0;\n@p bra.uni WL;\n}" ::"r"(t1) : "memory");
}

__device__ __forceinline__ void mbar_init(uint32_t bar, uint32_t cnt) {
    asm volatile("mbarrier.init.shared::cta.b64 [%0], %1;" ::"r"(bar), "r"(cnt) : "memory");
}
__device__ __forceinline__ void mbar_arrive(uint32_t bar) {
    asm volatile("mbarrier.arrive.shared::cta.b64 _, [%0];" ::"r"(bar) : "memory");
}
__device__ __forceinline__ void mbar_expect_tx(uint32_t bar, uint32_t bytes) {
    asm volatile("mbarrier.arrive.expect_tx.shared::cta.b64 _, [%0], %1;" ::"r"(bar), "r"(bytes) : "memory");
}
__device__ __forceinline__ void mbar_wait(uint32_t bar, uint32_t parity) {
    asm volatile(
        "{\n.reg .pred p, q;\n.reg .u32 n;\nmov.u32 n, 0;\n"
        "WL:\nmbarrier.try_wait.parity.shared::cta.b64 p, [%0], %1;\n"
        "add.u32 n, n, 1;\nsetp.gt.u32 q, n, %2;\n@q trap;\n@!p bra.uni WL;\n}" ::"r"(bar), "r"(parity), "n"(SPIN_LIMIT) : "memory");
}
__device__ __forceinline__ void mbar_wait_cluster(uint32_t bar, uint32_t parity) {
    asm volatile(
        "{\n.reg .pred p, q;\n.reg .u32 n;\nmov.u32 n, 0;\n"
        "WL:\nmbarrier.try_wait.parity.acquire.cluster.shared::cta.b64 p, [%0], %1;\n"
        "add.u32 n, n, 1;\nsetp.gt.u32 q, n, %2;\n@q trap;\n@!p bra.uni WL;\n}" ::"r"(bar), "r"(parity), "n"(SPIN_LIMIT) : "memory");
}
__device__ __forceinline__ void tma2d(uint32_t dst, const CUtensorMap* m, int c0, int c1, uint32_t bar) {
    asm volatile("cp.async.bulk.tensor.2d.shared::cluster.global.mbarrier::complete_tx::bytes [%0], [%1, {%3, %4}], [%2];"
                 ::"r"(dst), "l"(m), "r"(bar), "r"(c0), "r"(c1) : "memory");
}
__device__ __forceinline__ void tma3d(uint32_t dst, const CUtensorMap* m, int c0, int c1, int c2, uint32_t bar) {
    asm volatile("cp.async.bulk.tensor.3d.shared::cluster.global.mbarrier::complete_tx::bytes [%0], [%1, {%3, %4, %5}], [%2];"
                 ::"r"(dst), "l"(m), "r"(bar), "r"(c0), "r"(c1), "r"(c2) : "memory");
}
__device__ __forceinline__ void tma4d(uint32_t dst, const CUtensorMap* m, int c2, int c3, uint32_t bar) {
    asm volatile("cp.async.bulk.tensor.4d.shared::cluster.global.mbarrier::complete_tx::bytes [%0], [%1, {%5, %5, %3, %4}], [%2];"
                 ::"r"(dst), "l"(m), "r"(bar), "r"(c2), "r"(c3), "r"(0) : "memory");
}
__device__ __forceinline__ void bulk_g2s(uint32_t dst, const void* src, uint32_t bytes, uint32_t bar) {
    asm volatile("cp.async.bulk.shared::cluster.global.mbarrier::complete_tx::bytes [%0], [%1], %2, [%3];"
                 ::"r"(dst), "l"(src), "r"(bytes), "r"(bar) : "memory");
}
__device__ __forceinline__ void tma4d_prefetch(const CUtensorMap* m, int c2, int c3) {
    asm volatile("cp.async.bulk.prefetch.tensor.4d.L2.global [%0, {%3, %3, %1, %2}];" ::"l"(m), "r"(c2), "r"(c3), "r"(0) : "memory");
}
__device__ __forceinline__ void tma2d_prefetch(const CUtensorMap* m, int c0, int c1) {
    asm volatile("cp.async.bulk.prefetch.tensor.2d.L2.global [%0, {%1, %2}];" ::"l"(m), "r"(c0), "r"(c1) : "memory");
}
__device__ __forceinline__ void fence_async_smem() { asm volatile("fence.proxy.async.shared::cta;" ::: "memory"); }
__device__ __forceinline__ void fence_gpu() { asm volatile("fence.acq_rel.gpu;" ::: "memory"); }
__device__ __forceinline__ float rcp(float x) { float r; asm("rcp.approx.ftz.f32 %0, %1;" : "=f"(r) : "f"(x)); return r; }
__device__ __forceinline__ void bar_sync(int id, int n) { asm volatile("bar.sync %0, %1;" ::"r"(id), "r"(n) : "memory"); }

__device__ __forceinline__ bool bar_or(int id, int n, uint32_t x) {
    uint32_t r;
    asm volatile("{\n.reg .pred p, q;\n.reg .b32 t;\nand.b32 t, %3, 1;\nsetp.ne.u32 p, t, 0;\nbar.red.or.pred q, %1, %2, p;\nselp.u32 %0, 1, 0, q;\n}"
                 : "=r"(r) : "r"(id), "r"(n), "r"(x) : "memory");
    return __any_sync(~0u, r);
}
__device__ __forceinline__ uint32_t or3(uint32_t a, uint32_t b, uint32_t c) {
    uint32_t r; asm("lop3.b32 %0, %1, %2, %3, 0xFE;" : "=r"(r) : "r"(a), "r"(b), "r"(c)); return r;
}
__device__ __forceinline__ uint32_t pack_bf16(float lo, float hi) {
    uint32_t r; asm("cvt.rn.bf16x2.f32 %0, %1, %2;" : "=r"(r) : "f"(hi), "f"(lo)); return r;
}
__device__ __forceinline__ uint32_t add_bf16x2(uint32_t a, uint32_t b) {
    uint32_t r; asm volatile("add.rn.bf16x2 %0, %1, %2;" : "=r"(r) : "r"(a), "r"(b)); return r;
}
__device__ __forceinline__ uint32_t movm(uint32_t a) {
    uint32_t r; asm volatile("movmatrix.sync.aligned.m8n8.trans.b16 %0, %1;" : "=r"(r) : "r"(a)); return r;
}
__device__ __forceinline__ uint32_t orx(uint32_t acc, uint32_t a, uint32_t t) {
    uint32_t r; asm("lop3.b32 %0, %1, %2, %3, 0xF6;" : "=r"(r) : "r"(acc), "r"(a), "r"(t)); return r;
}
__device__ __forceinline__ uint32_t orx2(uint32_t a, uint32_t b, uint32_t t) {
    uint32_t r; asm("lop3.b32 %0, %1, %2, %3, 0x7E;" : "=r"(r) : "r"(a), "r"(b), "r"(t)); return r;
}
__device__ __forceinline__ float ex2(float x) { float r; asm("ex2.approx.ftz.f32 %0, %1;" : "=f"(r) : "f"(x)); return r; }
__device__ __forceinline__ void ldsm4t(uint32_t (&r)[4], uint32_t a) {
    asm volatile("ldmatrix.sync.aligned.m8n8.x4.trans.shared.b16 {%0,%1,%2,%3}, [%4];"
                 : "=r"(r[0]), "=r"(r[1]), "=r"(r[2]), "=r"(r[3]) : "r"(a) : "memory");
}
__device__ __forceinline__ void ldsm4(uint32_t (&r)[4], uint32_t a) {
    asm volatile("ldmatrix.sync.aligned.m8n8.x4.shared.b16 {%0,%1,%2,%3}, [%4];"
                 : "=r"(r[0]), "=r"(r[1]), "=r"(r[2]), "=r"(r[3]) : "r"(a) : "memory");
}
__device__ __forceinline__ void stsm4t(uint32_t a, uint32_t r0, uint32_t r1, uint32_t r2, uint32_t r3) {
    asm volatile("stmatrix.sync.aligned.m8n8.x4.trans.shared.b16 [%0], {%1,%2,%3,%4};"
                 ::"r"(a), "r"(r0), "r"(r1), "r"(r2), "r"(r3) : "memory");
}
__device__ __forceinline__ void stsm4(uint32_t a, uint32_t r0, uint32_t r1, uint32_t r2, uint32_t r3) {
    asm volatile("stmatrix.sync.aligned.m8n8.x4.shared.b16 [%0], {%1,%2,%3,%4};"
                 ::"r"(a), "r"(r0), "r"(r1), "r"(r2), "r"(r3) : "memory");
}
__device__ __forceinline__ void mma16816(float* c, uint32_t a0, uint32_t a1, uint32_t a2, uint32_t a3, uint32_t b0, uint32_t b1) {
    asm volatile("mma.sync.aligned.m16n8k16.row.col.f32.bf16.bf16.f32 {%0,%1,%2,%3}, {%4,%5,%6,%7}, {%8,%9}, {%0,%1,%2,%3};"
                 : "+f"(c[0]), "+f"(c[1]), "+f"(c[2]), "+f"(c[3]) : "r"(a0), "r"(a1), "r"(a2), "r"(a3), "r"(b0), "r"(b1));
}
__device__ __forceinline__ void mma1688(float* c, uint32_t a0, uint32_t a1, uint32_t b0) {
    asm volatile("mma.sync.aligned.m16n8k8.row.col.f32.bf16.bf16.f32 {%0,%1,%2,%3}, {%4,%5}, {%6}, {%0,%1,%2,%3};"
                 : "+f"(c[0]), "+f"(c[1]), "+f"(c[2]), "+f"(c[3]) : "r"(a0), "r"(a1), "r"(b0));
}
__device__ __forceinline__ void sts128(uint32_t a, float x, float y, float z, float w) {
    asm volatile("st.shared.v4.f32 [%0], {%1,%2,%3,%4};" ::"r"(a), "f"(x), "f"(y), "f"(z), "f"(w) : "memory");
}
__device__ __forceinline__ void sts64(uint32_t a, float x, float y) {
    asm volatile("st.shared.v2.f32 [%0], {%1,%2};" ::"r"(a), "f"(x), "f"(y) : "memory");
}
__device__ __forceinline__ void sts32(uint32_t a, uint32_t x) { asm volatile("st.shared.b32 [%0], %1;" ::"r"(a), "r"(x) : "memory"); }
__device__ __forceinline__ void sts128u(uint32_t a, uint4 v) {
    asm volatile("st.shared.v4.b32 [%0], {%1,%2,%3,%4};" ::"r"(a), "r"(v.x), "r"(v.y), "r"(v.z), "r"(v.w) : "memory");
}
__device__ __forceinline__ float4 lds128(uint32_t a) {
    float4 v; asm volatile("ld.shared.v4.f32 {%0,%1,%2,%3}, [%4];" : "=f"(v.x), "=f"(v.y), "=f"(v.z), "=f"(v.w) : "r"(a) : "memory"); return v;
}
__device__ __forceinline__ uint4 lds128u(uint32_t a) {
    uint4 v; asm volatile("ld.shared.v4.b32 {%0,%1,%2,%3}, [%4];" : "=r"(v.x), "=r"(v.y), "=r"(v.z), "=r"(v.w) : "r"(a) : "memory"); return v;
}
__device__ __forceinline__ uint4 lds128v(uint32_t a) {
    uint4 v; asm volatile("ld.volatile.shared.v4.b32 {%0,%1,%2,%3}, [%4];" : "=r"(v.x), "=r"(v.y), "=r"(v.z), "=r"(v.w) : "r"(a) : "memory"); return v;
}
__device__ __forceinline__ void sts64u(uint32_t a, uint2 v) { asm volatile("st.shared.v2.b32 [%0], {%1,%2};" ::"r"(a), "r"(v.x), "r"(v.y) : "memory"); }
__device__ __forceinline__ uint2 lds64u(uint32_t a) {
    uint2 v; asm volatile("ld.shared.v2.b32 {%0,%1}, [%2];" : "=r"(v.x), "=r"(v.y) : "r"(a) : "memory"); return v;
}
__device__ __forceinline__ float2 lds64(uint32_t a) {
    float2 v; asm volatile("ld.shared.v2.f32 {%0,%1}, [%2];" : "=f"(v.x), "=f"(v.y) : "r"(a) : "memory"); return v;
}
__device__ __forceinline__ uint2 ldg_rlx64(const void* p) {
    uint2 v; asm volatile("ld.relaxed.gpu.global.v2.b32 {%0,%1}, [%2];" : "=r"(v.x), "=r"(v.y) : "l"(p) : "memory"); return v;
}
__device__ __forceinline__ uint4 ldg_rlx128(const void* p) {
    uint4 v; asm volatile("ld.relaxed.gpu.global.v4.b32 {%0,%1,%2,%3}, [%4];" : "=r"(v.x), "=r"(v.y), "=r"(v.z), "=r"(v.w) : "l"(p) : "memory"); return v;
}
__device__ __forceinline__ void stg_rlx64(void* p, uint32_t x, uint32_t y) {
    asm volatile("st.relaxed.gpu.global.v2.b32 [%0], {%1,%2};" ::"l"(p), "r"(x), "r"(y) : "memory");
}
__device__ __forceinline__ void stg_rlx128(void* p, uint32_t x, uint32_t y, uint32_t z, uint32_t w) {
    asm volatile("st.relaxed.gpu.global.v4.b32 [%0], {%1,%2,%3,%4};" ::"l"(p), "r"(x), "r"(y), "r"(z), "r"(w) : "memory");
}
__device__ __forceinline__ uint32_t ldg_rlx32(const void* p) {
    uint32_t v; asm volatile("ld.relaxed.gpu.global.b32 %0, [%1];" : "=r"(v) : "l"(p) : "memory"); return v;
}
__device__ __forceinline__ void stg128(void* p, uint32_t x, uint32_t y, uint32_t z, uint32_t w) {
    asm volatile("st.global.v4.b32 [%0], {%1,%2,%3,%4};" ::"l"(p), "r"(x), "r"(y), "r"(z), "r"(w) : "memory");
}
__device__ __forceinline__ uint32_t ld_acquire(const unsigned* p) {
    uint32_t v; asm volatile("ld.acquire.gpu.global.u32 %0, [%1];" : "=r"(v) : "l"(p) : "memory"); return v;
}
__device__ __forceinline__ void red_add_u32(unsigned* p, uint32_t v) {
    asm volatile("red.relaxed.gpu.global.add.u32 [%0], %1;" ::"l"(p), "r"(v) : "memory");
}
__device__ __forceinline__ void wait_counter(const unsigned* p, uint32_t target) {
    uint32_t n = 0;
    while (ld_acquire(p) < target) { if (++n > SPIN_LIMIT) __trap(); }
}

__device__ __forceinline__ void wg_fence() { asm volatile("wgmma.fence.sync.aligned;" ::: "memory"); }
__device__ __forceinline__ void wg_commit() { asm volatile("wgmma.commit_group.sync.aligned;" ::: "memory"); }
template <int N> __device__ __forceinline__ void wg_wait() { asm volatile("wgmma.wait_group.sync.aligned %0;" ::"n"(N) : "memory"); }
__host__ __device__ constexpr uint64_t mkdesc(uint32_t addr, uint32_t lbo, uint32_t sbo, uint32_t swz) {
    return (uint64_t)((addr & 0x3FFFF) >> 4) | ((uint64_t)(lbo >> 4) << 16) | ((uint64_t)(sbo >> 4) << 32) | ((uint64_t)swz << 62);
}
#define F4(d, o) "+f"(d[o]), "+f"(d[o + 1]), "+f"(d[o + 2]), "+f"(d[o + 3])
template <int SC> __device__ __forceinline__ void wg_rs32(float (&d)[16], const uint32_t (&a)[4], uint64_t db) {
    asm volatile("wgmma.mma_async.sync.aligned.m64n32k16.f32.bf16.bf16 "
                 "{%0,%1,%2,%3,%4,%5,%6,%7,%8,%9,%10,%11,%12,%13,%14,%15}, {%16,%17,%18,%19}, %20, %21, 1, 1, 0;"
                 : F4(d, 0), F4(d, 4), F4(d, 8), F4(d, 12)
                 : "r"(a[0]), "r"(a[1]), "r"(a[2]), "r"(a[3]), "l"(db), "n"(SC));
}
template <int SC> __device__ __forceinline__ void wg_rs40(float (&d)[20], const uint32_t (&a)[4], uint64_t db) {
    asm volatile("wgmma.mma_async.sync.aligned.m64n40k16.f32.bf16.bf16 "
                 "{%0,%1,%2,%3,%4,%5,%6,%7,%8,%9,%10,%11,%12,%13,%14,%15,%16,%17,%18,%19}, {%20,%21,%22,%23}, %24, %25, 1, 1, 0;"
                 : F4(d, 0), F4(d, 4), F4(d, 8), F4(d, 12), F4(d, 16)
                 : "r"(a[0]), "r"(a[1]), "r"(a[2]), "r"(a[3]), "l"(db), "n"(SC));
}
template <int SC> __device__ __forceinline__ void wg_ss40(float (&d)[20], uint64_t da, uint64_t db) {
    asm volatile("wgmma.mma_async.sync.aligned.m64n40k16.f32.bf16.bf16 "
                 "{%0,%1,%2,%3,%4,%5,%6,%7,%8,%9,%10,%11,%12,%13,%14,%15,%16,%17,%18,%19}, %20, %21, %22, 1, 1, 1, 0;"
                 : F4(d, 0), F4(d, 4), F4(d, 8), F4(d, 12), F4(d, 16)
                 : "l"(da), "l"(db), "n"(SC));
}
template <int SC> __device__ __forceinline__ void wg_ss8(float (&d)[4], uint64_t da, uint64_t db) {
    asm volatile("wgmma.mma_async.sync.aligned.m64n8k16.f32.bf16.bf16 {%0,%1,%2,%3}, %4, %5, %6, 1, 1, 1, 1;"
                 : F4(d, 0) : "l"(da), "l"(db), "n"(SC));
}

constexpr int DBG_N = 11;
#define LT(st, k, v) do {} while (0)
#define TSI(st) do {} while (0)
#define TS(k) do {} while (0)
#define TSV(k, v) do {} while (0)
#define TSDUMP() do {} while (0)
#define GT(k) do {} while (0)

__device__ __align__(256) uint4 g_fy[2048 * 128];

constexpr uint32_t FG_SIZE = 2 * 32768 + 36864;
constexpr uint32_t FT_F16 = 2 * FG_SIZE, FT_B1F = FT_F16 + 2048, FT_B1I = FT_B1F + 2048, FT_C = FT_B1I + 2048, FT_A8 = FT_C + 2048,
                   FT_TWC = FT_A8 + 512, FT_TWB = FT_TWC + 8192, FT_BAR = FT_TWB + 8192, FFT_SMEM = FT_BAR + 256;
#define FW_PF 2
struct FftMaps { CUtensorMap x, y, o, y2, wr, wi; const unsigned char* w[3]; };

__device__ __forceinline__ float2 wroot(int e) {
    float s, c; sincospif((float)(e & 2047) * (-1.f / 1024.f), &s, &c); return make_float2(c, s);
}
__device__ __forceinline__ uint4 afrag(float2 a, float2 b) {
    return make_uint4(pack_bf16(a.x, -a.y), pack_bf16(a.y, a.x), pack_bf16(b.x, -b.y), pack_bf16(b.y, b.x));
}
__device__ __forceinline__ uint4 conjfrag(uint4 v) { return make_uint4(v.x ^ 0x80000000u, v.y ^ 0x8000u, v.z ^ 0x80000000u, v.w ^ 0x8000u); }
__device__ __forceinline__ uint4 negfrag(uint4 v) { return make_uint4(v.x ^ 0x80008000u, v.y ^ 0x80008000u, v.z ^ 0x80008000u, v.w ^ 0x80008000u); }
__device__ __forceinline__ uint32_t comp(const uint4& v, int i) { return i == 0 ? v.x : i == 1 ? v.y : i == 2 ? v.z : v.w; }
__device__ __forceinline__ void setcomp(uint4& v, int i, uint32_t x) { if (i == 0) v.x = x; else if (i == 1) v.y = x; else if (i == 2) v.z = x; else v.w = x; }
__device__ __forceinline__ float2 cmul(float2 a, float2 b) { return make_float2(a.x * b.x - a.y * b.y, a.x * b.y + a.y * b.x); }
__device__ __forceinline__ float2 cmulc(float2 a, float2 b) { return make_float2(a.x * b.x + a.y * b.y, a.y * b.x - a.x * b.y); }

__device__ __forceinline__ uint32_t pack_h2(float2 a) { uint32_t r; asm("cvt.rn.f16x2.f32 %0, %1, %2;" : "=r"(r) : "f"(a.y), "f"(a.x)); return r; }
__device__ __forceinline__ float2 unpack_h2(uint32_t v) {
    float2 r; asm("{\n.reg .b16 l, h;\nmov.b32 {l, h}, %2;\ncvt.f32.f16 %0, l;\ncvt.f32.f16 %1, h;\n}" : "=f"(r.x), "=f"(r.y) : "r"(v)); return r;
}
__device__ __forceinline__ void fft_tables(uint32_t tb, int tid, int nthr) {
    for (int i = tid; i < 128; i += nthr) {
        const int lane = i & 31, q = i >> 5, g = lane >> 2, t = lane & 3, o = 8 * (q >> 1) + g, in = 8 * (q & 1) + 2 * t;
        sts128u(tb + FT_F16 + i * 16, afrag(wroot(128 * o * in), wroot(128 * o * (in + 1))));
        sts128u(tb + FT_B1F + i * 16, afrag(wroot(64 * (1 + 2 * o) * in), wroot(64 * (1 + 2 * o) * (in + 1))));
        sts128u(tb + FT_B1I + i * 16, afrag(wroot(-64 * o * (1 + 2 * in)), wroot(-64 * o * (3 + 2 * in))));
        uint4 v;
        for (int r = 0; r < 4; r++) {
            const float2 a = wroot(128 * (4 * r + t) * (4 * q + (g >> 1)));
            setcomp(v, r, (g & 1) ? pack_bf16(a.y, a.x) : pack_bf16(a.x, -a.y));
        }
        sts128u(tb + FT_C + i * 16, v);
        if (q == 0) sts128u(tb + FT_A8 + lane * 16, afrag(wroot(256 * g * 2 * t), wroot(256 * g * (2 * t + 1))));
    }
    for (int i = tid; i < 512; i += nthr) {
        const int lane = i & 31, r = (i >> 5) & 3, phi = 8 * (i >> 7) + (lane >> 2), c = 4 * r + (lane & 3);
        const float2 a = wroot(4 * c * phi), b = wroot(2 * (phi + 32 * c));
        constexpr float SC = 1.f / (2.f * 2048.f * 512.f);
        sts128(tb + FT_TWC + i * 16, a.x * SC, a.y * SC, b.x, b.y);
    }
    for (int i = tid; i < 512; i += nthr) {
        const int lane = i & 31, r = (i >> 5) & 3, fa = (i >> 7) & 1, hf = i >> 8, c = 8 * (lane & 1) + r;
        const int p0 = fa + 2 * (lane >> 2), p1 = p0 + 16, s0 = (hf && p0) ? 32 - p0 : p0, s1 = hf ? 32 - p1 : p1;
        sts128u(tb + FT_TWB + i * 16, make_uint4(pack_h2(wroot(4 * c * s0)), pack_h2(wroot(4 * (c + 4) * s0)),
                                                 pack_h2(wroot(4 * c * s1)), pack_h2(wroot(4 * (c + 4) * s1))));
    }
}

template <bool TW>
__device__ __forceinline__ void dft16(uint4 (&out)[4], const uint4 (&in)[4], const uint4 (&m)[4], const uint4 (&tw)[4]) {
#pragma unroll
    for (int i = 0; i < 4; i++)
#pragma unroll
        for (int mt = 0; mt < 2; mt++) {
            float c[4] = {0.f, 0.f, 0.f, 0.f};
            mma16816(c, m[2 * mt].x, m[2 * mt].y, m[2 * mt].z, m[2 * mt].w, comp(in[0], i), comp(in[1], i));
            mma16816(c, m[2 * mt + 1].x, m[2 * mt + 1].y, m[2 * mt + 1].z, m[2 * mt + 1].w, comp(in[2], i), comp(in[3], i));
            if (TW) {
                const float2 a = cmul(make_float2(c[0], c[2]), unpack_h2(comp(tw[i], 2 * mt))), b = cmul(make_float2(c[1], c[3]), unpack_h2(comp(tw[i], 2 * mt + 1)));
                setcomp(out[2 * mt], i, pack_bf16(a.x, a.y));
                setcomp(out[2 * mt + 1], i, pack_bf16(b.x, b.y));
            } else {
                setcomp(out[2 * mt], i, pack_bf16(c[0], c[2]));
                setcomp(out[2 * mt + 1], i, pack_bf16(c[1], c[3]));
            }
        }
}
__device__ __forceinline__ void tma_ld4(uint32_t dst, const CUtensorMap* m, int c0, int c1, uint32_t bar) {
    asm volatile("cp.async.bulk.tensor.4d.shared::cluster.global.mbarrier::complete_tx::bytes [%0], [%1, {%3, %4, %5, %5}], [%2];"
                 ::"r"(dst), "l"(m), "r"(bar), "r"(c0), "r"(c1), "r"(0) : "memory");
}
__device__ __forceinline__ void tma_st4(uint32_t src, const CUtensorMap* m, int c0, int c1) {
    asm volatile("cp.async.bulk.tensor.4d.global.shared::cta.bulk_group [%1, {%2, %3, %4, %4}], [%0];" ::"r"(src), "l"(m), "r"(c0), "r"(c1), "r"(0) : "memory");
}
__device__ __forceinline__ void tma_ld3(uint32_t dst, const CUtensorMap* m, int c0, int c1, uint32_t bar) {
    asm volatile("cp.async.bulk.tensor.3d.shared::cluster.global.mbarrier::complete_tx::bytes [%0], [%1, {%3, %4, %5}], [%2];"
                 ::"r"(dst), "l"(m), "r"(bar), "r"(c0), "r"(c1), "r"(0) : "memory");
}
__device__ __forceinline__ void tma_st3(uint32_t src, const CUtensorMap* m, int c0, int c1) {
    asm volatile("cp.async.bulk.tensor.3d.global.shared::cta.bulk_group [%1, {%2, %3, %4}], [%0];" ::"r"(src), "l"(m), "r"(c0), "r"(c1), "r"(0) : "memory");
}
__device__ __forceinline__ void bulk_commit() { asm volatile("cp.async.bulk.commit_group;" ::: "memory"); }
__device__ __forceinline__ void bulk_wait_read() { asm volatile("cp.async.bulk.wait_group.read 0;" ::: "memory"); }
__device__ __forceinline__ void bulk_wait_all() { asm volatile("cp.async.bulk.wait_group 0;" ::: "memory"); }

__device__ __forceinline__ float2 wroot_fast(int e) {
    float s, c; __sincosf((float)(((e + 1024) & 2047) - 1024) * (-3.14159265358979f / 1024.f), &s, &c); return make_float2(c, s);
}
template <bool INV, int NT>
__device__ __forceinline__ void fft_col(int s2, int t0, const CUtensorMap* src, const CUtensorMap* dst, uint32_t gb, uint32_t mb,
                                        int w, int lane, int bar) {
    const int g = lane >> 2, t = lane & 3;
    const bool lead = w == 4 && lane == 0;
    if (NT > 1 && lead)
        for (int i = 0; i < 2; i++) { mbar_expect_tx(mb + 8 * i, 32768); tma_ld4(gb + i * 32768, src, (t0 + i) * 64, s2, mb + 8 * i); }
    uint4 f[4], m[2][4];
#pragma unroll
    for (int i = 0; i < 4; i++) {
        const int o = 8 * (i >> 1) + g, in = 8 * (i & 1) + 2 * t, sg = INV ? -128 : 128;
        f[i] = afrag(wroot_fast(sg * o * in), wroot_fast(sg * o * (in + 1)));
#pragma unroll
        for (int q = 0; q < 2; q++) {
            const int z = 2 * w + q;
            m[q][i] = INV ? afrag(wroot_fast(-(8 * o + s2) * (z + 16 * in)), wroot_fast(-(8 * o + s2) * (z + 16 * in + 16)))
                          : afrag(wroot_fast((z + 16 * o) * (8 * in + s2)), wroot_fast((z + 16 * o) * (8 * in + 8 + s2)));
        }
    }
    const uint32_t r1 = (32 * w + 2 * t) * 128 + ((g ^ (2 * t)) << 4);
    const uint32_t w1 = (32 * w + g) * 128 + (((2 * t) ^ (((w & 3) << 1) | (g & 1))) << 4);
    const uint32_t r2 = (32 * t + 2 * w) * 128 + ((g ^ (2 * t)) << 4);
    const uint32_t w2 = (32 * w + g) * 128 + (((2 * t) ^ g) << 4);
    int bi = 0, ph = 0;
#pragma unroll 1
    for (int it = 0; it < NT; it++) {
        const uint32_t buf = gb + bi * 32768;
        mbar_wait(mb + 8 * bi, ph);
        uint4 in[2][4], out[4];
#pragma unroll
        for (int q = 0; q < 2; q++)
#pragma unroll
            for (int i = 0; i < 4; i++) in[q][i] = lds128u(buf + (r1 ^ ((i & 1) * 0x90)) + (i >> 1) * 1024 + q * 2048);
        __syncwarp();
#pragma unroll
        for (int q = 0; q < 2; q++) {
            if (INV) dft16<false>(out, in[q], m[q], f); else dft16<false>(out, in[q], f, f);
#pragma unroll
            for (int i = 0; i < 4; i++) sts128u(buf + (w1 ^ ((i & 1) << 4)) + (i >> 1) * 1024 + q * 2048, out[i]);
        }
        bar_sync(bar, 256);
#pragma unroll
        for (int q = 0; q < 2; q++)
#pragma unroll
            for (int i = 0; i < 4; i++) in[q][i] = lds128u(buf + (r2 ^ (q * 0x90)) + (i & 1) * 2048 + (i >> 1) * 16384);
        const int bn = bi == 0 ? 2 : bi - 1;
        if (lead && it < NT - 2) { bulk_wait_read(); mbar_expect_tx(mb + 8 * bn, 32768); tma_ld4(gb + bn * 32768, src, (t0 + it + 2) * 64, s2, mb + 8 * bn); }
        bar_sync(bar, 256);
#pragma unroll
        for (int q = 0; q < 2; q++) {
            if (INV) dft16<false>(out, in[q], f, f); else dft16<false>(out, in[q], m[q], f);
#pragma unroll
            for (int i = 0; i < 4; i++) sts128u(buf + (w2 ^ ((i & 1) << 4)) + (i >> 1) * 1024 + q * 2048, out[i]);
        }
        fence_async_smem();
        bar_sync(bar, 256);
        if (NT > 1 && lead) { tma_st4(buf, dst, (t0 + it) * 64, s2); bulk_commit(); }
        if (++bi == 3) { bi = 0; ph ^= 1; }
    }
    if (NT > 1 && lead) bulk_wait_read();
}

__device__ __forceinline__ float ldw(uint32_t a) {
    uint16_t v; asm volatile("ld.shared.u16 %0, [%1];" : "=h"(v) : "r"(a) : "memory");
    return __uint_as_float((uint32_t)v << 16);
}
__device__ __forceinline__ void fft_mid(int grp, const FftMaps& fm, uint32_t tb,
                                        uint32_t gb, uint32_t mb, uint32_t& cnt, int w, int lane, int bar) {
    const int g = lane >> 2, t = lane & 3;
    const bool lead = w == 4 && lane == 0;
    const uint32_t wb = gb + 65536;
#define MID_LOAD(k, c)                                                                                                  \
    { mbar_expect_tx(mb + 8 * ((c) & 1), 32768);                                                                        \
      tma_ld3(gb + ((c) & 1) * 32768, &fm.y2, 0, (k) * 8, mb + 8 * ((c) & 1));                                          \
      tma_ld3(gb + ((c) & 1) * 32768 + 16384, &fm.y2, 0, ((256 - (k)) & 255) * 8, mb + 8 * ((c) & 1)); }
#define MID_LOADW(k)                                                                                                    \
    { mbar_expect_tx(mb + 16, 36864);                                                                                   \
      tma_ld3(wb, &fm.wr, (k) * 513 & ~7, 0, mb + 16); tma_ld3(wb + 9216, &fm.wi, (k) * 513 & ~7, 0, mb + 16);          \
      tma_ld3(wb + 18432, &fm.wr, ((256 - (k)) & 255) * 513 & ~7, 0, mb + 16); tma_ld3(wb + 27648, &fm.wi, ((256 - (k)) & 255) * 513 & ~7, 0, mb + 16); }
    if (lead) { MID_LOAD(grp, cnt); MID_LOADW(grp); }
    const int hB = w >> 2, faB = (w >> 1) & 1, xB = faB;
    const int phi = 8 * (w & 3) + g;
    const uint32_t rA = (8 * w + 2 * t) * 128 + ((g ^ (2 * t)) << 4);
    const uint32_t wA = (8 * w + g) * 128 + (((2 * t) ^ ((g & 1) | ((w & 3) << 1))) << 4);
    const uint32_t oB = (w >> 1) * 8192 + (w & 1) * 512;
    const uint32_t rB = oB + (8 * t + (g >> 2)) * 128 + (((g & 3) ^ ((g >> 2) | (t << 1)) ^ xB) << 4);
    const uint32_t wB = oB + (8 * (g >> 1) + (t >> 1)) * 128 + (((((g & 1) << 2) | (2 * (t & 1))) ^ ((t >> 1) | ((g >> 1) << 1)) ^ xB) << 4);
    const uint32_t wBi = oB + (8 * (g >> 1) + (t >> 1)) * 128 + (((((g & 1) << 2) | (2 * (t & 1))) ^ ((t >> 1) | ((w & 1) << 2))) << 4);
    const int hC = (lane >> 3) & 1, pr = 8 * (w & 3) + (lane & 7), pc = hC ? (32 - pr) & 31 : pr;
    const uint32_t aC = hC * 16384 + (pc & 1) * 8192 + (pc >> 2) * 1024 + (((((pc & 2) << 1) | (lane >> 4)) ^ (((pc >> 2) & 3) << 1) ^ (pc & 1)) << 4);
    const uint32_t g0 = wb + (t >> 1) * 144 + (32 * (t & 1) + phi) * 2, g1 = wb + 18432 + (7 - (t >> 1)) * 144 + (64 - 32 * (t & 1) - phi) * 2;
    const uint32_t wAo = (8 * w + g) * 128 + (((2 * t) ^ g) << 4);
    uint32_t wph = 0;
#pragma unroll 1
    for (int k1 = grp; k1 < 129; k1 += 8, cnt++, wph ^= 1) {
        const uint32_t buf = gb + (cnt & 1) * 32768;
        uint4 in[2][4], m[4], out[4];
        m[0] = m[1] = m[2] = lds128u(tb + FT_A8 + lane * 16);
        m[3] = negfrag(m[0]);
        mbar_wait(mb + 8 * (cnt & 1), (cnt >> 1) & 1);
#pragma unroll
        for (int q = 0; q < 2; q++)
#pragma unroll
            for (int i = 0; i < 4; i++) in[q][i] = lds128u(buf + (rA ^ ((i & 1) * 0x90)) + (i >> 1) * 8192 + q * 16384);
        __syncwarp();
#pragma unroll
        for (int q = 0; q < 2; q++) {
            dft16<false>(out, in[q], m, m);
#pragma unroll
            for (int i = 0; i < 4; i++) sts128u(buf + (wA ^ (((i ^ (i >> 1)) & 1) << 4)) + (i >> 1) * 8192 + q * 16384, out[i]);
        }
        {
            uint4 tw[4];
#pragma unroll
            for (int i = 0; i < 4; i++) {
                m[i] = lds128u(tb + (faB ? FT_B1F : FT_F16) + i * 512 + lane * 16);
                if (hB) { m[i].y ^= 0x80008000u; m[i].w ^= 0x80008000u; }
                tw[i] = lds128u(tb + FT_TWB + (w >> 1) * 2048 + i * 512 + lane * 16);
            }
            bar_sync(bar, 256);
#pragma unroll
            for (int q = 0; q < 2; q++)
#pragma unroll
                for (int i = 0; i < 4; i++) in[q][i] = lds128u(buf + (rB ^ ((i & 1) << 6)) + (i >> 1) * 4096 + q * 256);
            __syncwarp();
#pragma unroll
            for (int q = 0; q < 2; q++) {
                dft16<true>(out, in[q], m, tw);
#pragma unroll
                for (int i = 0; i < 4; i++) sts128u(buf + (wB ^ ((i & 1) << 4)) + (i >> 1) * 4096 + q * 256, out[i]);
            }
        }
        {
            const uint32_t cjm = (g & 1) ? 0x8000u : 0x80000000u;
            float4 tw[4];
#pragma unroll
            for (int i = 0; i < 4; i++) { m[i] = lds128u(tb + FT_C + i * 512 + lane * 16); tw[i] = lds128(tb + FT_TWC + ((w & 3) * 4 + i) * 512 + lane * 16); }
            if (lead && k1 + 8 < 129) { bulk_wait_read(); MID_LOAD(k1 + 8, cnt + 1); }
            __syncwarp();
            mbar_wait(mb + 16, wph);
            const uint32_t o0 = (k1 & 7) * 2, o1 = (-k1 & 7) * 2;
            if (w == 1 && lane < 16) {
                const int k2 = lane & 7, k2p = k1 ? 7 - k2 : (8 - k2) & 7;
                const uint32_t p0 = wb + (lane >> 3) * 9216 + k2 * 1152 + o0, p1 = wb + 18432 + (lane >> 3) * 9216 + k2p * 1152 + o1;
                const float sg = lane < 8 ? 0.5f : -0.5f;
                const uint32_t v = pack_bf16(0.5f * ldw(p0) + sg * ldw(p1), 0.5f * ldw(p1 + 1136) + sg * ldw(p0 + 1136));
                asm volatile("st.shared.u16 [%0], %1;" ::"r"(p0), "h"((uint16_t)v) : "memory");
                asm volatile("st.shared.u16 [%0], %1;" ::"r"(p1 + 1136), "h"((uint16_t)(v >> 16)) : "memory");
                fence_async_smem();
            }
            bar_sync(bar, 256);
#define FFT_CU 1
            constexpr int CU = FFT_CU;
#pragma unroll CU
            for (int q = 0; q < 4; q++) {
                const int k2 = 4 * (w >> 2) + q, k2p = k1 ? 7 - k2 : (8 - k2) & 7, kr = hC ? k2p : k2;
                const uint32_t a0 = buf + (aC ^ ((kr & 1) << 4)) + kr * 128;
                const uint32_t r0 = g0 + k2 * 1152 + o0, r1 = g1 + k2p * 1152 + o1;
                uint32_t x[4], y[4];
                ldsm4(x, a0); ldsm4(y, a0 ^ 32);
                float c[4][4];
#pragma unroll
                for (int i = 0; i < 4; i++) { c[i][0] = c[i][1] = c[i][2] = c[i][3] = 0.f; mma16816(c[i], x[0], x[1], x[2], x[3], m[i].x, m[i].y); }
#pragma unroll
                for (int i = 0; i < 4; i++) mma16816(c[i], y[0], y[1], y[2], y[3], m[i].z, m[i].w);
#pragma unroll
                for (int i = 0; i < 4; i++) {
                    const float2 ga = make_float2(ldw(r0 + i * 288), ldw(r0 + 9216 + i * 288));
                    const float2 gc = make_float2(ldw(r1 - i * 288), ldw(r1 + 9216 - i * 288));
                    const float tc = tw[i].z, ts = tw[i].w;
                    const float* z = c[i];
                    const float2 S = make_float2(ga.x + gc.x, ga.y - gc.y), D = make_float2(ga.x - gc.x, ga.y + gc.y);
                    const float2 u = make_float2(ts * z[0] - tc * z[3], ts * z[1] + tc * z[2]), v = make_float2(ts * z[2] - tc * z[1], ts * z[3] + tc * z[0]);
                    uint32_t* o = (i < 2 ? x : y) + 2 * (i & 1);
                    o[0] = pack_bf16(fmaf(S.x, z[0], fmaf(-S.y, z[1], fmaf(D.x, u.x, -D.y * u.y))), fmaf(S.x, z[1], fmaf(S.y, z[0], fmaf(D.x, u.y, D.y * u.x))));
                    o[1] = pack_bf16(fmaf(S.x, z[2], fmaf(-S.y, z[3], fmaf(-D.x, v.x, D.y * v.y))), fmaf(S.x, z[3], fmaf(S.y, z[2], fmaf(-D.x, v.y, -D.y * v.x))));
                }
#pragma unroll
                for (int i = 0; i < 4; i++) { c[i][0] = c[i][1] = c[i][2] = c[i][3] = 0.f; mma16816(c[i], x[0], x[1], x[2], x[3], m[i].x ^ cjm, m[i].y ^ cjm); }
#pragma unroll
                for (int i = 0; i < 4; i++) mma16816(c[i], y[0], y[1], y[2], y[3], m[i].z ^ cjm, m[i].w ^ cjm);
#pragma unroll
                for (int i = 0; i < 4; i++) {
                    uint32_t* o = (i < 2 ? x : y) + 2 * (i & 1);
                    o[0] = pack_bf16(c[i][0] * tw[i].x + c[i][1] * tw[i].y, c[i][1] * tw[i].x - c[i][0] * tw[i].y);
                    o[1] = pack_bf16(c[i][2] * tw[i].x + c[i][3] * tw[i].y, c[i][2] * tw[i].y - c[i][3] * tw[i].x);
                }
                stsm4(a0, x[0], x[1], x[2], x[3]);
                stsm4(a0 ^ 32, y[0], y[1], y[2], y[3]);
            }
        }
#pragma unroll
        for (int i = 0; i < 4; i++) { m[i] = lds128u(tb + (faB ? FT_B1I : FT_F16) + i * 512 + lane * 16); if (!faB) m[i] = conjfrag(m[i]); }
        bar_sync(bar, 256);
        if (lead && k1 + 8 < 129) MID_LOADW(k1 + 8);
        if (w == 4 && k1 < 8 * FW_PF && lane < 32 / FW_PF) {
            const unsigned char* p = fm.w[grp & 1] + (size_t)((grp >> 1) * 32 + (k1 >> 3) * (32 / FW_PF) + lane) * 16416;
            asm volatile("cp.async.bulk.prefetch.L2.global [%0], %1;" ::"l"(p), "r"(16416) : "memory");
        }
        __syncwarp();
#pragma unroll
        for (int q = 0; q < 2; q++)
#pragma unroll
            for (int i = 0; i < 4; i++) in[q][i] = lds128u(buf + (rB ^ ((i & 1) << 6)) + (i >> 1) * 4096 + q * 256);
        __syncwarp();
#pragma unroll
        for (int q = 0; q < 2; q++) {
            dft16<false>(out, in[q], m, m);
#pragma unroll
            for (int i = 0; i < 4; i++) sts128u(buf + (wBi ^ ((i & 1) << 4) ^ (q << 5)) + (i >> 1) * 4096 + q * 256, out[i]);
        }
        m[0] = m[1] = m[2] = conjfrag(lds128u(tb + FT_A8 + lane * 16));
        m[3] = negfrag(m[0]);
        bar_sync(bar, 256);
#pragma unroll
        for (int q = 0; q < 2; q++)
#pragma unroll
            for (int i = 0; i < 4; i++) in[q][i] = lds128u(buf + (rA ^ ((i & 1) * 0x90)) + (i >> 1) * 8192 + q * 16384);
        __syncwarp();
#pragma unroll
        for (int q = 0; q < 2; q++) {
            dft16<false>(out, in[q], m, m);
#pragma unroll
            for (int i = 0; i < 4; i++) sts128u(buf + (wAo ^ ((i & 1) << 4)) + (i >> 1) * 8192 + q * 16384, out[i]);
        }
        fence_async_smem();
        bar_sync(bar, 256);
        if (lead) {
            tma_st3(buf, &fm.y2, 0, k1 * 8);
            if (k1 & 127) tma_st3(buf + 16384, &fm.y2, 0, (256 - k1) * 8);
            bulk_commit();
        }
    }
    if (lead) bulk_wait_all();
}

__device__ __align__(128) unsigned g_start;
__device__ __align__(128) unsigned g_fbar;
__device__ __align__(128) unsigned g_end;
__device__ __forceinline__ unsigned gbar_arrive(unsigned* c, unsigned inc, unsigned total, int lane) {
    unsigned v = 0;
    if (lane == 0) { asm volatile("fence.proxy.async;" ::: "memory"); fence_gpu(); v = atomicAdd(c, inc); }
    return (__shfl_sync(~0u, v, 0) & ~(total - 1)) + total;
}
__device__ __forceinline__ void gbar_wait(unsigned* c, unsigned target, unsigned ns) {
    uint32_t n = 0;
    while (__any_sync(~0u, (int)(ld_acquire(c) - target) < 0)) { if (ns) __nanosleep(ns); if (++n > SPIN_LIMIT) __trap(); }
    asm volatile("fence.proxy.async;" ::: "memory");
}
__device__ __noinline__ void fft_rest(int cta, const FftMaps& fm, uint32_t sb, uint32_t opt) {
    const int hi = __shfl_sync(~0u, threadIdx.x >> 8, 0), w = __shfl_sync(~0u, (threadIdx.x >> 5) & 7, 0), lane = threadIdx.x & 31;
    unsigned target = 0;
    if (w == 4) target = gbar_arrive(&g_start, 16, 256, lane);
    if (threadIdx.x < 32) mbar_init(sb + FT_BAR + 8 * threadIdx.x, 1);
    fft_tables(sb, threadIdx.x, 512);
    fence_async_smem();
    __syncthreads();
    const int grp = cta * 2 + hi, bar = 1 + hi;
    const uint32_t gb = sb + hi * FG_SIZE, mb = sb + FT_BAR + hi * 128;
    uint32_t cnt = 0;
    if (w == 4) gbar_wait(&g_start, target, 200);
    GT(1);
    fft_mid(grp, fm, sb, gb, mb, cnt, w, lane, bar);
    if (w == 4) gbar_wait(&g_fbar, gbar_arrive(&g_fbar, 1, 8, lane), 200);
    GT(2);
    fft_col<true, 16>(grp, 0, &fm.y, &fm.o, gb, mb + 64, w, lane, bar);
}

__device__ __align__(256) uint4 g_kvq[4 * 32 * 3 * 8 * 2 * 32];
__device__ __align__(256) uint2 g_alpha[2 * 32 * 3 * 8 * 2 * 32];
__device__ __align__(256) uint4 g_red[5 * 32768 / 16];
__device__ __align__(256) uint4 g_stamp[32];
__device__ __align__(256) uint4 g_qst[128 * 2];
__device__ __align__(256) bf16 g_ox[2048 * 4096];
struct Tune { uint32_t d_alpha, d_r, opt, d_q, d_v, spread, extra; };
#define OP_SPLIT 1
#define X_SEQ 24
#define QKW_POS 0
#define XO_POS 0
#define V_SEQ 28
#define X_HALF 0
#define V_KEEP 0
#define STAMP_V 1
#define EXP 0
#define FIN_BAR B_SRDY
#define V_LATE 0
#define R_SPLIT 1
#define PV_MODE 0
#define OPD_EARLY 1
constexpr int RA = 2;

constexpr uint32_t SM_BASE = 1024;
constexpr uint32_t O_WO = 0;
constexpr uint32_t O_WV = 65536;
constexpr uint32_t O_XB = 131072;
constexpr uint32_t O_MEM = O_XB + 16384;
constexpr uint32_t O_RECV = O_XB + 40960;
constexpr uint32_t O_KVQ = O_RECV + 12288;
constexpr uint32_t O_STG = O_KVQ + 18432;
constexpr uint32_t O_S = O_STG + 8192;
constexpr uint32_t O_P = O_S + 10240;
constexpr uint32_t O_O = O_P + 1536;
constexpr uint32_t O_DBG = O_O + 2048;
constexpr uint32_t O_F1 = 196608;
constexpr uint32_t O_VM = O_F1 + 32768;
constexpr uint32_t O_BAR = 232448 - 512;
constexpr uint32_t MAIN_SMEM = 232448;
static_assert(O_DBG + (DBG_TIMING ? (4 * DBG_N + 1) * 96 : 0) <= O_VM && FFT_SMEM <= MAIN_SMEM && O_VM + 2048 <= O_BAR, "smem");
constexpr int G_ST = 6;
enum { B_W = 0, B_WO = B_W + 12, B_F1, B_XP, B_XFULL, B_RFULL, B_AFULL, B_KVFULL, B_XF1, B_QST, B_RECV, B_GF = B_RECV + 6,
       B_QDONE = B_GF + G_ST, B_KDONE, B_XEMPTY, B_VA, B_X0, B_SRDY, B_OPDONE, B_QX, B_GE, B_XPE = B_GE + G_ST, B_QKW, B_MEM, B_COUNT };

constexpr float SM_SCALE_LOG2 = 0.08838834764831845f * 1.4426950408889634f;
constexpr float MASK_VAL = -1.0e9f / 0.08838834764831845f;

__device__ __forceinline__ uint32_t red_grp(int grp) { return (uint32_t)((grp >> 1) * 1024 + (grp & 1) * 256); }
__host__ __device__ constexpr uint32_t kb_off(int kb) { return (uint32_t)((kb >> 2) * 20480 + (kb & 3) * 1024); }
__host__ __device__ constexpr uint64_t xdesc(int ks) { return mkdesc(SM_BASE + O_XB + kb_off(ks >> 2) + (ks & 3) * 32, 16, 4096, 1); }

__device__ __forceinline__ void x_split(const float* d, uint32_t (&sn)[4], uint32_t (&kp)[4], int kh) {
#pragma unroll
    for (int i = 0; i < 4; i++) {
        const uint32_t lo = pack_bf16(d[2 * i], d[2 * i + 1]), hi = pack_bf16(d[8 + 2 * i], d[8 + 2 * i + 1]);
        sn[i] = kh ? lo : hi; kp[i] = kh ? hi : lo;
    }
}
__device__ __forceinline__ void x_send(int R, const uint32_t (&sn)[4], int sg, int tid, uint32_t sb, uint32_t mate) {
    const uint32_t par = sg & 1;
    const uint32_t bar = O_BAR + 8 * (B_RECV + R * 2) + 8 * par;
    if (tid == 0) mbar_expect_tx(sb + bar, 2048);
    asm volatile("st.async.shared::cluster.mbarrier::complete_tx::bytes.v4.b32 [%0], {%1,%2,%3,%4}, [%5];"
                 ::"r"(mate + O_RECV + (par * 3 + R) * 2048 + tid * 16), "r"(sn[0]), "r"(sn[1]), "r"(sn[2]), "r"(sn[3]), "r"(mate + bar) : "memory");
}
__device__ __forceinline__ void x_wait(int R, int sg, uint32_t sb) {
    mbar_wait_cluster(sb + O_BAR + 8 * (B_RECV + R * 2) + 8 * (sg & 1), (sg >> 1) & 1);
}
template <int R>
__device__ __forceinline__ void x_finish(const uint32_t (&kp)[4], int sg, int h, int mt, int kh, int tid, uint32_t sb) {
    const uint4 r = lds128u(sb + O_RECV + ((sg & 1) * 3 + R) * 2048 + tid * 16);
    uint32_t u0 = add_bf16x2(kp[0], r.x), u1 = add_bf16x2(kp[1], r.y), u2 = add_bf16x2(kp[2], r.z), u3 = add_bf16x2(kp[3], r.w);
    const uint32_t tag = ((sg >> 2) & 1) ^ 1;
    uint4* const hb = &g_kvq[((sg & 3) * 32 + h) * (3 * 512)];
    if (R < 2) {
        const uint32_t m = (tid & 7) ? ~0u : ~1u, t = tag & ~m;
        uint32_t* p = (uint32_t*)hb + (R == 0 ? (kh * 16 + mt) * 64 : 2048 + (mt * 2 + kh) * 128) + (tid & 31);
        asm volatile("{\n.reg .pred p;\nsetp.lt.s32 p, %5, 64;\n@p st.relaxed.gpu.global.b32 [%0], %1;\n@p st.relaxed.gpu.global.b32 [%0+128], %2;\n"
                     "@p st.relaxed.gpu.global.b32 [%0+%6], %3;\n@p st.relaxed.gpu.global.b32 [%0+%7], %4;\n}"
                     ::"l"(p), "r"((u0 & m) | t), "r"((u1 & m) | t), "r"((u2 & m) | t), "r"((u3 & m) | t), "r"(sg),
                       "n"(R == 0 ? 2048 : 256), "n"(R == 0 ? 2176 : 384) : "memory");
    } else {
        asm volatile("{\n.reg .pred p;\nsetp.lt.s32 p, %5, 64;\n@p st.relaxed.gpu.global.v4.b32 [%0], {%1,%2,%3,%4};\n}"
                     ::"l"(hb + R * 512 + (mt * 2 + kh) * 32 + (tid & 31)), "r"((u0 & ~1u) | tag), "r"(u1), "r"(u2), "r"(u3), "r"(sg) : "memory");
    }
}
__device__ __forceinline__ uint32_t tags4(const uint32_t (&r)[4], uint32_t tag) { return orx(orx(orx2(r[0], r[1], tag), r[2], tag), r[3], tag); }

__device__ __forceinline__ uint32_t convert_mem(const unsigned char* redp, int s, int kh, int jj, int w, int lane, uint32_t sb, uint32_t& sf) {
    const uint32_t off = red_grp(jj * 16 + w * 4 + (lane >> 3)), o16 = off + (lane & 7) * 16, o8 = off + 512 + ((lane >> 3) & 1) * 64 + (lane & 7) * 8;
    uint32_t ma = sb + O_MEM + jj * 20480 + (lane >> 4) * 1024 + (lane & 7) * 128 + (((2 * w + ((lane >> 3) & 1)) ^ (lane & 7)) << 4);
    uint32_t a16 = sb + O_STG + o16, a8 = sb + O_STG + o8;
    const uint32_t target = (s & 4) ? 0x42C00000u : 0x42000000u;
    uint32_t n = 0;
    bool redo;
    KEEP2(ma, a16); KEEP2(a8, target);
#pragma unroll 1
    do {
        asm volatile("" : "+r"(n));
        if (n) {
            const unsigned char* pg = redp + (s & 3) * 32768 + __shfl_sync(~0u, kh, 0) * 16384;
            const uint4 x = ldg_rlx128(pg + o16), y = ldg_rlx128(pg + o16 + 128);
            const uint2 z = ldg_rlx64(pg + o8);
            sts128u(a16, x); sts128u(a16 + 128, y); sts64u(a8, z);
            if (n > SPIN_LIMIT) __trap();
        }
        n++;
        mbar_wait(sb + O_BAR + 8 * (R_SPLIT && jj ? B_XF1 : B_RFULL), s & 1);
        const uint4 ra = lds128u(a16), rb = lds128u(a16 + 128);
        const uint2 rc = lds64u(a8);
        stsm4t(ma, ra.x, ra.y, ra.z, __byte_perm(ra.w, rc.x, 0x5410));
        stsm4t(ma + 2048, rb.x, rb.y, rb.z, __byte_perm(rb.w, rc.x, 0x7610));
        redo = __any_sync(~0u, orx(orx2(ra.w, rb.w, target), rc.y, target) > 0xffffu);
    } while (redo);
    if (lane == 0) mbar_arrive(sb + O_BAR + 8 * B_MEM);
    fence_async_smem();
    __syncwarp();
    if (lane == 0) mbar_arrive(sb + O_BAR + 8 * B_QKW);
    return n - 1;
}

#define F16(d, o) F4(d, o), F4(d, o + 4), F4(d, o + 8), F4(d, o + 12)
__device__ __forceinline__ void wg_ss128(float (&d)[64], uint64_t da, uint64_t db, int sc) {
    asm volatile("{\n.reg .pred p;\nsetp.ne.b32 p, %66, 0;\nwgmma.mma_async.sync.aligned.m64n128k16.f32.bf16.bf16 "
                 "{%0,%1,%2,%3,%4,%5,%6,%7,%8,%9,%10,%11,%12,%13,%14,%15,%16,%17,%18,%19,%20,%21,%22,%23,%24,%25,%26,%27,%28,%29,%30,%31,"
                 "%32,%33,%34,%35,%36,%37,%38,%39,%40,%41,%42,%43,%44,%45,%46,%47,%48,%49,%50,%51,%52,%53,%54,%55,%56,%57,%58,%59,%60,%61,%62,%63}, "
                 "%64, %65, p, 1, 1, 1, 1;\n}"
                 : F16(d, 0), F16(d, 16), F16(d, 32), F16(d, 48) : "l"(da), "l"(db), "r"(sc));
}
__device__ __forceinline__ void stg_rlx32(void* p, uint32_t v) { asm volatile("st.relaxed.gpu.global.u32 [%0], %1;" ::"l"(p), "r"(v) : "memory"); }

__global__ void __cluster_dims__(2, 1, 1) __launch_bounds__(512, 1)
rmt_main(const __grid_constant__ CUtensorMap tm_x, const __grid_constant__ CUtensorMap tm_wq, const __grid_constant__ CUtensorMap tm_wk,
         const __grid_constant__ CUtensorMap tm_wv, const __grid_constant__ CUtensorMap tm_wo, const bf16* __restrict__ mem0,
         const Tune tn, const __grid_constant__ FftMaps fm, const __grid_constant__ CUtensorMap tm_o,
         const __grid_constant__ CUtensorMap tm_w2, bf16* __restrict__ out) {
    extern __shared__ __align__(1024) unsigned char smem_raw[];
    const uint32_t sb = smem_u32(smem_raw);
    if ((sb & 0x3FFFF) != SM_BASE) __trap();
    GT(6);
    const int cid = blockIdx.x >> 1, kh = blockIdx.x & 1;
    const int tpc = cid < 4 ? 62 + cid : cid - 4;
    int h, nh;
    if (tpc < 32) { h = (tpc >> 4) * 8 + (tpc & 7); nh = (tpc >> 3) & 1; }
    else if (tpc < 60) { int u = tpc - 32, r = u % 14; h = 16 + (u / 14) * 7 + r % 7; nh = r / 7; }
    else if (tpc < 62) { GT(0); fft_rest((tpc - 60) * 2 + kh, fm, sb, tn.opt); GT(3); return; }
    else { h = 30 + ((tpc - 62) >> 1); nh = tpc & 1; }
    const int j = nh * 2 + kh, role = h * 4 + j;
    const int wgi = __shfl_sync(~0u, threadIdx.x >> 7, 0);
    const int w = __shfl_sync(~0u, (threadIdx.x >> 5) & 3, 0);
    const int tid = threadIdx.x & 127, lane = tid & 31;
#define PIN_IDS() const int tid = __shfl_sync(~0u, threadIdx.x & 127, threadIdx.x & 31), lane = tid & 31
#define OPAQUE_IDS() int tid_ = tid; asm volatile("" : "+r"(tid_)); const int tid = tid_, lane = tid_ & 31; (void)lane
    unsigned char* const redp = (unsigned char*)(((uintptr_t)g_red + 32767) & ~(uintptr_t)32767);
    const uint32_t bars = sb + O_BAR;

    if (threadIdx.x < B_COUNT) {
        const int i = threadIdx.x;
        mbar_init(bars + 8 * i, i == B_XFULL && !X_HALF ? 2 : i < B_QDONE ? 1 : i < B_GE ? 4 : i < B_XPE ? 8 : i < B_QKW ? 12 : 16);
        asm volatile("fence.mbarrier_init.release.cluster;" ::: "memory");
        fence_async_smem();
    } else if (threadIdx.x >= 64 && threadIdx.x < 71) {
        const int i = threadIdx.x - 64;
        const CUtensorMap* m = i == 0 ? &tm_wk : i == 1 ? &tm_wq : i == 2 ? &fm.x : i == 3 ? &tm_x : i == 4 ? &tm_wv : i == 5 ? &tm_wo : &fm.y;
        asm volatile("prefetch.tensormap [%0];" ::"l"(m) : "memory");
    }
    __syncthreads();
    const int wc0 = h * 128 + nh * 64;
#define W_LOAD(i)                                                                                                     \
    if (lane == 0) {                                                                                                  \
        mbar_expect_tx(bars + 8 * (B_W + (i)), 16384);                                                                \
        tma2d(sb + ((i) < 4 ? O_XB : (i) < 8 ? O_WO : O_WV) + ((i) & 3) * 16384, (i) < 4 ? &tm_wk : (i) < 8 ? &tm_wq : &tm_wv, \
              wc0, kh * 512 + ((i) & 3) * 128, bars + 8 * (B_W + (i)));                                               \
    }
#define X_LOAD(dst, sg, u, bar) tma4d(sb + (dst), &tm_x, kh * 8 + (u) * 4, ((sg) & 63) * 4, bars + 8 * (bar))
#define X_REFILL(sg, u) { const int b_ = (X_HALF && (u)) ? B_XF1 : B_XFULL; if (EXP & 1) mbar_arrive(bars + 8 * b_); else { mbar_expect_tx(bars + 8 * b_, 16384); X_LOAD(O_XB + (u) * 20480, sg, u, b_); } }
    const int depth = (tn.opt >> 8) & 15, nearly = 8 + ((tn.opt >> 4) & 7);
    if (wgi == 0 && w == 3) {
        if (lane == 0) {
            mbar_expect_tx(bars + 8 * B_F1, 32768);
            tma_ld4(sb + O_F1, &fm.x, (role & 15) * 64, role >> 4, bars + 8 * B_F1);
        }
#pragma unroll 1
        for (int i = 0; i < nearly; i++) {
            if (i == depth - 2) mbar_wait(bars + 8 * B_F1, 0);
            if (i >= depth) mbar_wait(bars + 8 * (B_W + i - depth), 0);
            W_LOAD(i);
        }
    } else if (wgi == 1 && w == 2 && lane == 0 && role < 4 * (RA + 3)) tma4d_prefetch(&tm_x, j * 4, h * 4);
    GT(7);
    uint32_t mate;
    asm volatile("mapa.shared::cluster.u32 %0, %1, %2;" : "=r"(mate) : "r"(sb), "r"(kh ^ 1));
    if (wgi >= 2) fft_col<false, 1>(role >> 4, role & 15, &fm.x, &fm.y, sb + O_F1, bars + 8 * B_F1, (wgi - 2) * 4 + w, lane, 6);

    if (wgi < 2) {
        asm volatile("setmaxnreg.inc.sync.aligned.u32 176;");
        PIN_IDS();
        uint32_t a[32][4], sf = 0;
        {
            const uint32_t stage = sb + (wgi == 0 ? O_WO : O_XB);
            const uint32_t ad = stage + (((lane >> 4) & 1) * 8 + (lane & 7)) * 128 + (((2 * w + ((lane >> 3) & 1)) ^ (lane & 7)) << 4);
#pragma unroll
            for (int i = 0; i < 4; i++) {
                mbar_wait(bars + 8 * (B_W + 4 * (wgi ^ 1) + i), 0);
#pragma unroll
                for (int ks = 0; ks < 8; ks++) ldsm4t(a[i * 8 + ks], ad + (i * 8 + ks) * 2048);
            }
#pragma unroll
            for (int ks = 0; ks < 32; ks += 2) KEEP2(a[ks][0], a[ks + 1][0]);
            SCHED_FENCE();
            if (lane == 0) mbar_arrive(bars + 8 * (B_QDONE + wgi));
            if (wgi == 0) GT(10); else GT(11);
        }
        asm volatile("barrier.cluster.arrive.relaxed.aligned;" ::: "memory");
        asm volatile("barrier.cluster.wait.acquire.aligned;" ::: "memory");
        uint32_t kp[4];
#define X_PASS(d, dofs)                                                                                    \
        wg_fence();                                                                                        \
        _Pragma("unroll") for (int ks = 0; ks < 32; ks++) { if (ks == 0) wg_rs32<0>(d, a[ks], xdesc(ks) + (dofs)); else wg_rs32<1>(d, a[ks], xdesc(ks) - (ks >> 4) * 256 + (dofs)); } \
        wg_commit();                                                                                       \
        wg_wait<0>();
#define X_FINISH(sg) { if (wgi == 0) x_finish<0>(kp, sg, h, nh * 4 + w, kh, tid, sb); else x_finish<1>(kp, sg, h, nh * 4 + w, kh, tid, sb); }
        mbar_wait(bars + 8 * B_XP, 0);
        if (wgi == 0) GT(8);
#pragma unroll 1
        for (int sg = 0; sg < RA; sg++) {
            float d[16]; uint32_t sn[4];
            X_PASS(d, sg * 2048 - (int)((O_XB - O_WO) >> 4));
            if (sg > 0) {
                if (lane == 0) mbar_arrive(bars + 8 * B_XPE);
                x_wait(wgi, sg - 1, sb); X_FINISH(sg - 1);
            }
            x_split(d, sn, kp, kh);
            x_send(wgi, sn, sg, tid, sb, mate);
        }
        x_wait(wgi, RA - 1, sb); X_FINISH(RA - 1);
        const int lq = wgi == 0 ? 4 : 0;
        const uint32_t xbar = bars + 8 * (wgi ? B_QX : B_OPDONE);
#pragma unroll 1
        for (int s = 0; s < 64; s++) {
            TSI(s);
            uint32_t* ap = (uint32_t*)&g_alpha[((s & 1) * 32 + h) * (3 * 512) + wgi * 512 + ((nh * 4 + w) * 2 + kh) * 32] + lane;
            uint32_t mb0 = sb + O_MEM + (lane & 7) * 128 + (((lane >> 3) ^ (lane & 7)) << 4), mb1 = mb0 ^ 64;
            const uint32_t tag = ((s >> 1) & 1) ^ 1;
            const uint32_t tm = (lane & 7) ? ~0u : ~1u, tt = tag & ~tm;
            {
                float d[16]; uint32_t sn[4];
                mbar_wait(bars + 8 * B_XFULL, s & 1);
                mbar_wait(xbar, s & 1);
                TS(6);
                wg_fence();
#pragma unroll
                for (int ks = 0; ks < 32; ks++) {
                    if (ks == 0) wg_rs32<0>(d, a[ks], xdesc(ks)); else if (!(EXP & 4) || ks >= 8) wg_rs32<1>(d, a[ks], xdesc(ks));
                    if (ks == X_SEQ - 1) wg_commit();
                    if (X_HALF && ks == 15) { mbar_wait(bars + 8 * B_XF1, s & 1); wg_fence(); }
                }
                wg_commit();
                KEEP2(mb0, mb1); KEEPP(ap); KEEP2(tm, tt);
                SCHED_FENCE();
                wg_wait<1>();
                if (tid < lq) mbar_arrive(bars + 8 * B_QX);
                wg_wait<0>();
                TS(7);
                if (lane == 0) mbar_arrive(bars + 8 * B_MEM);
                x_split(d, sn, kp, kh);
                if (!(EXP & 8)) x_send(wgi, sn, s + RA, tid, sb, mate); else { KEEP2(sn[0], sn[1]); KEEP2(sn[2], sn[3]); KEEP2(kp[0], kp[1]); KEEP2(kp[2], kp[3]); }
                TS(4);
            }
            float e[2][4];
#pragma unroll
            for (int i = 0; i < 4; i++) e[0][i] = e[1][i] = 0.f;
            mbar_wait(bars + 8 * B_MEM, s & 1);
            TS(0);
#pragma unroll
            for (int ks = 0; ks < 32; ks += 2) {
                uint32_t b[4];
                ldsm4(b, ((ks & 2) ? mb1 : mb0) + kb_off(ks >> 2));
                mma16816(e[0], a[ks][0], a[ks][1], a[ks][2], a[ks][3], b[0], b[1]);
                mma16816(e[1], a[ks + 1][0], a[ks + 1][1], a[ks + 1][2], a[ks + 1][3], b[2], b[3]);
            }
            TS(2);
            if (QKW_POS == 0) { SCHED_FENCE(); if (lane == 0) mbar_arrive(bars + 8 * B_QKW); }
            stg_rlx32(ap, (pack_bf16(e[0][0] + e[1][0], e[0][1] + e[1][1]) & tm) | tt);
            stg_rlx32(ap + 32, (pack_bf16(e[0][2] + e[1][2], e[0][3] + e[1][3]) & tm) | tt);
            if (QKW_POS == 1 && lane == 0) mbar_arrive(bars + 8 * B_QKW);
            TS(3);
            if (wgi == 1) {
                const uint2* vp = &g_alpha[((s & 1) * 32 + h) * (3 * 512) + 1024 + w * 128 + lane];
                const uint32_t vs = sb + O_VM + tid * 16;
                KEEPP(vp); KEEP2(vs, 0);
                mbar_wait(bars + 8 * B_QST, s & 1);
                uint32_t n, bad;
                asm volatile("ld.shared.u32 %0, [%1];" : "=r"(n) : "r"(bars + 504) : "memory");
                wait_gtime(n + tn.d_v);
                TS(8);
                n = 0;
                do {
                    uint2 va[4];
#pragma unroll
                    for (int i = 0; i < 4; i++) va[i] = ldg_rlx64(vp + i * 32);
                    if (++n > SPIN_LIMIT) __trap();
                    bad = (orx2(va[0].x, va[1].x, tag) | orx2(va[2].x, va[3].x, tag)) & 1;
                    sts128u(vs, make_uint4((add_bf16x2(va[0].x, va[1].x) & ~1u) | ((~s ^ bad) & 1), add_bf16x2(va[0].y, va[1].y),
                                                             add_bf16x2(va[2].x, va[3].x), add_bf16x2(va[2].y, va[3].y)));
                } while (__any_sync(~0u, bad));
                TS(9);
                TSV(16 + w, n - 1);
                LT(s, 4 + w, n - 1);
            }
            if (!(EXP & 8)) {
                x_wait(wgi, s + RA, sb);
                mbar_wait(bars + 8 * FIN_BAR, s & 1);
                X_FINISH(s + RA);
                TS(5);
            }
        }
        sts32(bars + 508, sf);
        TSDUMP();
        asm volatile("bar.arrive 7, 512;" ::: "memory");
        float d[64];
        int st = 0, ph = 0;
#pragma unroll 1
        for (int kt = 0; kt < 64; kt++) {
            mbar_wait(bars + 8 * (B_GF + st), ph);
            if (kt == 0) GT(4);
            const uint64_t da = mkdesc(SM_BASE + st * 32768 + wgi * 8192, 128, 1024, 0), db = mkdesc(SM_BASE + st * 32768 + 16384, 8192, 1024, 1);
            wg_fence();
#pragma unroll
            for (int k = 0; k < 4; k++) wg_ss128(d, da + k * 16, db + k * 128, kt | k);
            wg_commit();
            if (kt > 0) {
                wg_wait<1>();
                if (lane == 0) mbar_arrive(bars + 8 * (B_GE + (st == 0 ? G_ST - 1 : st - 1)));
            }
            if (++st == G_ST) { st = 0; ph ^= 1; }
        }
        wg_wait<0>();
        {
            const uint32_t sl = sb + O_F1 + (wgi * 4 + w) * 4096;
#pragma unroll
            for (int i = 0; i < 8; i++)
                stsm4(sl + (lane & 15) * 256 + (((2 * i + (lane >> 4)) ^ (lane & 7)) << 4), pack_bf16(d[8 * i], d[8 * i + 1]),
                      pack_bf16(d[8 * i + 2], d[8 * i + 3]), pack_bf16(d[8 * i + 4], d[8 * i + 5]), pack_bf16(d[8 * i + 6], d[8 * i + 7]));
            __syncwarp();
            bf16* op = out + (size_t)((role >> 3) * 128 + wgi * 64 + w * 16 + (lane >> 4)) * 2048 + 1024 + (role & 7) * 128 + (lane & 15) * 8;
#pragma unroll
            for (int i = 0; i < 8; i++) {
                const int r = 2 * i + (lane >> 4);
                const uint4 v = lds128u(sl + r * 256 + (((lane & 15) ^ (r & 7)) << 4));
                stg128(op + (size_t)i * 4096, v.x, v.y, v.z, v.w);
            }
        }
        GT(5);
    } else if (wgi == 2) {
        asm volatile("setmaxnreg.dec.sync.aligned.u32 64;");
        PIN_IDS();
        asm volatile("barrier.cluster.arrive.relaxed.aligned;" ::: "memory");
        if (w == 0) {
            mbar_wait(bars + 8 * B_KDONE, 0);
            if (lane == 0) { X_REFILL(RA, 0); X_REFILL(RA, 1); }
            mbar_wait(bars + 8 * B_QDONE, 0);
            if (lane == 0) { mbar_expect_tx(bars + 8 * B_XP, 65536); for (int i = 0; i < 4; i++) X_LOAD(O_WO + i * 16384, i >> 1, i & 1, B_XP); }
#pragma unroll 1
            for (int i = nearly; i < 12; i++) { mbar_wait(bars + 8 * (B_W + i - depth), 0); W_LOAD(i); }
        }
        asm volatile("barrier.cluster.wait.acquire.aligned;" ::: "memory");
#pragma unroll 1
        for (int i = 8; i < 12; i++) mbar_wait(bars + 8 * (B_W + i), 0);
        GT(12);
        uint32_t sf = 0, tref = gtime() - 4000;
        uint32_t* const stp = lane < 8 ? (uint32_t*)g_qst + role * 8 + lane : (uint32_t*)g_stamp + role;
#define STAMP(st) { mbar_wait(bars + 8 * B_MEM, (st) & 1); if (lane < 9) stg_rlx32(stp, gtime()); }
#define V_PASS(d)                                                                                          \
        wg_fence();                                                                                        \
        _Pragma("unroll") for (int ks = 0; ks < 32; ks++) {                                                \
            constexpr uint64_t da0 = mkdesc(SM_BASE + O_WV, 16, 1024, 1);                                  \
            if (ks == 0) wg_ss40<0>(d, da0 + ks * 128, xdesc(ks)); else wg_ss40<1>(d, da0 + ks * 128, xdesc(ks)); \
            if (ks == V_SEQ - 1) wg_commit();                                                              \
        }                                                                                                  \
        wg_commit();                                                                                       \
        if (V_SEQ) wg_wait<1>();                                                                           \
        if (V_SEQ && lane == 0) mbar_arrive(bars + 8 * B_VA);        \
        wg_wait<0>();
        mbar_wait(bars + 8 * B_XP, 0);
        {
            uint32_t kp[4];
#pragma unroll 1
            for (int sg = 0; sg <= RA; sg++) {
                float d[20]; uint32_t sn[4];
                if (sg < RA) {
#pragma unroll
                    for (int i = 0; i < 20; i++) d[i] = 0.f;
#pragma unroll 1
                    for (int kb = 0; kb < 8; kb++) {
                        const uint64_t da = mkdesc(SM_BASE + O_WV, 16, 1024, 1) + kb * 512, db = mkdesc(SM_BASE + O_WO, 16, 4096, 1) + sg * 2048 + (kb >> 2) * 1024 + (kb & 3) * 64;
                        wg_fence();
#pragma unroll
                        for (int i = 0; i < 4; i++) wg_ss40<1>(d, da + i * 128, db + i * 2);
                        wg_commit();
                    }
                    wg_wait<0>();
                }
                if (sg == RA - 1) {
                    if (lane == 0) mbar_arrive(bars + 8 * B_XPE);
                    if (w == 0) {
                        mbar_wait(bars + 8 * B_XPE, 0);
                        GT(9);
                        if (lane == 0) {
                            mbar_expect_tx(bars + 8 * B_WO, 65536);
#pragma unroll
                            for (int i = 0; i < 4; i++) tma2d(sb + O_WO + i * 16384, &tm_wo, j * 256 + i * 64, h * 128, bars + 8 * B_WO);
                        }
                    }
                }
                if (sg > 0) { x_wait(2, sg - 1, sb); x_finish<2>(kp, sg - 1, h, nh * 4 + w, kh, tid, sb); }
                if (sg < RA) { x_split(d, sn, kp, kh); x_send(2, sn, sg, tid, sb, mate); }
            }
        }
        if (STAMP_V && w == 2) STAMP(0);
#pragma unroll 1
        for (int s = 0; s < 64; s++) {
            TSI(s);
            OPAQUE_IDS();
            uint2* ap = &g_alpha[((s & 1) * 32 + h) * (3 * 512) + 1024 + ((nh * 4 + w) * 2 + kh) * 32 + lane];
            KEEPP(ap);
            float d[20];
            mbar_wait(bars + 8 * B_QKW, s & 1);
            TS(0);
            if (s == 0) GT(14);
            V_PASS(d);
            TS(1);
            stg_rlx64(ap, (pack_bf16(d[16], d[17]) & ~1u) | (((s >> 1) & 1) ^ 1), pack_bf16(d[18], d[19]));
            if (lane == 0) mbar_arrive(bars + 8 * B_XEMPTY);
            if (s == 63) break;
            uint32_t sn[4], kp[4];
            x_split(d, sn, kp, kh);
            if (w == 3) {
                uint32_t n = 0, mx;
                do {
                    const uint4 st = ldg_rlx128(&g_stamp[lane]);
                    mx = __reduce_max_sync(~0u, max(max(st.x - tref, st.y - tref), max(st.z - tref, st.w - tref)));
                    if (DBG_TIMING) TSV(14, mx - __reduce_min_sync(~0u, min(min(st.x - tref, st.y - tref), min(st.z - tref, st.w - tref))));
                } while (mx >= 200000u && ++n < 64);
                tref = mx < 200000u ? tref + mx + 1 : gtime();
                TSV(12, clk()); TSV(13, n);
            }
            if (w == 0) {
                mbar_wait(bars + 8 * B_XEMPTY, s & 1);
                mbar_wait(bars + 8 * B_SRDY, s & 1);
                if (lane == 0) { X_REFILL(s + RA + 1, 0); X_REFILL(s + RA + 1, 1); }
            } else if (w == 1) {
                const uint4* hb = &g_kvq[(((s + 1) & 3) * 32 + h) * (3 * 512)];
                if (V_KEEP) { mbar_wait(bars + 8 * B_SRDY, s & 1); wait_clk(clk(), tn.spread); } else mbar_wait(bars + 8 * B_X0, s & 1);
                if (lane == 0) {
                    if (EXP & 2) mbar_arrive(bars + 8 * B_KVFULL); else {
                    mbar_expect_tx(bars + 8 * B_KVFULL, 18432);
                    bulk_g2s(sb + O_KVQ, hb + 512, 16384, bars + 8 * B_KVFULL);
                    bulk_g2s(sb + O_KVQ + 16384, hb + j * 128, 2048, bars + 8 * B_KVFULL);
                    }
                    if (((h ^ s) & 7) == 0 && s < 61 - RA) tma4d_prefetch(&tm_x, j * 4, (s + RA + 3) * 4);
                }
            }
            mbar_wait(bars + 8 * B_OPDONE, (s + 1) & 1);
            if (!(EXP & 8)) x_send(2, sn, s + RA, tid, sb, mate); else { KEEP2(sn[0], sn[1]); KEEP2(sn[2], sn[3]); KEEP2(kp[0], kp[1]); KEEP2(kp[2], kp[3]); }
            if (w == 3) {
                wait_gtime(tref + tn.d_r);
                if (lane <= R_SPLIT) {
                    const uint32_t bytes = 16384 >> R_SPLIT, bar = bars + 8 * (lane ? B_XF1 : B_RFULL);
                    mbar_expect_tx(bar, bytes);
                    bulk_g2s(sb + O_STG + lane * 8192, redp + (s & 3) * 32768 + kh * 16384 + lane * 8192, bytes, bar);
                }
                TSV(3, clk());
            }
            if (!V_LATE && !(EXP & 8)) { x_wait(2, s + RA, sb); x_finish<2>(kp, s + RA, h, nh * 4 + w, kh, tid, sb); TS(6); }
            if (DBG_TIMING && w == 0) { mbar_wait(bars + 8 * B_RFULL, s & 1); TS(4); }
            const uint32_t n = convert_mem(redp, s, kh, 0, w, lane, sb, sf); (void)n;
            TS(5);
            TSV(8 + w, n);
            LT(s, 8 + w, n);
            if (STAMP_V && w == 2) STAMP(s + 1);
            if (V_LATE && !(EXP & 8)) { x_wait(2, s + RA, sb); x_finish<2>(kp, s + RA, h, nh * 4 + w, kh, tid, sb); }
        }
        sts32(bars + 508, sf);
        TSDUMP();
        asm volatile("bar.arrive 7, 512;" ::: "memory");
    } else {
        asm volatile("setmaxnreg.dec.sync.aligned.u32 96;");
        PIN_IDS();
        GT(0);
        asm volatile("barrier.cluster.arrive.relaxed.aligned;" ::: "memory");
#define RED_CLEAR(st)                                                                                           \
        if (lane < 16) {                                                                                        \
            const uint32_t cb = ((st) & 4) ? 0x42800000u : 0u;                                                  \
            stg128(redp + ((st) & 3) * 32768 + role * 256 + lane * 16, 0, (role & 2) ? cb : 0u, 0, cb);        \
        }
        if (w == 0) {
            RED_CLEAR(0); RED_CLEAR(1); RED_CLEAR(2);
            if (lane == 0) { tma_st4(sb + O_F1, &fm.y, (role & 15) * 64, role >> 4); bulk_commit(); }
        }
        sts128u(sb + O_VM + tid * 16, make_uint4(0, 0, 0, 0));
        {
            uint4 v[4];
#pragma unroll
            for (int q = 0; q < 4; q++) v[q] = *(const uint4*)(mem0 + ((lane >> 3) + (q & 1) * 4) * 1024 + kh * 512 + (2 * w + (q >> 1)) * 64 + (lane & 7) * 8);
            mbar_wait(bars + 8 * B_KDONE, 0);
#pragma unroll
            for (int q = 0; q < 4; q++) {
                const int row = (lane >> 3) + (q & 1) * 4;
                sts128u(sb + O_MEM + kb_off(2 * w + (q >> 1)) + row * 128 + (((lane & 7) ^ row) << 4), v[q]);
            }
            fence_async_smem();
            __syncwarp();
            if (lane < 2) { mbar_arrive(bars + 8 * B_MEM); mbar_arrive(bars + 8 * B_QKW); }
            if (lane == 0) mbar_arrive(bars + 8 * B_OPDONE);
            if (tid == 0) mbar_arrive(bars + 8 * B_KVFULL);
        }
        asm volatile("barrier.cluster.wait.acquire.aligned;" ::: "memory");
        if (w == 0) {
            if (lane == 0) bulk_wait_all();
            __syncwarp();
            gbar_wait(&g_start, gbar_arrive(&g_start, 1, 256, lane), 0);
            GT(13);
        }
        if (w == 1) {
            mbar_wait(bars + 8 * (B_W + 10), 0);
            uint32_t t = gtime();
#pragma unroll 1
            for (int i = 0; i < 4; i++) { if (lane == 0) tma2d_prefetch(&tm_wo, j * 256 + i * 64, h * 128); t += tn.extra; if (i < 3) wait_gtime(t); }
        }
        bar_sync(1, 128);
        uint32_t sf = 0, xo[4];
#define XO_STORE(st) { uint32_t* op = (uint32_t*)g_ox + ((size_t)((st) * 4 + j) * 4096 + h * 128 + w * 32) * 4 + lane; op[0] = xo[0]; op[32] = xo[1]; op[64] = xo[2]; op[96] = xo[3]; }
#pragma unroll 1
        for (int s = 0; s < 64; s++) {
            TSI(s);
            OPAQUE_IDS();
            uint32_t kf[4][4], qf[4];
            const uint32_t l03 = lane < 4;
            const uint32_t tg = ((s >> 2) & 1) ^ 1;
            {
                const uint32_t ka = sb + O_KVQ + w * 2048 + lane * 16, qa = sb + O_KVQ + 16384 + w * 512 + lane * 16;
                uint32_t n = s == 0;
                bool redo;
#pragma unroll 1
                do {
                    asm volatile("" : "+r"(n));
                    if (n) {
                        const uint4* hb = &g_kvq[((s & 3) * 32 + __shfl_sync(~0u, h, 0)) * (3 * 512)];
                        uint4 x[4], y[4], z;
                        do {
#pragma unroll
                            for (int i = 0; i < 4; i++) { x[i] = ldg_rlx128(hb + 512 + w * 128 + i * 32 + lane); y[i] = ldg_rlx128(hb + 1024 + w * 128 + i * 32 + lane); }
                            z = ldg_rlx128(hb + j * 128 + w * 32 + lane);
                            if (++n > SPIN_LIMIT) __trap();
                        } while (__any_sync(~0u, (orx2(y[0].x, y[1].x, tg) | orx2(y[2].x, y[3].x, tg)) & 1));
#pragma unroll
                        for (int i = 0; i < 4; i++) { sts128u(ka + i * 512, x[i]); sts128u(ka + 8192 + i * 512, y[i]); }
                        sts128u(qa, z);
                        fence_async_smem();
                    }
                    n++;
                    mbar_wait(bars + 8 * B_KVFULL, s & 1);
#pragma unroll
                    for (int i = 0; i < 4; i++) ldsm4t(kf[i], ka + i * 512);
                    ldsm4t(qf, qa);
                    redo = __any_sync(~0u, or3(or3(tags4(kf[0], tg), tags4(kf[1], tg), tags4(kf[2], tg)), tags4(kf[3], tg), tags4(qf, tg)) & l03 & ((EXP & 10) ? s >> 8 : ~0u));
                } while (redo);
                if (w == 0) TSV(22, n - 1);
            }
            TS(9);
            if (s == 0) GT(15);
            if (s > 0) {
                if (XO_POS == 0) XO_STORE(s - 1);
                const uint32_t n = convert_mem(redp, s - 1, kh, 1, w, lane, sb, sf); (void)n;
                TS(11);
                TSV(16 + w, n);
                LT(s - 1, 12 + w, n);
                if (XO_POS == 1) XO_STORE(s - 1);
                if (w == 1 && s < 62) RED_CLEAR(s + 2);
            }
            const uint32_t tag = ((s >> 1) & 1) ^ 1;
            const uint4* ap = (const uint4*)&g_alpha[((s & 1) * 32 + h) * (3 * 512) + w * 128] + lane;
            const uint32_t l16 = sb + lane * 16, l4 = sb + lane * 4;
            const uint32_t sw = l16 + O_S + w * 2560, sr = l4 + O_S + w * 128;
            uint32_t pw = sb + O_P + ((lane >> 1) & 1) * 704 + (2 * w + (lane >> 4)) * 16 + ((lane >> 2) & 3) * 4 + (lane & 1) * 2;
            int lim = (lane & 2) ? 8 * j + 2 * w + (lane >> 4) - 2 * ((lane >> 2) & 3) - (lane & 1) : 64;
            const uint32_t aa = l16 + O_STG + w * 1024;
            unsigned char* pa = redp + (s & 3) * 32768 + red_grp(j * 16 + (tid >> 3));
            unsigned char* pb = pa + 512 + ((lane >> 3) & 1) * 64 + (lane & 7) * 8;
            pa += (lane & 7) * 16;
            KEEPP(pa); KEEPP(pb);
            KEEP2(l16, l4); KEEP2(pw, lim); KEEP2(sr, 0); KEEP2(l03, tag);
            TS(0);
            if (w == 0) {
                const uint32_t* qp = (const uint32_t*)g_qst + h * 32 + lane;
                KEEPP(qp);
                mbar_wait(bars + 8 * B_MEM, s & 1);
                const uint32_t win = s ? 1024 : 12288;
                uint32_t tq = gtime() - win;
                if (!STAMP_V && lane < 9) stg_rlx32(lane < 8 ? (uint32_t*)g_qst + role * 8 + lane : (uint32_t*)g_stamp + role, tq + win);
                wait_clk(clk(), tn.d_q);
                uint32_t n = 0, mx;
                do { mx = __reduce_max_sync(~0u, ldg_rlx32(qp) - tq); } while (mx > 100000u && ++n < 16);
                TSV(13, n);
                LT(s, 2, n);
                tq += mx <= 100000u ? mx : win;
                if (lane == 0) { sts32(bars + 504, tq); mbar_arrive(bars + 8 * B_QST); }
                TS(14);
                mbar_wait(bars + 8 * B_QKW, s & 1);
                TS(1);
                wait_gtime(tq + tn.d_alpha);
                if (lane == 0) {
                    mbar_expect_tx(bars + 8 * B_AFULL, 8192);
                    bulk_g2s(sb + O_STG, ap, 8192, bars + 8 * B_AFULL);
                }
                if (s == 0) { mbar_wait(bars + 8 * B_WO, 0); GT(1); }
            }
            {
                uint32_t n = 0;
                bool redo;
#pragma unroll 1
                do {
                    asm volatile("" : "+r"(n));
                    if (n) {
                        uint4 x[4];
#pragma unroll
                        for (int q = 0; q < 4; q++) x[q] = ldg_rlx128(ap + (q >> 1) * 256 + (q & 1) * 32);
#pragma unroll
                        for (int q = 0; q < 4; q++) sts128u(aa + (q >> 1) * 4096 + (q & 1) * 512, x[q]);
                        __syncwarp();
                        if (n > SPIN_LIMIT) __trap();
                    }
                    n++;
                    mbar_wait(bars + 8 * B_AFULL, s & 1);
                    TS(12);
                    if (V_SEQ) mbar_wait(bars + 8 * B_VA, s & 1);
                    uint32_t qa[2][4], ka[2][4];
#pragma unroll
                    for (int u = 0; u < 2; u++) { ldsm4t(qa[u], aa + u * 512); ldsm4t(ka[u], aa + 4096 + u * 512); }
                    float sa[5][4];
#pragma unroll
                    for (int i = 0; i < 5; i++) sa[i][0] = sa[i][1] = sa[i][2] = sa[i][3] = 0.f;
#pragma unroll
                    for (int u = 0; u < 2; u++) {
                        const uint32_t q0 = add_bf16x2(qa[u][0], qa[u][2]), q1 = add_bf16x2(qa[u][1], qa[u][3]);
                        mma16816(sa[1], q0, qf[2 * u], q1, qf[2 * u + 1], kf[2 * u][0], kf[2 * u][1]);
                        mma16816(sa[2], q0, qf[2 * u], q1, qf[2 * u + 1], kf[2 * u][2], kf[2 * u][3]);
                        mma16816(sa[3], q0, qf[2 * u], q1, qf[2 * u + 1], kf[2 * u + 1][0], kf[2 * u + 1][1]);
                        mma16816(sa[4], q0, qf[2 * u], q1, qf[2 * u + 1], kf[2 * u + 1][2], kf[2 * u + 1][3]);
                        const uint32_t k0 = add_bf16x2(ka[u][0], ka[u][2]), k1 = add_bf16x2(ka[u][1], ka[u][3]);
                        mma16816(sa[0], q0, qf[2 * u], q1, qf[2 * u + 1], k0, k1);
                        if (u == 0) SCHED_FENCE();
                    }
                    redo = __any_sync(~0u, (or3(tags4(qa[0], tag), tags4(ka[0], tag), tags4(qa[1], tag)) | tags4(ka[1], tag)) & l03);
#pragma unroll
                    for (int i = 1; i <= 5; i++) sts128(sw + (i % 5) * 512, sa[i % 5][0], sa[i % 5][1], sa[i % 5][2], sa[i % 5][3]);
                } while (redo);
                if (w == 0) TSV(20, n - 1);
                if (n > 1) LT(s, 3, 0x10000 + s);
            }
            TS(2);
            bar_sync(1, 128);
            float sc[5];
            {
                float x[4][5];
#pragma unroll
                for (int q = 0; q < 4; q++)
#pragma unroll
                    for (int n = 0; n < 5; n++) asm volatile("ld.shared.f32 %0, [%1];" : "=f"(x[q][n]) : "r"(sr + q * 2560 + n * 512) : "memory");
#pragma unroll
                for (int n = 0; n < 5; n++) sc[n] = (x[0][n] + x[1][n]) + (x[2][n] + x[3][n]);
            }
            TS(15);
#pragma unroll
            for (int n = 1; n < 5; n++) if (8 * (n - 1) > lim) sc[n] = MASK_VAL;
            float m = fmaxf(fmaxf(fmaxf(sc[0], sc[1]), fmaxf(sc[2], sc[3])), sc[4]);
            m = fmaxf(m, __shfl_xor_sync(~0u, m, 1));
            m = fmaxf(m, __shfl_xor_sync(~0u, m, 4));
            m = fmaxf(m, __shfl_xor_sync(~0u, m, 8));
            SCHED_FENCE();
            uint4 vf[4];
#pragma unroll
            for (int i = 0; i < 4; i++) vf[i] = lds128u(l16 + O_KVQ + 8192 + w * 2048 + i * 512);
            m *= -SM_SCALE_LOG2;
#pragma unroll
            for (int n = 0; n < 5; n++) {
                const uint32_t pv = pack_bf16(ex2(fmaf(sc[n], SM_SCALE_LOG2, m)), 0.f);
                asm volatile("st.shared.u16 [%0], %1;" ::"r"(pw + n * 128), "h"((uint16_t)pv) : "memory");
            }
            if (V_KEEP) { KEEP2(vf[0].x, vf[1].x); KEEP2(vf[2].x, vf[3].x); SCHED_FENCE(); }
            bar_sync(1, 128);
            TS(3);
            if (lane == 0) mbar_arrive(bars + 8 * B_SRDY);
            float ox[2][4], sm[4], sx[4], cc[4][4];
#pragma unroll 1
            for (uint32_t nv = 0;; nv++) {
                uint32_t pf[4], p0, px[4], px0;
                ldsm4(pf, l16 + O_P + 128);
                ldsm4(px, l16 + O_P + 128 + 704);
                asm volatile("ld.shared.u32 %0, [%1];" : "=r"(p0) : "r"(l4 + O_P) : "memory");
                asm volatile("ld.shared.u32 %0, [%1];" : "=r"(px0) : "r"(l4 + O_P + 704) : "memory");
                float o[2][4];
#pragma unroll
                for (int i = 0; i < 4; i++) o[0][i] = o[1][i] = ox[0][i] = ox[1][i] = sm[i] = sx[i] = 0.f;
                constexpr uint32_t ONE2 = 0x3f803f80u;
                mma1688(sm, ONE2, ONE2, p0);
                mma1688(sx, ONE2, ONE2, px0);
#pragma unroll
                for (int c = 0; c < 2; c++) {
#pragma unroll
                    for (int u = 0; u < 2; u++) mma16816(o[u], vf[2 * u + c].x, vf[2 * u + c].y, vf[2 * u + c].z, vf[2 * u + c].w, pf[2 * c], pf[2 * c + 1]);
#pragma unroll
                    for (int u = 0; u < 2; u++) mma16816(ox[u], vf[2 * u + c].x, vf[2 * u + c].y, vf[2 * u + c].z, vf[2 * u + c].w, px[2 * c], px[2 * c + 1]);
                    mma16816(sm, ONE2, ONE2, ONE2, ONE2, pf[2 * c], pf[2 * c + 1]);
                    mma16816(sx, ONE2, ONE2, ONE2, ONE2, px[2 * c], px[2 * c + 1]);
                }
                const uint32_t vbad = orx(orx(orx2(vf[0].x, vf[1].x, tg), vf[2].x, tg), vf[3].x, tg);
                uint4 vm;
                {
                    uint32_t n = 0;
                    bool redo;
#pragma unroll 1
                    do {
                        vm = lds128v(l16 + O_VM + w * 512);
                        float o2[2][4];
#pragma unroll
                        for (int i = 0; i < 4; i++) { o2[0][i] = o[0][i]; o2[1][i] = o[1][i]; }
                        mma1688(o2[0], vm.x, vm.y, p0);
                        mma1688(o2[1], vm.z, vm.w, p0);
                        redo = __any_sync(~0u, ((vm.x ^ ~s) & 1) && ++n < SPIN_LIMIT);
                        const uint32_t oa = l4 + O_O + w * 512;
                        sts32(oa, pack_bf16(o2[0][0], o2[0][1]));
                        sts32(oa + 128, pack_bf16(o2[0][2], o2[0][3]));
                        sts32(oa + 256, pack_bf16(o2[1][0], o2[1][1]));
                        sts32(oa + 384, pack_bf16(o2[1][2], o2[1][3]));
                    } while (redo);
                    if (w == 0) TSV(21, n);
                }
                TS(4);
                fence_async_smem();
                mma1688(ox[0], vm.x, vm.y, px0);
                mma1688(ox[1], vm.z, vm.w, px0);
                sm[0] = rcp(sm[0]); sm[1] = rcp(sm[1]);
                bar_sync(1, 128);
                if (!V_KEEP && lane == 0 && nv == 0) mbar_arrive(bars + 8 * B_X0);
                TS(5);
#define OP_ISSUE(t0, t1)                                                                                       \
                wg_fence();                                                                                    \
                _Pragma("unroll") for (int ks = 0; ks < 8; ks++)                                               \
                    _Pragma("unroll") for (int t = t0; t < t1; t++) {                                          \
                        constexpr uint64_t da0 = mkdesc(SM_BASE + O_WO, 16, 1024, 1), db0 = mkdesc(SM_BASE + O_O, 128, 128, 0); \
                        if (ks == 0) wg_ss8<0>(cc[t], da0 + t * 1024, db0); else wg_ss8<1>(cc[t], da0 + t * 1024 + ks * 128, db0 + ks * 16); \
                    }                                                                                          \
                wg_commit();
                OP_ISSUE(0, (OP_SPLIT ? 2 : 4));
                if (!bar_or(1, 128, vbad & ((EXP & 10) ? s >> 8 : ~0u))) break;
                wg_wait<0>();
                const uint4* vq = &g_kvq[((s & 3) * 32 + h) * (3 * 512) + 1024 + w * 128 + __shfl_sync(~0u, lane, lane)];
#pragma unroll
                for (int i = 0; i < 4; i++) { vf[i] = ldg_rlx128(vq + i * 32); }
                KEEP2(vf[0].x, vf[1].x); KEEP2(vf[2].x, vf[3].x);
                SCHED_FENCE();
                if (nv > SPIN_LIMIT) __trap();
                bar_sync(1, 128);
            }
            {
                const float i0 = sm[0], i1 = sm[1];
#pragma unroll
                for (int hf = 0; hf < 2; hf++) {
                    if (hf == 0 || OP_SPLIT) wg_wait<0>();
                    if (hf == 0) TS(6);
                    if (OPD_EARLY && hf == OP_SPLIT && lane == 0) mbar_arrive(bars + 8 * B_OPDONE);
                    asm volatile("red.relaxed.gpu.global.add.noftz.v4.bf16x2 [%0], {%1,%2,%3,%4};" ::"l"(pa + hf * 128),
                                 "r"(pack_bf16(cc[2 * hf][0] * i0, cc[2 * hf][1] * i1)), "r"(pack_bf16(cc[2 * hf][2] * i0, cc[2 * hf][3] * i1)),
                                 "r"(pack_bf16(cc[2 * hf + 1][0] * i0, cc[2 * hf + 1][1] * i1)), "r"(pack_bf16(cc[2 * hf + 1][2] * i0, 1.f)) : "memory");
                    if (OP_SPLIT && hf == 0) { SCHED_FENCE(); OP_ISSUE(2, 4); }
                }
                asm volatile("red.relaxed.gpu.global.add.noftz.v2.bf16x2 [%0], {%1,%2};" ::"l"(pb), "r"(pack_bf16(cc[1][3] * i1, cc[3][3] * i1)), "r"(0x3f800000u) : "memory");
                if (!OPD_EARLY && lane == 0) mbar_arrive(bars + 8 * B_OPDONE);
                SCHED_FENCE();
                TS(7);
            }
            {
                const float ix0 = rcp(sx[0]), ix1 = rcp(sx[1]);
                xo[0] = pack_bf16(ox[0][0] * ix0, ox[0][1] * ix1); xo[1] = pack_bf16(ox[0][2] * ix0, ox[0][3] * ix1);
                xo[2] = pack_bf16(ox[1][0] * ix0, ox[1][1] * ix1); xo[3] = pack_bf16(ox[1][2] * ix0, ox[1][3] * ix1);
                if (XO_POS == 2) XO_STORE(s);
            }
            TS(8);
            if (w == 2) { LT(s, 0, gtime()); LT(s, 1, clk()); }
            if (s == 0) GT(2);
        }
        if (XO_POS < 2) XO_STORE(63);
        GT(3);
        sts32(bars + 508, sf);
        TSDUMP();
        bar_sync(7, 512);
        const int m0 = (role >> 3) * 16, nb = (role & 7) * 2;
#define W2_LOAD(st, kt) { mbar_expect_tx(bars + 8 * (B_GF + (st)), 32768); tma3d(sb + (st) * 32768 + 16384, &tm_w2, 0, (kt) * 64, nb, bars + 8 * (B_GF + (st))); }
        if (w == 1 && lane == 0) {
            fence_async_smem();
#pragma unroll 1
            for (int kt = 0; kt < G_ST; kt++) W2_LOAD(kt, kt);
        }
        if (w == 0) {
            gbar_wait(&g_end, gbar_arrive(&g_end, 1, 128, lane), 0);
            int st = 0, ph = 1;
#pragma unroll 1
            for (int kt = 0; kt < 64; kt++) {
                if (kt >= G_ST) mbar_wait(bars + 8 * (B_GE + st), ph);
                if (lane == 0) {
                    if (kt >= G_ST) W2_LOAD(st, kt);
                    tma2d(sb + st * 32768, &tm_o, kt * 128, m0, bars + 8 * (B_GF + st));
                }
                if (++st == G_ST) { st = 0; ph ^= 1; }
            }
        }
    }
}

typedef CUresult (*EncodeFn)(CUtensorMap*, CUtensorMapDataType, cuuint32_t, void*, const cuuint64_t*, const cuuint64_t*,
                             const cuuint32_t*, const cuuint32_t*, CUtensorMapInterleave, CUtensorMapSwizzle,
                             CUtensorMapL2promotion, CUtensorMapFloatOOBfill);

static void make_map(EncodeFn fn, CUtensorMap* m, const void* p, uint64_t cols, uint64_t rows, uint32_t bc, uint32_t br) {
    cuuint64_t dims[2] = {cols, rows}, strides[1] = {cols * 2};
    cuuint32_t box[2] = {bc, br}, es[2] = {1, 1};
    fn(m, CU_TENSOR_MAP_DATA_TYPE_BFLOAT16, 2, (void*)p, dims, strides, box, es, CU_TENSOR_MAP_INTERLEAVE_NONE,
       CU_TENSOR_MAP_SWIZZLE_128B, CU_TENSOR_MAP_L2_PROMOTION_L2_128B, CU_TENSOR_MAP_FLOAT_OOB_FILL_NONE);
}

static Tune h_tune = {480, 1888, 16 * 2 + 256 * 4, 100, 960, 300, 600};

extern "C" void kernel_launch(void* const* d_in, const int* in_sizes, int n_in, void* d_out, int out_size) {
    static bool init = false;
    static FftMaps fm;
    static CUtensorMap tm_x, tm_wq, tm_wk, tm_wv, tm_wo, tm_o, tm_wo2;
    if (!init) {
        void* fp = nullptr; cudaDriverEntryPointQueryResult qr;
        cudaGetDriverEntryPoint("cuTensorMapEncodeTiled", &fp, cudaEnableDefault, &qr);
        EncodeFn fn = (EncodeFn)fp;
        void* ox = nullptr; cudaGetSymbolAddress(&ox, g_ox);
        {
            cuuint64_t dims[4] = {64, 8, 16, 256}, strides[3] = {2048, 128, 16384};
            cuuint32_t box[4] = {64, 8, 4, 4}, es[4] = {1, 1, 1, 1};
            fn(&tm_x, CU_TENSOR_MAP_DATA_TYPE_BFLOAT16, 4, d_in[3], dims, strides, box, es, CU_TENSOR_MAP_INTERLEAVE_NONE,
               CU_TENSOR_MAP_SWIZZLE_128B, CU_TENSOR_MAP_L2_PROMOTION_L2_128B, CU_TENSOR_MAP_FLOAT_OOB_FILL_NONE);
        }
        void* fy = nullptr; cudaGetSymbolAddress(&fy, g_fy);
        for (int i = 0; i < 3; i++) {
            const cuuint64_t pitch = i == 2 ? 4096 : 2048;
            cuuint64_t dims[4] = {1024, 8, 16, 16}, strides[3] = {pitch, 128 * pitch, 8 * pitch};
            cuuint32_t box[4] = {64, 1, 16, 16}, es[4] = {1, 1, 1, 1};
            fn(i == 0 ? &fm.x : i == 1 ? &fm.y : &fm.o, CU_TENSOR_MAP_DATA_TYPE_BFLOAT16, 4, i == 0 ? d_in[0] : i == 1 ? fy : d_out, dims, strides, box, es,
               CU_TENSOR_MAP_INTERLEAVE_NONE, CU_TENSOR_MAP_SWIZZLE_128B, CU_TENSOR_MAP_L2_PROMOTION_L2_256B, CU_TENSOR_MAP_FLOAT_OOB_FILL_NONE);
        }
        {
            cuuint64_t dims[3] = {64, 2048, 16}, strides[2] = {2048, 128};
            cuuint32_t box[3] = {64, 8, 16}, es[3] = {1, 1, 1};
            fn(&fm.y2, CU_TENSOR_MAP_DATA_TYPE_BFLOAT16, 3, fy, dims, strides, box, es, CU_TENSOR_MAP_INTERLEAVE_NONE,
               CU_TENSOR_MAP_SWIZZLE_128B, CU_TENSOR_MAP_L2_PROMOTION_L2_128B, CU_TENSOR_MAP_FLOAT_OOB_FILL_NONE);
        }
        for (int i = 0; i < 2; i++) {
            cuuint64_t dims[3] = {256 * 513 - 448, 8, 8}, strides[2] = {128, 256 * 1026};
            cuuint32_t box[3] = {72, 8, 8}, es[3] = {1, 1, 1};
            fn(i ? &fm.wi : &fm.wr, CU_TENSOR_MAP_DATA_TYPE_BFLOAT16, 3, d_in[1 + i], dims, strides, box, es, CU_TENSOR_MAP_INTERLEAVE_NONE,
               CU_TENSOR_MAP_SWIZZLE_NONE, CU_TENSOR_MAP_L2_PROMOTION_L2_128B, CU_TENSOR_MAP_FLOAT_OOB_FILL_NONE);
        }
        fm.w[0] = (const unsigned char*)d_in[1]; fm.w[1] = (const unsigned char*)d_in[2]; fm.w[2] = (const unsigned char*)d_in[3];
        make_map(fn, &tm_wq, d_in[5], 4096, 1024, 64, 128);
        make_map(fn, &tm_wk, d_in[6], 4096, 1024, 64, 128);
        make_map(fn, &tm_wv, d_in[7], 4096, 1024, 64, 128);
        make_map(fn, &tm_wo, d_in[8], 1024, 4096, 64, 128);
        {
            cuuint64_t dims[2] = {8192, 256}, strides[1] = {65536};
            cuuint32_t box[2] = {128, 16}, es[2] = {1, 1};
            fn(&tm_o, CU_TENSOR_MAP_DATA_TYPE_UINT64, 2, ox, dims, strides, box, es, CU_TENSOR_MAP_INTERLEAVE_NONE,
               CU_TENSOR_MAP_SWIZZLE_NONE, CU_TENSOR_MAP_L2_PROMOTION_L2_128B, CU_TENSOR_MAP_FLOAT_OOB_FILL_NONE);
        }
        {
            cuuint64_t dims[3] = {64, 4096, 16}, strides[2] = {2048, 128};
            cuuint32_t box[3] = {64, 64, 2}, es[3] = {1, 1, 1};
            fn(&tm_wo2, CU_TENSOR_MAP_DATA_TYPE_BFLOAT16, 3, d_in[8], dims, strides, box, es, CU_TENSOR_MAP_INTERLEAVE_NONE,
               CU_TENSOR_MAP_SWIZZLE_128B, CU_TENSOR_MAP_L2_PROMOTION_L2_128B, CU_TENSOR_MAP_FLOAT_OOB_FILL_NONE);
        }
        cudaFuncSetAttribute(rmt_main, cudaFuncAttributeMaxDynamicSharedMemorySize, MAIN_SMEM);
        init = true;
    }
    rmt_main<<<132, 512, MAIN_SMEM>>>(tm_x, tm_wq, tm_wk, tm_wv, tm_wo, (const bf16*)d_in[4], h_tune, fm, tm_o, tm_wo2, (bf16*)d_out);
}
```
